```python
import torch

def _softmax(x, axis=-1):
    return torch.softmax(x, dim=axis)
def _gelu(x):
    return torch.nn.functional.gelu(x, approximate="tanh")
def _silu(x):
    return torch.nn.functional.silu(x)
def _sigmoid(x):
    return torch.sigmoid(x)
def _layernorm(x, axis=-1, eps=1e-5):
    m = x.mean(dim=axis, keepdim=True)
    v = x.var(dim=axis, keepdim=True, unbiased=False)
    return (x - m) / torch.sqrt(v + eps)
def _scatter_add(tgt, idx, src, axis=0):
    return tgt.clone().index_add_(axis, idx, src)
def _segment_sum(src, seg, n):
    out = torch.zeros((n,) + src.shape[1:], dtype=src.dtype)
    return out.index_add_(0, seg, src)
def _pad(x, pw):
    flat = tuple(v for pair in reversed(pw) for v in pair)
    return torch.nn.functional.pad(x, flat)

kernel_name = 'standalone__sequential_behavior_din__recsys'

def setup_inputs():

    _w = (lambda a: (lambda t: t.to(torch.bfloat16) if t.is_floating_point() else t)(torch.as_tensor(a)))
    B, L, D = 16384, 200, 64
    H = D
    return {
        "target": _w((lambda *s: torch.randn(*s, dtype=torch.bfloat16) * 1.6)(B, D)),
        "hist": _w((lambda *s: torch.randn(*s, dtype=torch.bfloat16) * 1.6)(B, L, D)),
        "mask": _w((lambda lo, hi, *s: torch.randint(lo, hi, s))(0, 2, B, L).to(float)),
        "w1": _w((lambda *s: torch.randn(*s, dtype=torch.bfloat16) * 1.6)(4 * D, H) * (4 * D) ** -0.5),
        "b1": _w((lambda *s: torch.randn(*s, dtype=torch.bfloat16) * 1.6)(H) * 0.1),
        "w2": _w((lambda *s: torch.randn(*s, dtype=torch.bfloat16) * 0.05)(H, 1) * H ** -0.5),
        "b2": _w((lambda *s: torch.randn(*s, dtype=torch.bfloat16) * 0.05)(1) * 0.1),
    }

def reference(target, hist, mask, w1, b1, w2, b2):
    L = hist.shape[1]
    tgt = (lambda x, n, axis: torch.repeat_interleave(x, n, dim=axis))(target[:, None, :], L, axis=1)
    feat = torch.concatenate([hist, tgt, hist - tgt, hist * tgt], axis=-1)
    h = _sigmoid(feat @ w1 + b1)
    scores = (h @ w2 + b2)[..., 0] * mask
    return torch.einsum('bl,bld->bd', scores, hist)
```

```cpp
#include <cuda_runtime.h>
#include <cuda_bf16.h>
#include <stdint.h>

namespace din {

constexpr int kL = 200, kD = 64;
#define NCW 3
#define NSLOT 3
constexpr int CHUNK = 128;
constexpr int NTHREADS = NCW * 128 + 128;
#define PREGS 56
#define CREGS 152
constexpr int PROD_REGS = PREGS, CONS_REGS = CREGS;
#define PF_ROWS 8
#define PF_FAST 10
#define PF_SLOW 2000
#define PF_CYCLES 280
#define RED_SLEEP 40
#define K_SEL 0
#define K_FIRST 0
#define K_LAST 0
#define K_LO 1
#define K_HI1 1
#define K_HI2 1
#define K_ADV 0
#define KL 2
#define KM 0
#define GA 1
#define GW4 1
#define SPLIT 1
#define SA 2
#define SB 1
#define EARLY 4
#define PIN2 1
#define SPREAD 80
#define SPREAD_UP 400
#define DOFF 0
#define BQE 0
#define TP 0
#define LC 1
#define EA 1
#define K0 3
#define WP 0
#define GATE_HALF "hi, hi"
#define SLOW_ROUNDS 16
#define SLOW_BY 7
#define PF_EARLY 3
constexpr int NSTATIC = 2;
constexpr int S_TGT = CHUNK * 128;
constexpr int S_HDR = S_TGT + 128;
constexpr int S_FULL = S_HDR + 8;
constexpr int S_EMPTY = S_HDR + 16;
constexpr int S_ROW = S_HDR + 24;
constexpr int S_REST = S_HDR + 32;
constexpr int S_MASK = S_TGT + 256;
constexpr int S_OUT = S_TGT + 1024;
constexpr int SLOT_BYTES = S_OUT + 8192;
constexpr int RING_BYTES_ = NSLOT * SLOT_BYTES;
constexpr int R_PACE = 2 * RING_BYTES_ + S_TGT + 768;
constexpr int R_STOP = S_HDR + 44;
constexpr int R_LIST = S_TGT + 512;
constexpr int R_VEC = S_TGT + 768;
constexpr int R_SEL = S_TGT + 896;
constexpr int R_CARRY = SLOT_BYTES + S_TGT + 512;
constexpr int R_TGT0 = (NSLOT - 1) * SLOT_BYTES + S_OUT;
constexpr int RING_BYTES = NSLOT * SLOT_BYTES;
constexpr int SMEM_BYTES = NCW * RING_BYTES + 1024;
__device__ constexpr int w1_at(int i) { return (i >> 1) * RING_BYTES + (i & 1) * SLOT_BYTES + S_OUT; }
#define LOGT(slot)
static_assert(SMEM_BYTES <= 232448, "shared memory");
constexpr uint32_t H_GENERAL = 1u << 17, H_FINAL = 1u << 18, H_SELF = 1u << 19;
constexpr uint32_t ROW_REST = 1u << 30, ROW_MORE = 1u << 31;

__device__ unsigned int g_next;

#define STAMP(k)

#define DURT(sign)
#define STR2(x) #x
#define STR(x) STR2(x)
constexpr int NA = 5;
__device__ __forceinline__ void sel_clr(float (&d)[20], const uint32_t (&a)[4], uint32_t lo, uint32_t hi) {
  asm volatile("{\n.reg .b64 db;\n.reg .b32 lo, hi;\n"
    "mov.b32 hi, %25;\n"
    "add.u32 lo, %24, 0;\nmov.b64 db, {lo, hi};\n"
    "wgmma.mma_async.sync.aligned.m64n40k16.f32.bf16.bf16 {%0, %1, %2, %3, %4, %5, %6, %7, %8, %9, %10, %11, %12, %13, %14, %15, %16, %17, %18, %19}, {%20, %21, %22, %23}, db, 0, 1, 1, 0;\n"
    "}\n"
    : "=f"(d[0]), "=f"(d[1]), "=f"(d[2]), "=f"(d[3]), "=f"(d[4]), "=f"(d[5]), "=f"(d[6]), "=f"(d[7]), "=f"(d[8]), "=f"(d[9]), "=f"(d[10]), "=f"(d[11]), "=f"(d[12]), "=f"(d[13]), "=f"(d[14]), "=f"(d[15]), "=f"(d[16]), "=f"(d[17]), "=f"(d[18]), "=f"(d[19])
    : "r"(a[0]), "r"(a[1]), "r"(a[2]), "r"(a[3]), "r"(lo), "r"(hi)
    : "memory");
}
__device__ __forceinline__ void sel_clr(float (&d)[24], const uint32_t (&a)[4], uint32_t lo, uint32_t hi) {
  asm volatile("{\n.reg .b64 db;\n.reg .b32 lo, hi;\n"
    "mov.b32 hi, %29;\n"
    "add.u32 lo, %28, 0;\nmov.b64 db, {lo, hi};\n"
    "wgmma.mma_async.sync.aligned.m64n48k16.f32.bf16.bf16 {%0, %1, %2, %3, %4, %5, %6, %7, %8, %9, %10, %11, %12, %13, %14, %15, %16, %17, %18, %19, %20, %21, %22, %23}, {%24, %25, %26, %27}, db, 0, 1, 1, 0;\n"
    "}\n"
    : "=f"(d[0]), "=f"(d[1]), "=f"(d[2]), "=f"(d[3]), "=f"(d[4]), "=f"(d[5]), "=f"(d[6]), "=f"(d[7]), "=f"(d[8]), "=f"(d[9]), "=f"(d[10]), "=f"(d[11]), "=f"(d[12]), "=f"(d[13]), "=f"(d[14]), "=f"(d[15]), "=f"(d[16]), "=f"(d[17]), "=f"(d[18]), "=f"(d[19]), "=f"(d[20]), "=f"(d[21]), "=f"(d[22]), "=f"(d[23])
    : "r"(a[0]), "r"(a[1]), "r"(a[2]), "r"(a[3]), "r"(lo), "r"(hi)
    : "memory");
}
__device__ __forceinline__ void sel_clr(float (&d)[28], const uint32_t (&a)[4], uint32_t lo, uint32_t hi) {
  asm volatile("{\n.reg .b64 db;\n.reg .b32 lo, hi;\n"
    "mov.b32 hi, %33;\n"
    "add.u32 lo, %32, 0;\nmov.b64 db, {lo, hi};\n"
    "wgmma.mma_async.sync.aligned.m64n56k16.f32.bf16.bf16 {%0, %1, %2, %3, %4, %5, %6, %7, %8, %9, %10, %11, %12, %13, %14, %15, %16, %17, %18, %19, %20, %21, %22, %23, %24, %25, %26, %27}, {%28, %29, %30, %31}, db, 0, 1, 1, 0;\n"
    "}\n"
    : "=f"(d[0]), "=f"(d[1]), "=f"(d[2]), "=f"(d[3]), "=f"(d[4]), "=f"(d[5]), "=f"(d[6]), "=f"(d[7]), "=f"(d[8]), "=f"(d[9]), "=f"(d[10]), "=f"(d[11]), "=f"(d[12]), "=f"(d[13]), "=f"(d[14]), "=f"(d[15]), "=f"(d[16]), "=f"(d[17]), "=f"(d[18]), "=f"(d[19]), "=f"(d[20]), "=f"(d[21]), "=f"(d[22]), "=f"(d[23]), "=f"(d[24]), "=f"(d[25]), "=f"(d[26]), "=f"(d[27])
    : "r"(a[0]), "r"(a[1]), "r"(a[2]), "r"(a[3]), "r"(lo), "r"(hi)
    : "memory");
}
__device__ __forceinline__ void sel_clr(float (&d)[32], const uint32_t (&a)[4], uint32_t lo, uint32_t hi) {
  asm volatile("{\n.reg .b64 db;\n.reg .b32 lo, hi;\n"
    "mov.b32 hi, %37;\n"
    "add.u32 lo, %36, 0;\nmov.b64 db, {lo, hi};\n"
    "wgmma.mma_async.sync.aligned.m64n64k16.f32.bf16.bf16 {%0, %1, %2, %3, %4, %5, %6, %7, %8, %9, %10, %11, %12, %13, %14, %15, %16, %17, %18, %19, %20, %21, %22, %23, %24, %25, %26, %27, %28, %29, %30, %31}, {%32, %33, %34, %35}, db, 0, 1, 1, 0;\n"
    "}\n"
    : "=f"(d[0]), "=f"(d[1]), "=f"(d[2]), "=f"(d[3]), "=f"(d[4]), "=f"(d[5]), "=f"(d[6]), "=f"(d[7]), "=f"(d[8]), "=f"(d[9]), "=f"(d[10]), "=f"(d[11]), "=f"(d[12]), "=f"(d[13]), "=f"(d[14]), "=f"(d[15]), "=f"(d[16]), "=f"(d[17]), "=f"(d[18]), "=f"(d[19]), "=f"(d[20]), "=f"(d[21]), "=f"(d[22]), "=f"(d[23]), "=f"(d[24]), "=f"(d[25]), "=f"(d[26]), "=f"(d[27]), "=f"(d[28]), "=f"(d[29]), "=f"(d[30]), "=f"(d[31])
    : "r"(a[0]), "r"(a[1]), "r"(a[2]), "r"(a[3]), "r"(lo), "r"(hi)
    : "memory");
}
__device__ __forceinline__ void sel_clr(float (&d)[36], const uint32_t (&a)[4], uint32_t lo, uint32_t hi) {
  asm volatile("{\n.reg .b64 db;\n.reg .b32 lo, hi;\n"
    "mov.b32 hi, %41;\n"
    "add.u32 lo, %40, 0;\nmov.b64 db, {lo, hi};\n"
    "wgmma.mma_async.sync.aligned.m64n72k16.f32.bf16.bf16 {%0, %1, %2, %3, %4, %5, %6, %7, %8, %9, %10, %11, %12, %13, %14, %15, %16, %17, %18, %19, %20, %21, %22, %23, %24, %25, %26, %27, %28, %29, %30, %31, %32, %33, %34, %35}, {%36, %37, %38, %39}, db, 0, 1, 1, 0;\n"
    "}\n"
    : "=f"(d[0]), "=f"(d[1]), "=f"(d[2]), "=f"(d[3]), "=f"(d[4]), "=f"(d[5]), "=f"(d[6]), "=f"(d[7]), "=f"(d[8]), "=f"(d[9]), "=f"(d[10]), "=f"(d[11]), "=f"(d[12]), "=f"(d[13]), "=f"(d[14]), "=f"(d[15]), "=f"(d[16]), "=f"(d[17]), "=f"(d[18]), "=f"(d[19]), "=f"(d[20]), "=f"(d[21]), "=f"(d[22]), "=f"(d[23]), "=f"(d[24]), "=f"(d[25]), "=f"(d[26]), "=f"(d[27]), "=f"(d[28]), "=f"(d[29]), "=f"(d[30]), "=f"(d[31]), "=f"(d[32]), "=f"(d[33]), "=f"(d[34]), "=f"(d[35])
    : "r"(a[0]), "r"(a[1]), "r"(a[2]), "r"(a[3]), "r"(lo), "r"(hi)
    : "memory");
}
__device__ __forceinline__ void sel_clr(float (&d)[44], const uint32_t (&a)[4], uint32_t lo, uint32_t hi) {
  asm volatile("{\n.reg .b64 db;\n.reg .b32 lo, hi;\n"
    "mov.b32 hi, %49;\n"
    "add.u32 lo, %48, 0;\nmov.b64 db, {lo, hi};\n"
    "wgmma.mma_async.sync.aligned.m64n88k16.f32.bf16.bf16 {%0, %1, %2, %3, %4, %5, %6, %7, %8, %9, %10, %11, %12, %13, %14, %15, %16, %17, %18, %19, %20, %21, %22, %23, %24, %25, %26, %27, %28, %29, %30, %31, %32, %33, %34, %35, %36, %37, %38, %39, %40, %41, %42, %43}, {%44, %45, %46, %47}, db, 0, 1, 1, 0;\n"
    "}\n"
    : "=f"(d[0]), "=f"(d[1]), "=f"(d[2]), "=f"(d[3]), "=f"(d[4]), "=f"(d[5]), "=f"(d[6]), "=f"(d[7]), "=f"(d[8]), "=f"(d[9]), "=f"(d[10]), "=f"(d[11]), "=f"(d[12]), "=f"(d[13]), "=f"(d[14]), "=f"(d[15]), "=f"(d[16]), "=f"(d[17]), "=f"(d[18]), "=f"(d[19]), "=f"(d[20]), "=f"(d[21]), "=f"(d[22]), "=f"(d[23]), "=f"(d[24]), "=f"(d[25]), "=f"(d[26]), "=f"(d[27]), "=f"(d[28]), "=f"(d[29]), "=f"(d[30]), "=f"(d[31]), "=f"(d[32]), "=f"(d[33]), "=f"(d[34]), "=f"(d[35]), "=f"(d[36]), "=f"(d[37]), "=f"(d[38]), "=f"(d[39]), "=f"(d[40]), "=f"(d[41]), "=f"(d[42]), "=f"(d[43])
    : "r"(a[0]), "r"(a[1]), "r"(a[2]), "r"(a[3]), "r"(lo), "r"(hi)
    : "memory");
}
template<int D> __device__ __forceinline__ void c1_acc(float (&d)[20], const uint32_t (&a)[16], uint64_t db) {
  asm volatile("{\n.reg .b64 db;\n"
    "add.s64 db, %36, %37 + 0;\n"
    "wgmma.mma_async.sync.aligned.m64n40k16.f32.bf16.bf16 {%0, %1, %2, %3, %4, %5, %6, %7, %8, %9, %10, %11, %12, %13, %14, %15, %16, %17, %18, %19}, {%20, %21, %22, %23}, db, 1, 1, 1, 0;\n"
    "add.s64 db, %36, %37 + 2;\n"
    "wgmma.mma_async.sync.aligned.m64n40k16.f32.bf16.bf16 {%0, %1, %2, %3, %4, %5, %6, %7, %8, %9, %10, %11, %12, %13, %14, %15, %16, %17, %18, %19}, {%24, %25, %26, %27}, db, 1, 1, 1, 0;\n"
    "add.s64 db, %36, %37 + 4;\n"
    "wgmma.mma_async.sync.aligned.m64n40k16.f32.bf16.bf16 {%0, %1, %2, %3, %4, %5, %6, %7, %8, %9, %10, %11, %12, %13, %14, %15, %16, %17, %18, %19}, {%28, %29, %30, %31}, db, 1, 1, 1, 0;\n"
    "add.s64 db, %36, %37 + 6;\n"
    "wgmma.mma_async.sync.aligned.m64n40k16.f32.bf16.bf16 {%0, %1, %2, %3, %4, %5, %6, %7, %8, %9, %10, %11, %12, %13, %14, %15, %16, %17, %18, %19}, {%32, %33, %34, %35}, db, 1, 1, 1, 0;\n"
    "wgmma.commit_group.sync.aligned;\n}\n"
    : "+f"(d[0]), "+f"(d[1]), "+f"(d[2]), "+f"(d[3]), "+f"(d[4]), "+f"(d[5]), "+f"(d[6]), "+f"(d[7]), "+f"(d[8]), "+f"(d[9]), "+f"(d[10]), "+f"(d[11]), "+f"(d[12]), "+f"(d[13]), "+f"(d[14]), "+f"(d[15]), "+f"(d[16]), "+f"(d[17]), "+f"(d[18]), "+f"(d[19])
    : "r"(a[0]), "r"(a[1]), "r"(a[2]), "r"(a[3]), "r"(a[4]), "r"(a[5]), "r"(a[6]), "r"(a[7]), "r"(a[8]), "r"(a[9]), "r"(a[10]), "r"(a[11]), "r"(a[12]), "r"(a[13]), "r"(a[14]), "r"(a[15]), "l"(db), "n"(D)
    : "memory");
}
template<int D> __device__ __forceinline__ void c1_acc(float (&d)[24], const uint32_t (&a)[16], uint64_t db) {
  asm volatile("{\n.reg .b64 db;\n"
    "add.s64 db, %40, %41 + 0;\n"
    "wgmma.mma_async.sync.aligned.m64n48k16.f32.bf16.bf16 {%0, %1, %2, %3, %4, %5, %6, %7, %8, %9, %10, %11, %12, %13, %14, %15, %16, %17, %18, %19, %20, %21, %22, %23}, {%24, %25, %26, %27}, db, 1, 1, 1, 0;\n"
    "add.s64 db, %40, %41 + 2;\n"
    "wgmma.mma_async.sync.aligned.m64n48k16.f32.bf16.bf16 {%0, %1, %2, %3, %4, %5, %6, %7, %8, %9, %10, %11, %12, %13, %14, %15, %16, %17, %18, %19, %20, %21, %22, %23}, {%28, %29, %30, %31}, db, 1, 1, 1, 0;\n"
    "add.s64 db, %40, %41 + 4;\n"
    "wgmma.mma_async.sync.aligned.m64n48k16.f32.bf16.bf16 {%0, %1, %2, %3, %4, %5, %6, %7, %8, %9, %10, %11, %12, %13, %14, %15, %16, %17, %18, %19, %20, %21, %22, %23}, {%32, %33, %34, %35}, db, 1, 1, 1, 0;\n"
    "add.s64 db, %40, %41 + 6;\n"
    "wgmma.mma_async.sync.aligned.m64n48k16.f32.bf16.bf16 {%0, %1, %2, %3, %4, %5, %6, %7, %8, %9, %10, %11, %12, %13, %14, %15, %16, %17, %18, %19, %20, %21, %22, %23}, {%36, %37, %38, %39}, db, 1, 1, 1, 0;\n"
    "wgmma.commit_group.sync.aligned;\n}\n"
    : "+f"(d[0]), "+f"(d[1]), "+f"(d[2]), "+f"(d[3]), "+f"(d[4]), "+f"(d[5]), "+f"(d[6]), "+f"(d[7]), "+f"(d[8]), "+f"(d[9]), "+f"(d[10]), "+f"(d[11]), "+f"(d[12]), "+f"(d[13]), "+f"(d[14]), "+f"(d[15]), "+f"(d[16]), "+f"(d[17]), "+f"(d[18]), "+f"(d[19]), "+f"(d[20]), "+f"(d[21]), "+f"(d[22]), "+f"(d[23])
    : "r"(a[0]), "r"(a[1]), "r"(a[2]), "r"(a[3]), "r"(a[4]), "r"(a[5]), "r"(a[6]), "r"(a[7]), "r"(a[8]), "r"(a[9]), "r"(a[10]), "r"(a[11]), "r"(a[12]), "r"(a[13]), "r"(a[14]), "r"(a[15]), "l"(db), "n"(D)
    : "memory");
}
template<int D> __device__ __forceinline__ void c1_acc(float (&d)[28], const uint32_t (&a)[16], uint64_t db) {
  asm volatile("{\n.reg .b64 db;\n"
    "add.s64 db, %44, %45 + 0;\n"
    "wgmma.mma_async.sync.aligned.m64n56k16.f32.bf16.bf16 {%0, %1, %2, %3, %4, %5, %6, %7, %8, %9, %10, %11, %12, %13, %14, %15, %16, %17, %18, %19, %20, %21, %22, %23, %24, %25, %26, %27}, {%28, %29, %30, %31}, db, 1, 1, 1, 0;\n"
    "add.s64 db, %44, %45 + 2;\n"
    "wgmma.mma_async.sync.aligned.m64n56k16.f32.bf16.bf16 {%0, %1, %2, %3, %4, %5, %6, %7, %8, %9, %10, %11, %12, %13, %14, %15, %16, %17, %18, %19, %20, %21, %22, %23, %24, %25, %26, %27}, {%32, %33, %34, %35}, db, 1, 1, 1, 0;\n"
    "add.s64 db, %44, %45 + 4;\n"
    "wgmma.mma_async.sync.aligned.m64n56k16.f32.bf16.bf16 {%0, %1, %2, %3, %4, %5, %6, %7, %8, %9, %10, %11, %12, %13, %14, %15, %16, %17, %18, %19, %20, %21, %22, %23, %24, %25, %26, %27}, {%36, %37, %38, %39}, db, 1, 1, 1, 0;\n"
    "add.s64 db, %44, %45 + 6;\n"
    "wgmma.mma_async.sync.aligned.m64n56k16.f32.bf16.bf16 {%0, %1, %2, %3, %4, %5, %6, %7, %8, %9, %10, %11, %12, %13, %14, %15, %16, %17, %18, %19, %20, %21, %22, %23, %24, %25, %26, %27}, {%40, %41, %42, %43}, db, 1, 1, 1, 0;\n"
    "wgmma.commit_group.sync.aligned;\n}\n"
    : "+f"(d[0]), "+f"(d[1]), "+f"(d[2]), "+f"(d[3]), "+f"(d[4]), "+f"(d[5]), "+f"(d[6]), "+f"(d[7]), "+f"(d[8]), "+f"(d[9]), "+f"(d[10]), "+f"(d[11]), "+f"(d[12]), "+f"(d[13]), "+f"(d[14]), "+f"(d[15]), "+f"(d[16]), "+f"(d[17]), "+f"(d[18]), "+f"(d[19]), "+f"(d[20]), "+f"(d[21]), "+f"(d[22]), "+f"(d[23]), "+f"(d[24]), "+f"(d[25]), "+f"(d[26]), "+f"(d[27])
    : "r"(a[0]), "r"(a[1]), "r"(a[2]), "r"(a[3]), "r"(a[4]), "r"(a[5]), "r"(a[6]), "r"(a[7]), "r"(a[8]), "r"(a[9]), "r"(a[10]), "r"(a[11]), "r"(a[12]), "r"(a[13]), "r"(a[14]), "r"(a[15]), "l"(db), "n"(D)
    : "memory");
}
template<int D> __device__ __forceinline__ void c1_acc(float (&d)[32], const uint32_t (&a)[16], uint64_t db) {
  asm volatile("{\n.reg .b64 db;\n"
    "add.s64 db, %48, %49 + 0;\n"
    "wgmma.mma_async.sync.aligned.m64n64k16.f32.bf16.bf16 {%0, %1, %2, %3, %4, %5, %6, %7, %8, %9, %10, %11, %12, %13, %14, %15, %16, %17, %18, %19, %20, %21, %22, %23, %24, %25, %26, %27, %28, %29, %30, %31}, {%32, %33, %34, %35}, db, 1, 1, 1, 0;\n"
    "add.s64 db, %48, %49 + 2;\n"
    "wgmma.mma_async.sync.aligned.m64n64k16.f32.bf16.bf16 {%0, %1, %2, %3, %4, %5, %6, %7, %8, %9, %10, %11, %12, %13, %14, %15, %16, %17, %18, %19, %20, %21, %22, %23, %24, %25, %26, %27, %28, %29, %30, %31}, {%36, %37, %38, %39}, db, 1, 1, 1, 0;\n"
    "add.s64 db, %48, %49 + 4;\n"
    "wgmma.mma_async.sync.aligned.m64n64k16.f32.bf16.bf16 {%0, %1, %2, %3, %4, %5, %6, %7, %8, %9, %10, %11, %12, %13, %14, %15, %16, %17, %18, %19, %20, %21, %22, %23, %24, %25, %26, %27, %28, %29, %30, %31}, {%40, %41, %42, %43}, db, 1, 1, 1, 0;\n"
    "add.s64 db, %48, %49 + 6;\n"
    "wgmma.mma_async.sync.aligned.m64n64k16.f32.bf16.bf16 {%0, %1, %2, %3, %4, %5, %6, %7, %8, %9, %10, %11, %12, %13, %14, %15, %16, %17, %18, %19, %20, %21, %22, %23, %24, %25, %26, %27, %28, %29, %30, %31}, {%44, %45, %46, %47}, db, 1, 1, 1, 0;\n"
    "wgmma.commit_group.sync.aligned;\n}\n"
    : "+f"(d[0]), "+f"(d[1]), "+f"(d[2]), "+f"(d[3]), "+f"(d[4]), "+f"(d[5]), "+f"(d[6]), "+f"(d[7]), "+f"(d[8]), "+f"(d[9]), "+f"(d[10]), "+f"(d[11]), "+f"(d[12]), "+f"(d[13]), "+f"(d[14]), "+f"(d[15]), "+f"(d[16]), "+f"(d[17]), "+f"(d[18]), "+f"(d[19]), "+f"(d[20]), "+f"(d[21]), "+f"(d[22]), "+f"(d[23]), "+f"(d[24]), "+f"(d[25]), "+f"(d[26]), "+f"(d[27]), "+f"(d[28]), "+f"(d[29]), "+f"(d[30]), "+f"(d[31])
    : "r"(a[0]), "r"(a[1]), "r"(a[2]), "r"(a[3]), "r"(a[4]), "r"(a[5]), "r"(a[6]), "r"(a[7]), "r"(a[8]), "r"(a[9]), "r"(a[10]), "r"(a[11]), "r"(a[12]), "r"(a[13]), "r"(a[14]), "r"(a[15]), "l"(db), "n"(D)
    : "memory");
}
template<int D> __device__ __forceinline__ void c1_acc(float (&d)[36], const uint32_t (&a)[16], uint64_t db) {
  asm volatile("{\n.reg .b64 db;\n"
    "add.s64 db, %52, %53 + 0;\n"
    "wgmma.mma_async.sync.aligned.m64n72k16.f32.bf16.bf16 {%0, %1, %2, %3, %4, %5, %6, %7, %8, %9, %10, %11, %12, %13, %14, %15, %16, %17, %18, %19, %20, %21, %22, %23, %24, %25, %26, %27, %28, %29, %30, %31, %32, %33, %34, %35}, {%36, %37, %38, %39}, db, 1, 1, 1, 0;\n"
    "add.s64 db, %52, %53 + 2;\n"
    "wgmma.mma_async.sync.aligned.m64n72k16.f32.bf16.bf16 {%0, %1, %2, %3, %4, %5, %6, %7, %8, %9, %10, %11, %12, %13, %14, %15, %16, %17, %18, %19, %20, %21, %22, %23, %24, %25, %26, %27, %28, %29, %30, %31, %32, %33, %34, %35}, {%40, %41, %42, %43}, db, 1, 1, 1, 0;\n"
    "add.s64 db, %52, %53 + 4;\n"
    "wgmma.mma_async.sync.aligned.m64n72k16.f32.bf16.bf16 {%0, %1, %2, %3, %4, %5, %6, %7, %8, %9, %10, %11, %12, %13, %14, %15, %16, %17, %18, %19, %20, %21, %22, %23, %24, %25, %26, %27, %28, %29, %30, %31, %32, %33, %34, %35}, {%44, %45, %46, %47}, db, 1, 1, 1, 0;\n"
    "add.s64 db, %52, %53 + 6;\n"
    "wgmma.mma_async.sync.aligned.m64n72k16.f32.bf16.bf16 {%0, %1, %2, %3, %4, %5, %6, %7, %8, %9, %10, %11, %12, %13, %14, %15, %16, %17, %18, %19, %20, %21, %22, %23, %24, %25, %26, %27, %28, %29, %30, %31, %32, %33, %34, %35}, {%48, %49, %50, %51}, db, 1, 1, 1, 0;\n"
    "wgmma.commit_group.sync.aligned;\n}\n"
    : "+f"(d[0]), "+f"(d[1]), "+f"(d[2]), "+f"(d[3]), "+f"(d[4]), "+f"(d[5]), "+f"(d[6]), "+f"(d[7]), "+f"(d[8]), "+f"(d[9]), "+f"(d[10]), "+f"(d[11]), "+f"(d[12]), "+f"(d[13]), "+f"(d[14]), "+f"(d[15]), "+f"(d[16]), "+f"(d[17]), "+f"(d[18]), "+f"(d[19]), "+f"(d[20]), "+f"(d[21]), "+f"(d[22]), "+f"(d[23]), "+f"(d[24]), "+f"(d[25]), "+f"(d[26]), "+f"(d[27]), "+f"(d[28]), "+f"(d[29]), "+f"(d[30]), "+f"(d[31]), "+f"(d[32]), "+f"(d[33]), "+f"(d[34]), "+f"(d[35])
    : "r"(a[0]), "r"(a[1]), "r"(a[2]), "r"(a[3]), "r"(a[4]), "r"(a[5]), "r"(a[6]), "r"(a[7]), "r"(a[8]), "r"(a[9]), "r"(a[10]), "r"(a[11]), "r"(a[12]), "r"(a[13]), "r"(a[14]), "r"(a[15]), "l"(db), "n"(D)
    : "memory");
}
template<int D> __device__ __forceinline__ void c1_acc(float (&d)[44], const uint32_t (&a)[16], uint64_t db) {
  asm volatile("{\n.reg .b64 db;\n"
    "add.s64 db, %60, %61 + 0;\n"
    "wgmma.mma_async.sync.aligned.m64n88k16.f32.bf16.bf16 {%0, %1, %2, %3, %4, %5, %6, %7, %8, %9, %10, %11, %12, %13, %14, %15, %16, %17, %18, %19, %20, %21, %22, %23, %24, %25, %26, %27, %28, %29, %30, %31, %32, %33, %34, %35, %36, %37, %38, %39, %40, %41, %42, %43}, {%44, %45, %46, %47}, db, 1, 1, 1, 0;\n"
    "add.s64 db, %60, %61 + 2;\n"
    "wgmma.mma_async.sync.aligned.m64n88k16.f32.bf16.bf16 {%0, %1, %2, %3, %4, %5, %6, %7, %8, %9, %10, %11, %12, %13, %14, %15, %16, %17, %18, %19, %20, %21, %22, %23, %24, %25, %26, %27, %28, %29, %30, %31, %32, %33, %34, %35, %36, %37, %38, %39, %40, %41, %42, %43}, {%48, %49, %50, %51}, db, 1, 1, 1, 0;\n"
    "add.s64 db, %60, %61 + 4;\n"
    "wgmma.mma_async.sync.aligned.m64n88k16.f32.bf16.bf16 {%0, %1, %2, %3, %4, %5, %6, %7, %8, %9, %10, %11, %12, %13, %14, %15, %16, %17, %18, %19, %20, %21, %22, %23, %24, %25, %26, %27, %28, %29, %30, %31, %32, %33, %34, %35, %36, %37, %38, %39, %40, %41, %42, %43}, {%52, %53, %54, %55}, db, 1, 1, 1, 0;\n"
    "add.s64 db, %60, %61 + 6;\n"
    "wgmma.mma_async.sync.aligned.m64n88k16.f32.bf16.bf16 {%0, %1, %2, %3, %4, %5, %6, %7, %8, %9, %10, %11, %12, %13, %14, %15, %16, %17, %18, %19, %20, %21, %22, %23, %24, %25, %26, %27, %28, %29, %30, %31, %32, %33, %34, %35, %36, %37, %38, %39, %40, %41, %42, %43}, {%56, %57, %58, %59}, db, 1, 1, 1, 0;\n"
    "wgmma.commit_group.sync.aligned;\n}\n"
    : "+f"(d[0]), "+f"(d[1]), "+f"(d[2]), "+f"(d[3]), "+f"(d[4]), "+f"(d[5]), "+f"(d[6]), "+f"(d[7]), "+f"(d[8]), "+f"(d[9]), "+f"(d[10]), "+f"(d[11]), "+f"(d[12]), "+f"(d[13]), "+f"(d[14]), "+f"(d[15]), "+f"(d[16]), "+f"(d[17]), "+f"(d[18]), "+f"(d[19]), "+f"(d[20]), "+f"(d[21]), "+f"(d[22]), "+f"(d[23]), "+f"(d[24]), "+f"(d[25]), "+f"(d[26]), "+f"(d[27]), "+f"(d[28]), "+f"(d[29]), "+f"(d[30]), "+f"(d[31]), "+f"(d[32]), "+f"(d[33]), "+f"(d[34]), "+f"(d[35]), "+f"(d[36]), "+f"(d[37]), "+f"(d[38]), "+f"(d[39]), "+f"(d[40]), "+f"(d[41]), "+f"(d[42]), "+f"(d[43])
    : "r"(a[0]), "r"(a[1]), "r"(a[2]), "r"(a[3]), "r"(a[4]), "r"(a[5]), "r"(a[6]), "r"(a[7]), "r"(a[8]), "r"(a[9]), "r"(a[10]), "r"(a[11]), "r"(a[12]), "r"(a[13]), "r"(a[14]), "r"(a[15]), "l"(db), "n"(D)
    : "memory");
}
template<int D> __device__ __forceinline__ void cbias(float (&d)[4], const uint32_t (&a)[16], uint64_t db) {
  asm volatile("{\n.reg .b64 db;\n"
    "add.s64 db, %20, %21 + 0;\n"
    "wgmma.mma_async.sync.aligned.m64n8k16.f32.bf16.bf16 {%0, %1, %2, %3}, {%4, %5, %6, %7}, db, 0, 1, 1, 0;\n"
    "add.s64 db, %20, %21 + 2;\n"
    "wgmma.mma_async.sync.aligned.m64n8k16.f32.bf16.bf16 {%0, %1, %2, %3}, {%8, %9, %10, %11}, db, 1, 1, 1, 0;\n"
    "add.s64 db, %20, %21 + 4;\n"
    "wgmma.mma_async.sync.aligned.m64n8k16.f32.bf16.bf16 {%0, %1, %2, %3}, {%12, %13, %14, %15}, db, 1, 1, 1, 0;\n"
    "add.s64 db, %20, %21 + 6;\n"
    "wgmma.mma_async.sync.aligned.m64n8k16.f32.bf16.bf16 {%0, %1, %2, %3}, {%16, %17, %18, %19}, db, 1, 1, 1, 0;\n"
    "wgmma.commit_group.sync.aligned;\n}\n"
    : "=f"(d[0]), "=f"(d[1]), "=f"(d[2]), "=f"(d[3])
    : "r"(a[0]), "r"(a[1]), "r"(a[2]), "r"(a[3]), "r"(a[4]), "r"(a[5]), "r"(a[6]), "r"(a[7]), "r"(a[8]), "r"(a[9]), "r"(a[10]), "r"(a[11]), "r"(a[12]), "r"(a[13]), "r"(a[14]), "r"(a[15]), "l"(db), "n"(D)
    : "memory");
}
template<int D> __device__ __forceinline__ void c2_first(float (&d)[16], const uint32_t (&a)[4], uint64_t db, uint32_t meta) {
  asm volatile("{\n.reg .b64 db;\n"
    "wgmma.fence.sync.aligned;\n"
    "add.s64 db, %20, %21 + 0;\n"
    "wgmma.mma_async.sp.sync.aligned.m64n32k32.f32.bf16.bf16 {%0, %1, %2, %3, %4, %5, %6, %7, %8, %9, %10, %11, %12, %13, %14, %15}, {%16, %17, %18, %19}, db, %22, 0, 0, 1, 1, 1;\n"
    "wgmma.commit_group.sync.aligned;\n}\n"
    : "=f"(d[0]), "=f"(d[1]), "=f"(d[2]), "=f"(d[3]), "=f"(d[4]), "=f"(d[5]), "=f"(d[6]), "=f"(d[7]), "=f"(d[8]), "=f"(d[9]), "=f"(d[10]), "=f"(d[11]), "=f"(d[12]), "=f"(d[13]), "=f"(d[14]), "=f"(d[15])
    : "r"(a[0]), "r"(a[1]), "r"(a[2]), "r"(a[3]), "l"(db), "n"(D), "r"(meta)
    : "memory");
}
template<int D> __device__ __forceinline__ void c2_more(float (&d)[16], const uint32_t (&a)[4], uint64_t db, uint32_t meta) {
  asm volatile("{\n.reg .b64 db;\n"
    "wgmma.fence.sync.aligned;\n"
    "add.s64 db, %20, %21 + 0;\n"
    "wgmma.mma_async.sp.sync.aligned.m64n32k32.f32.bf16.bf16 {%0, %1, %2, %3, %4, %5, %6, %7, %8, %9, %10, %11, %12, %13, %14, %15}, {%16, %17, %18, %19}, db, %22, 0, 1, 1, 1, 1;\n"
    "wgmma.commit_group.sync.aligned;\n}\n"
    : "+f"(d[0]), "+f"(d[1]), "+f"(d[2]), "+f"(d[3]), "+f"(d[4]), "+f"(d[5]), "+f"(d[6]), "+f"(d[7]), "+f"(d[8]), "+f"(d[9]), "+f"(d[10]), "+f"(d[11]), "+f"(d[12]), "+f"(d[13]), "+f"(d[14]), "+f"(d[15])
    : "r"(a[0]), "r"(a[1]), "r"(a[2]), "r"(a[3]), "l"(db), "n"(D), "r"(meta)
    : "memory");
}
template<int D> __device__ __forceinline__ void c2_first(float (&d)[16], const uint32_t (&a)[8], uint64_t db, uint32_t meta) {
  asm volatile("{\n.reg .b64 db;\n"
    "wgmma.fence.sync.aligned;\n"
    "add.s64 db, %24, %25 + 0;\n"
    "wgmma.mma_async.sp.sync.aligned.m64n32k32.f32.bf16.bf16 {%0, %1, %2, %3, %4, %5, %6, %7, %8, %9, %10, %11, %12, %13, %14, %15}, {%16, %17, %18, %19}, db, %26, 0, 0, 1, 1, 1;\n"
    "add.s64 db, %24, %25 + 128;\n"
    "wgmma.mma_async.sp.sync.aligned.m64n32k32.f32.bf16.bf16 {%0, %1, %2, %3, %4, %5, %6, %7, %8, %9, %10, %11, %12, %13, %14, %15}, {%20, %21, %22, %23}, db, %26, 0, 1, 1, 1, 1;\n"
    "wgmma.commit_group.sync.aligned;\n}\n"
    : "=f"(d[0]), "=f"(d[1]), "=f"(d[2]), "=f"(d[3]), "=f"(d[4]), "=f"(d[5]), "=f"(d[6]), "=f"(d[7]), "=f"(d[8]), "=f"(d[9]), "=f"(d[10]), "=f"(d[11]), "=f"(d[12]), "=f"(d[13]), "=f"(d[14]), "=f"(d[15])
    : "r"(a[0]), "r"(a[1]), "r"(a[2]), "r"(a[3]), "r"(a[4]), "r"(a[5]), "r"(a[6]), "r"(a[7]), "l"(db), "n"(D), "r"(meta)
    : "memory");
}
template<int D> __device__ __forceinline__ void c2_more(float (&d)[16], const uint32_t (&a)[8], uint64_t db, uint32_t meta) {
  asm volatile("{\n.reg .b64 db;\n"
    "wgmma.fence.sync.aligned;\n"
    "add.s64 db, %24, %25 + 0;\n"
    "wgmma.mma_async.sp.sync.aligned.m64n32k32.f32.bf16.bf16 {%0, %1, %2, %3, %4, %5, %6, %7, %8, %9, %10, %11, %12, %13, %14, %15}, {%16, %17, %18, %19}, db, %26, 0, 1, 1, 1, 1;\n"
    "add.s64 db, %24, %25 + 128;\n"
    "wgmma.mma_async.sp.sync.aligned.m64n32k32.f32.bf16.bf16 {%0, %1, %2, %3, %4, %5, %6, %7, %8, %9, %10, %11, %12, %13, %14, %15}, {%20, %21, %22, %23}, db, %26, 0, 1, 1, 1, 1;\n"
    "wgmma.commit_group.sync.aligned;\n}\n"
    : "+f"(d[0]), "+f"(d[1]), "+f"(d[2]), "+f"(d[3]), "+f"(d[4]), "+f"(d[5]), "+f"(d[6]), "+f"(d[7]), "+f"(d[8]), "+f"(d[9]), "+f"(d[10]), "+f"(d[11]), "+f"(d[12]), "+f"(d[13]), "+f"(d[14]), "+f"(d[15])
    : "r"(a[0]), "r"(a[1]), "r"(a[2]), "r"(a[3]), "r"(a[4]), "r"(a[5]), "r"(a[6]), "r"(a[7]), "l"(db), "n"(D), "r"(meta)
    : "memory");
}
template<int D> __device__ __forceinline__ void c2_first(float (&d)[16], const uint32_t (&a)[12], uint64_t db, uint32_t meta) {
  asm volatile("{\n.reg .b64 db;\n"
    "wgmma.fence.sync.aligned;\n"
    "add.s64 db, %28, %29 + 0;\n"
    "wgmma.mma_async.sp.sync.aligned.m64n32k32.f32.bf16.bf16 {%0, %1, %2, %3, %4, %5, %6, %7, %8, %9, %10, %11, %12, %13, %14, %15}, {%16, %17, %18, %19}, db, %30, 0, 0, 1, 1, 1;\n"
    "add.s64 db, %28, %29 + 128;\n"
    "wgmma.mma_async.sp.sync.aligned.m64n32k32.f32.bf16.bf16 {%0, %1, %2, %3, %4, %5, %6, %7, %8, %9, %10, %11, %12, %13, %14, %15}, {%20, %21, %22, %23}, db, %30, 0, 1, 1, 1, 1;\n"
    "add.s64 db, %28, %29 + 256;\n"
    "wgmma.mma_async.sp.sync.aligned.m64n32k32.f32.bf16.bf16 {%0, %1, %2, %3, %4, %5, %6, %7, %8, %9, %10, %11, %12, %13, %14, %15}, {%24, %25, %26, %27}, db, %30, 0, 1, 1, 1, 1;\n"
    "wgmma.commit_group.sync.aligned;\n}\n"
    : "=f"(d[0]), "=f"(d[1]), "=f"(d[2]), "=f"(d[3]), "=f"(d[4]), "=f"(d[5]), "=f"(d[6]), "=f"(d[7]), "=f"(d[8]), "=f"(d[9]), "=f"(d[10]), "=f"(d[11]), "=f"(d[12]), "=f"(d[13]), "=f"(d[14]), "=f"(d[15])
    : "r"(a[0]), "r"(a[1]), "r"(a[2]), "r"(a[3]), "r"(a[4]), "r"(a[5]), "r"(a[6]), "r"(a[7]), "r"(a[8]), "r"(a[9]), "r"(a[10]), "r"(a[11]), "l"(db), "n"(D), "r"(meta)
    : "memory");
}
template<int D> __device__ __forceinline__ void c2_more(float (&d)[16], const uint32_t (&a)[12], uint64_t db, uint32_t meta) {
  asm volatile("{\n.reg .b64 db;\n"
    "wgmma.fence.sync.aligned;\n"
    "add.s64 db, %28, %29 + 0;\n"
    "wgmma.mma_async.sp.sync.aligned.m64n32k32.f32.bf16.bf16 {%0, %1, %2, %3, %4, %5, %6, %7, %8, %9, %10, %11, %12, %13, %14, %15}, {%16, %17, %18, %19}, db, %30, 0, 1, 1, 1, 1;\n"
    "add.s64 db, %28, %29 + 128;\n"
    "wgmma.mma_async.sp.sync.aligned.m64n32k32.f32.bf16.bf16 {%0, %1, %2, %3, %4, %5, %6, %7, %8, %9, %10, %11, %12, %13, %14, %15}, {%20, %21, %22, %23}, db, %30, 0, 1, 1, 1, 1;\n"
    "add.s64 db, %28, %29 + 256;\n"
    "wgmma.mma_async.sp.sync.aligned.m64n32k32.f32.bf16.bf16 {%0, %1, %2, %3, %4, %5, %6, %7, %8, %9, %10, %11, %12, %13, %14, %15}, {%24, %25, %26, %27}, db, %30, 0, 1, 1, 1, 1;\n"
    "wgmma.commit_group.sync.aligned;\n}\n"
    : "+f"(d[0]), "+f"(d[1]), "+f"(d[2]), "+f"(d[3]), "+f"(d[4]), "+f"(d[5]), "+f"(d[6]), "+f"(d[7]), "+f"(d[8]), "+f"(d[9]), "+f"(d[10]), "+f"(d[11]), "+f"(d[12]), "+f"(d[13]), "+f"(d[14]), "+f"(d[15])
    : "r"(a[0]), "r"(a[1]), "r"(a[2]), "r"(a[3]), "r"(a[4]), "r"(a[5]), "r"(a[6]), "r"(a[7]), "r"(a[8]), "r"(a[9]), "r"(a[10]), "r"(a[11]), "l"(db), "n"(D), "r"(meta)
    : "memory");
}
template<int D> __device__ __forceinline__ void c2_first(float (&d)[16], const uint32_t (&a)[16], uint64_t db, uint32_t meta) {
  asm volatile("{\n.reg .b64 db;\n"
    "wgmma.fence.sync.aligned;\n"
    "add.s64 db, %32, %33 + 0;\n"
    "wgmma.mma_async.sp.sync.aligned.m64n32k32.f32.bf16.bf16 {%0, %1, %2, %3, %4, %5, %6, %7, %8, %9, %10, %11, %12, %13, %14, %15}, {%16, %17, %18, %19}, db, %34, 0, 0, 1, 1, 1;\n"
    "add.s64 db, %32, %33 + 128;\n"
    "wgmma.mma_async.sp.sync.aligned.m64n32k32.f32.bf16.bf16 {%0, %1, %2, %3, %4, %5, %6, %7, %8, %9, %10, %11, %12, %13, %14, %15}, {%20, %21, %22, %23}, db, %34, 0, 1, 1, 1, 1;\n"
    "add.s64 db, %32, %33 + 256;\n"
    "wgmma.mma_async.sp.sync.aligned.m64n32k32.f32.bf16.bf16 {%0, %1, %2, %3, %4, %5, %6, %7, %8, %9, %10, %11, %12, %13, %14, %15}, {%24, %25, %26, %27}, db, %34, 0, 1, 1, 1, 1;\n"
    "add.s64 db, %32, %33 + 384;\n"
    "wgmma.mma_async.sp.sync.aligned.m64n32k32.f32.bf16.bf16 {%0, %1, %2, %3, %4, %5, %6, %7, %8, %9, %10, %11, %12, %13, %14, %15}, {%28, %29, %30, %31}, db, %34, 0, 1, 1, 1, 1;\n"
    "wgmma.commit_group.sync.aligned;\n}\n"
    : "=f"(d[0]), "=f"(d[1]), "=f"(d[2]), "=f"(d[3]), "=f"(d[4]), "=f"(d[5]), "=f"(d[6]), "=f"(d[7]), "=f"(d[8]), "=f"(d[9]), "=f"(d[10]), "=f"(d[11]), "=f"(d[12]), "=f"(d[13]), "=f"(d[14]), "=f"(d[15])
    : "r"(a[0]), "r"(a[1]), "r"(a[2]), "r"(a[3]), "r"(a[4]), "r"(a[5]), "r"(a[6]), "r"(a[7]), "r"(a[8]), "r"(a[9]), "r"(a[10]), "r"(a[11]), "r"(a[12]), "r"(a[13]), "r"(a[14]), "r"(a[15]), "l"(db), "n"(D), "r"(meta)
    : "memory");
}
template<int D> __device__ __forceinline__ void c2_more(float (&d)[16], const uint32_t (&a)[16], uint64_t db, uint32_t meta) {
  asm volatile("{\n.reg .b64 db;\n"
    "wgmma.fence.sync.aligned;\n"
    "add.s64 db, %32, %33 + 0;\n"
    "wgmma.mma_async.sp.sync.aligned.m64n32k32.f32.bf16.bf16 {%0, %1, %2, %3, %4, %5, %6, %7, %8, %9, %10, %11, %12, %13, %14, %15}, {%16, %17, %18, %19}, db, %34, 0, 1, 1, 1, 1;\n"
    "add.s64 db, %32, %33 + 128;\n"
    "wgmma.mma_async.sp.sync.aligned.m64n32k32.f32.bf16.bf16 {%0, %1, %2, %3, %4, %5, %6, %7, %8, %9, %10, %11, %12, %13, %14, %15}, {%20, %21, %22, %23}, db, %34, 0, 1, 1, 1, 1;\n"
    "add.s64 db, %32, %33 + 256;\n"
    "wgmma.mma_async.sp.sync.aligned.m64n32k32.f32.bf16.bf16 {%0, %1, %2, %3, %4, %5, %6, %7, %8, %9, %10, %11, %12, %13, %14, %15}, {%24, %25, %26, %27}, db, %34, 0, 1, 1, 1, 1;\n"
    "add.s64 db, %32, %33 + 384;\n"
    "wgmma.mma_async.sp.sync.aligned.m64n32k32.f32.bf16.bf16 {%0, %1, %2, %3, %4, %5, %6, %7, %8, %9, %10, %11, %12, %13, %14, %15}, {%28, %29, %30, %31}, db, %34, 0, 1, 1, 1, 1;\n"
    "wgmma.commit_group.sync.aligned;\n}\n"
    : "+f"(d[0]), "+f"(d[1]), "+f"(d[2]), "+f"(d[3]), "+f"(d[4]), "+f"(d[5]), "+f"(d[6]), "+f"(d[7]), "+f"(d[8]), "+f"(d[9]), "+f"(d[10]), "+f"(d[11]), "+f"(d[12]), "+f"(d[13]), "+f"(d[14]), "+f"(d[15])
    : "r"(a[0]), "r"(a[1]), "r"(a[2]), "r"(a[3]), "r"(a[4]), "r"(a[5]), "r"(a[6]), "r"(a[7]), "r"(a[8]), "r"(a[9]), "r"(a[10]), "r"(a[11]), "r"(a[12]), "r"(a[13]), "r"(a[14]), "r"(a[15]), "l"(db), "n"(D), "r"(meta)
    : "memory");
}
template<int D> __device__ __forceinline__ void c2_first(float (&d)[16], const uint32_t (&a)[20], uint64_t db, uint32_t meta) {
  asm volatile("{\n.reg .b64 db;\n"
    "wgmma.fence.sync.aligned;\n"
    "add.s64 db, %36, %37 + 0;\n"
    "wgmma.mma_async.sp.sync.aligned.m64n32k32.f32.bf16.bf16 {%0, %1, %2, %3, %4, %5, %6, %7, %8, %9, %10, %11, %12, %13, %14, %15}, {%16, %17, %18, %19}, db, %38, 0, 0, 1, 1, 1;\n"
    "add.s64 db, %36, %37 + 128;\n"
    "wgmma.mma_async.sp.sync.aligned.m64n32k32.f32.bf16.bf16 {%0, %1, %2, %3, %4, %5, %6, %7, %8, %9, %10, %11, %12, %13, %14, %15}, {%20, %21, %22, %23}, db, %38, 0, 1, 1, 1, 1;\n"
    "add.s64 db, %36, %37 + 256;\n"
    "wgmma.mma_async.sp.sync.aligned.m64n32k32.f32.bf16.bf16 {%0, %1, %2, %3, %4, %5, %6, %7, %8, %9, %10, %11, %12, %13, %14, %15}, {%24, %25, %26, %27}, db, %38, 0, 1, 1, 1, 1;\n"
    "add.s64 db, %36, %37 + 384;\n"
    "wgmma.mma_async.sp.sync.aligned.m64n32k32.f32.bf16.bf16 {%0, %1, %2, %3, %4, %5, %6, %7, %8, %9, %10, %11, %12, %13, %14, %15}, {%28, %29, %30, %31}, db, %38, 0, 1, 1, 1, 1;\n"
    "add.s64 db, %36, %37 + 512;\n"
    "wgmma.mma_async.sp.sync.aligned.m64n32k32.f32.bf16.bf16 {%0, %1, %2, %3, %4, %5, %6, %7, %8, %9, %10, %11, %12, %13, %14, %15}, {%32, %33, %34, %35}, db, %38, 0, 1, 1, 1, 1;\n"
    "wgmma.commit_group.sync.aligned;\n}\n"
    : "=f"(d[0]), "=f"(d[1]), "=f"(d[2]), "=f"(d[3]), "=f"(d[4]), "=f"(d[5]), "=f"(d[6]), "=f"(d[7]), "=f"(d[8]), "=f"(d[9]), "=f"(d[10]), "=f"(d[11]), "=f"(d[12]), "=f"(d[13]), "=f"(d[14]), "=f"(d[15])
    : "r"(a[0]), "r"(a[1]), "r"(a[2]), "r"(a[3]), "r"(a[4]), "r"(a[5]), "r"(a[6]), "r"(a[7]), "r"(a[8]), "r"(a[9]), "r"(a[10]), "r"(a[11]), "r"(a[12]), "r"(a[13]), "r"(a[14]), "r"(a[15]), "r"(a[16]), "r"(a[17]), "r"(a[18]), "r"(a[19]), "l"(db), "n"(D), "r"(meta)
    : "memory");
}
template<int D> __device__ __forceinline__ void c2_more(float (&d)[16], const uint32_t (&a)[20], uint64_t db, uint32_t meta) {
  asm volatile("{\n.reg .b64 db;\n"
    "wgmma.fence.sync.aligned;\n"
    "add.s64 db, %36, %37 + 0;\n"
    "wgmma.mma_async.sp.sync.aligned.m64n32k32.f32.bf16.bf16 {%0, %1, %2, %3, %4, %5, %6, %7, %8, %9, %10, %11, %12, %13, %14, %15}, {%16, %17, %18, %19}, db, %38, 0, 1, 1, 1, 1;\n"
    "add.s64 db, %36, %37 + 128;\n"
    "wgmma.mma_async.sp.sync.aligned.m64n32k32.f32.bf16.bf16 {%0, %1, %2, %3, %4, %5, %6, %7, %8, %9, %10, %11, %12, %13, %14, %15}, {%20, %21, %22, %23}, db, %38, 0, 1, 1, 1, 1;\n"
    "add.s64 db, %36, %37 + 256;\n"
    "wgmma.mma_async.sp.sync.aligned.m64n32k32.f32.bf16.bf16 {%0, %1, %2, %3, %4, %5, %6, %7, %8, %9, %10, %11, %12, %13, %14, %15}, {%24, %25, %26, %27}, db, %38, 0, 1, 1, 1, 1;\n"
    "add.s64 db, %36, %37 + 384;\n"
    "wgmma.mma_async.sp.sync.aligned.m64n32k32.f32.bf16.bf16 {%0, %1, %2, %3, %4, %5, %6, %7, %8, %9, %10, %11, %12, %13, %14, %15}, {%28, %29, %30, %31}, db, %38, 0, 1, 1, 1, 1;\n"
    "add.s64 db, %36, %37 + 512;\n"
    "wgmma.mma_async.sp.sync.aligned.m64n32k32.f32.bf16.bf16 {%0, %1, %2, %3, %4, %5, %6, %7, %8, %9, %10, %11, %12, %13, %14, %15}, {%32, %33, %34, %35}, db, %38, 0, 1, 1, 1, 1;\n"
    "wgmma.commit_group.sync.aligned;\n}\n"
    : "+f"(d[0]), "+f"(d[1]), "+f"(d[2]), "+f"(d[3]), "+f"(d[4]), "+f"(d[5]), "+f"(d[6]), "+f"(d[7]), "+f"(d[8]), "+f"(d[9]), "+f"(d[10]), "+f"(d[11]), "+f"(d[12]), "+f"(d[13]), "+f"(d[14]), "+f"(d[15])
    : "r"(a[0]), "r"(a[1]), "r"(a[2]), "r"(a[3]), "r"(a[4]), "r"(a[5]), "r"(a[6]), "r"(a[7]), "r"(a[8]), "r"(a[9]), "r"(a[10]), "r"(a[11]), "r"(a[12]), "r"(a[13]), "r"(a[14]), "r"(a[15]), "r"(a[16]), "r"(a[17]), "r"(a[18]), "r"(a[19]), "l"(db), "n"(D), "r"(meta)
    : "memory");
}
template<int D> __device__ __forceinline__ void c2_first(float (&d)[16], const uint32_t (&a)[24], uint64_t db, uint32_t meta) {
  asm volatile("{\n.reg .b64 db;\n"
    "wgmma.fence.sync.aligned;\n"
    "add.s64 db, %40, %41 + 0;\n"
    "wgmma.mma_async.sp.sync.aligned.m64n32k32.f32.bf16.bf16 {%0, %1, %2, %3, %4, %5, %6, %7, %8, %9, %10, %11, %12, %13, %14, %15}, {%16, %17, %18, %19}, db, %42, 0, 0, 1, 1, 1;\n"
    "add.s64 db, %40, %41 + 128;\n"
    "wgmma.mma_async.sp.sync.aligned.m64n32k32.f32.bf16.bf16 {%0, %1, %2, %3, %4, %5, %6, %7, %8, %9, %10, %11, %12, %13, %14, %15}, {%20, %21, %22, %23}, db, %42, 0, 1, 1, 1, 1;\n"
    "add.s64 db, %40, %41 + 256;\n"
    "wgmma.mma_async.sp.sync.aligned.m64n32k32.f32.bf16.bf16 {%0, %1, %2, %3, %4, %5, %6, %7, %8, %9, %10, %11, %12, %13, %14, %15}, {%24, %25, %26, %27}, db, %42, 0, 1, 1, 1, 1;\n"
    "add.s64 db, %40, %41 + 384;\n"
    "wgmma.mma_async.sp.sync.aligned.m64n32k32.f32.bf16.bf16 {%0, %1, %2, %3, %4, %5, %6, %7, %8, %9, %10, %11, %12, %13, %14, %15}, {%28, %29, %30, %31}, db, %42, 0, 1, 1, 1, 1;\n"
    "add.s64 db, %40, %41 + 512;\n"
    "wgmma.mma_async.sp.sync.aligned.m64n32k32.f32.bf16.bf16 {%0, %1, %2, %3, %4, %5, %6, %7, %8, %9, %10, %11, %12, %13, %14, %15}, {%32, %33, %34, %35}, db, %42, 0, 1, 1, 1, 1;\n"
    "add.s64 db, %40, %41 + 640;\n"
    "wgmma.mma_async.sp.sync.aligned.m64n32k32.f32.bf16.bf16 {%0, %1, %2, %3, %4, %5, %6, %7, %8, %9, %10, %11, %12, %13, %14, %15}, {%36, %37, %38, %39}, db, %42, 0, 1, 1, 1, 1;\n"
    "wgmma.commit_group.sync.aligned;\n}\n"
    : "=f"(d[0]), "=f"(d[1]), "=f"(d[2]), "=f"(d[3]), "=f"(d[4]), "=f"(d[5]), "=f"(d[6]), "=f"(d[7]), "=f"(d[8]), "=f"(d[9]), "=f"(d[10]), "=f"(d[11]), "=f"(d[12]), "=f"(d[13]), "=f"(d[14]), "=f"(d[15])
    : "r"(a[0]), "r"(a[1]), "r"(a[2]), "r"(a[3]), "r"(a[4]), "r"(a[5]), "r"(a[6]), "r"(a[7]), "r"(a[8]), "r"(a[9]), "r"(a[10]), "r"(a[11]), "r"(a[12]), "r"(a[13]), "r"(a[14]), "r"(a[15]), "r"(a[16]), "r"(a[17]), "r"(a[18]), "r"(a[19]), "r"(a[20]), "r"(a[21]), "r"(a[22]), "r"(a[23]), "l"(db), "n"(D), "r"(meta)
    : "memory");
}
template<int D> __device__ __forceinline__ void c2_more(float (&d)[16], const uint32_t (&a)[24], uint64_t db, uint32_t meta) {
  asm volatile("{\n.reg .b64 db;\n"
    "wgmma.fence.sync.aligned;\n"
    "add.s64 db, %40, %41 + 0;\n"
    "wgmma.mma_async.sp.sync.aligned.m64n32k32.f32.bf16.bf16 {%0, %1, %2, %3, %4, %5, %6, %7, %8, %9, %10, %11, %12, %13, %14, %15}, {%16, %17, %18, %19}, db, %42, 0, 1, 1, 1, 1;\n"
    "add.s64 db, %40, %41 + 128;\n"
    "wgmma.mma_async.sp.sync.aligned.m64n32k32.f32.bf16.bf16 {%0, %1, %2, %3, %4, %5, %6, %7, %8, %9, %10, %11, %12, %13, %14, %15}, {%20, %21, %22, %23}, db, %42, 0, 1, 1, 1, 1;\n"
    "add.s64 db, %40, %41 + 256;\n"
    "wgmma.mma_async.sp.sync.aligned.m64n32k32.f32.bf16.bf16 {%0, %1, %2, %3, %4, %5, %6, %7, %8, %9, %10, %11, %12, %13, %14, %15}, {%24, %25, %26, %27}, db, %42, 0, 1, 1, 1, 1;\n"
    "add.s64 db, %40, %41 + 384;\n"
    "wgmma.mma_async.sp.sync.aligned.m64n32k32.f32.bf16.bf16 {%0, %1, %2, %3, %4, %5, %6, %7, %8, %9, %10, %11, %12, %13, %14, %15}, {%28, %29, %30, %31}, db, %42, 0, 1, 1, 1, 1;\n"
    "add.s64 db, %40, %41 + 512;\n"
    "wgmma.mma_async.sp.sync.aligned.m64n32k32.f32.bf16.bf16 {%0, %1, %2, %3, %4, %5, %6, %7, %8, %9, %10, %11, %12, %13, %14, %15}, {%32, %33, %34, %35}, db, %42, 0, 1, 1, 1, 1;\n"
    "add.s64 db, %40, %41 + 640;\n"
    "wgmma.mma_async.sp.sync.aligned.m64n32k32.f32.bf16.bf16 {%0, %1, %2, %3, %4, %5, %6, %7, %8, %9, %10, %11, %12, %13, %14, %15}, {%36, %37, %38, %39}, db, %42, 0, 1, 1, 1, 1;\n"
    "wgmma.commit_group.sync.aligned;\n}\n"
    : "+f"(d[0]), "+f"(d[1]), "+f"(d[2]), "+f"(d[3]), "+f"(d[4]), "+f"(d[5]), "+f"(d[6]), "+f"(d[7]), "+f"(d[8]), "+f"(d[9]), "+f"(d[10]), "+f"(d[11]), "+f"(d[12]), "+f"(d[13]), "+f"(d[14]), "+f"(d[15])
    : "r"(a[0]), "r"(a[1]), "r"(a[2]), "r"(a[3]), "r"(a[4]), "r"(a[5]), "r"(a[6]), "r"(a[7]), "r"(a[8]), "r"(a[9]), "r"(a[10]), "r"(a[11]), "r"(a[12]), "r"(a[13]), "r"(a[14]), "r"(a[15]), "r"(a[16]), "r"(a[17]), "r"(a[18]), "r"(a[19]), "r"(a[20]), "r"(a[21]), "r"(a[22]), "r"(a[23]), "l"(db), "n"(D), "r"(meta)
    : "memory");
}
template<int D> __device__ __forceinline__ void c2_first(float (&d)[16], const uint32_t (&a)[28], uint64_t db, uint32_t meta) {
  asm volatile("{\n.reg .b64 db;\n"
    "wgmma.fence.sync.aligned;\n"
    "add.s64 db, %44, %45 + 0;\n"
    "wgmma.mma_async.sp.sync.aligned.m64n32k32.f32.bf16.bf16 {%0, %1, %2, %3, %4, %5, %6, %7, %8, %9, %10, %11, %12, %13, %14, %15}, {%16, %17, %18, %19}, db, %46, 0, 0, 1, 1, 1;\n"
    "add.s64 db, %44, %45 + 128;\n"
    "wgmma.mma_async.sp.sync.aligned.m64n32k32.f32.bf16.bf16 {%0, %1, %2, %3, %4, %5, %6, %7, %8, %9, %10, %11, %12, %13, %14, %15}, {%20, %21, %22, %23}, db, %46, 0, 1, 1, 1, 1;\n"
    "add.s64 db, %44, %45 + 256;\n"
    "wgmma.mma_async.sp.sync.aligned.m64n32k32.f32.bf16.bf16 {%0, %1, %2, %3, %4, %5, %6, %7, %8, %9, %10, %11, %12, %13, %14, %15}, {%24, %25, %26, %27}, db, %46, 0, 1, 1, 1, 1;\n"
    "add.s64 db, %44, %45 + 384;\n"
    "wgmma.mma_async.sp.sync.aligned.m64n32k32.f32.bf16.bf16 {%0, %1, %2, %3, %4, %5, %6, %7, %8, %9, %10, %11, %12, %13, %14, %15}, {%28, %29, %30, %31}, db, %46, 0, 1, 1, 1, 1;\n"
    "add.s64 db, %44, %45 + 512;\n"
    "wgmma.mma_async.sp.sync.aligned.m64n32k32.f32.bf16.bf16 {%0, %1, %2, %3, %4, %5, %6, %7, %8, %9, %10, %11, %12, %13, %14, %15}, {%32, %33, %34, %35}, db, %46, 0, 1, 1, 1, 1;\n"
    "add.s64 db, %44, %45 + 640;\n"
    "wgmma.mma_async.sp.sync.aligned.m64n32k32.f32.bf16.bf16 {%0, %1, %2, %3, %4, %5, %6, %7, %8, %9, %10, %11, %12, %13, %14, %15}, {%36, %37, %38, %39}, db, %46, 0, 1, 1, 1, 1;\n"
    "add.s64 db, %44, %45 + 768;\n"
    "wgmma.mma_async.sp.sync.aligned.m64n32k32.f32.bf16.bf16 {%0, %1, %2, %3, %4, %5, %6, %7, %8, %9, %10, %11, %12, %13, %14, %15}, {%40, %41, %42, %43}, db, %46, 0, 1, 1, 1, 1;\n"
    "wgmma.commit_group.sync.aligned;\n}\n"
    : "=f"(d[0]), "=f"(d[1]), "=f"(d[2]), "=f"(d[3]), "=f"(d[4]), "=f"(d[5]), "=f"(d[6]), "=f"(d[7]), "=f"(d[8]), "=f"(d[9]), "=f"(d[10]), "=f"(d[11]), "=f"(d[12]), "=f"(d[13]), "=f"(d[14]), "=f"(d[15])
    : "r"(a[0]), "r"(a[1]), "r"(a[2]), "r"(a[3]), "r"(a[4]), "r"(a[5]), "r"(a[6]), "r"(a[7]), "r"(a[8]), "r"(a[9]), "r"(a[10]), "r"(a[11]), "r"(a[12]), "r"(a[13]), "r"(a[14]), "r"(a[15]), "r"(a[16]), "r"(a[17]), "r"(a[18]), "r"(a[19]), "r"(a[20]), "r"(a[21]), "r"(a[22]), "r"(a[23]), "r"(a[24]), "r"(a[25]), "r"(a[26]), "r"(a[27]), "l"(db), "n"(D), "r"(meta)
    : "memory");
}
template<int D> __device__ __forceinline__ void c2_more(float (&d)[16], const uint32_t (&a)[28], uint64_t db, uint32_t meta) {
  asm volatile("{\n.reg .b64 db;\n"
    "wgmma.fence.sync.aligned;\n"
    "add.s64 db, %44, %45 + 0;\n"
    "wgmma.mma_async.sp.sync.aligned.m64n32k32.f32.bf16.bf16 {%0, %1, %2, %3, %4, %5, %6, %7, %8, %9, %10, %11, %12, %13, %14, %15}, {%16, %17, %18, %19}, db, %46, 0, 1, 1, 1, 1;\n"
    "add.s64 db, %44, %45 + 128;\n"
    "wgmma.mma_async.sp.sync.aligned.m64n32k32.f32.bf16.bf16 {%0, %1, %2, %3, %4, %5, %6, %7, %8, %9, %10, %11, %12, %13, %14, %15}, {%20, %21, %22, %23}, db, %46, 0, 1, 1, 1, 1;\n"
    "add.s64 db, %44, %45 + 256;\n"
    "wgmma.mma_async.sp.sync.aligned.m64n32k32.f32.bf16.bf16 {%0, %1, %2, %3, %4, %5, %6, %7, %8, %9, %10, %11, %12, %13, %14, %15}, {%24, %25, %26, %27}, db, %46, 0, 1, 1, 1, 1;\n"
    "add.s64 db, %44, %45 + 384;\n"
    "wgmma.mma_async.sp.sync.aligned.m64n32k32.f32.bf16.bf16 {%0, %1, %2, %3, %4, %5, %6, %7, %8, %9, %10, %11, %12, %13, %14, %15}, {%28, %29, %30, %31}, db, %46, 0, 1, 1, 1, 1;\n"
    "add.s64 db, %44, %45 + 512;\n"
    "wgmma.mma_async.sp.sync.aligned.m64n32k32.f32.bf16.bf16 {%0, %1, %2, %3, %4, %5, %6, %7, %8, %9, %10, %11, %12, %13, %14, %15}, {%32, %33, %34, %35}, db, %46, 0, 1, 1, 1, 1;\n"
    "add.s64 db, %44, %45 + 640;\n"
    "wgmma.mma_async.sp.sync.aligned.m64n32k32.f32.bf16.bf16 {%0, %1, %2, %3, %4, %5, %6, %7, %8, %9, %10, %11, %12, %13, %14, %15}, {%36, %37, %38, %39}, db, %46, 0, 1, 1, 1, 1;\n"
    "add.s64 db, %44, %45 + 768;\n"
    "wgmma.mma_async.sp.sync.aligned.m64n32k32.f32.bf16.bf16 {%0, %1, %2, %3, %4, %5, %6, %7, %8, %9, %10, %11, %12, %13, %14, %15}, {%40, %41, %42, %43}, db, %46, 0, 1, 1, 1, 1;\n"
    "wgmma.commit_group.sync.aligned;\n}\n"
    : "+f"(d[0]), "+f"(d[1]), "+f"(d[2]), "+f"(d[3]), "+f"(d[4]), "+f"(d[5]), "+f"(d[6]), "+f"(d[7]), "+f"(d[8]), "+f"(d[9]), "+f"(d[10]), "+f"(d[11]), "+f"(d[12]), "+f"(d[13]), "+f"(d[14]), "+f"(d[15])
    : "r"(a[0]), "r"(a[1]), "r"(a[2]), "r"(a[3]), "r"(a[4]), "r"(a[5]), "r"(a[6]), "r"(a[7]), "r"(a[8]), "r"(a[9]), "r"(a[10]), "r"(a[11]), "r"(a[12]), "r"(a[13]), "r"(a[14]), "r"(a[15]), "r"(a[16]), "r"(a[17]), "r"(a[18]), "r"(a[19]), "r"(a[20]), "r"(a[21]), "r"(a[22]), "r"(a[23]), "r"(a[24]), "r"(a[25]), "r"(a[26]), "r"(a[27]), "l"(db), "n"(D), "r"(meta)
    : "memory");
}
template<int N> __device__ __forceinline__ void mma_wait(float (&d)[4]) {
  asm volatile("wgmma.wait_group.sync.aligned %4;"
    : "+f"(d[0]), "+f"(d[1]), "+f"(d[2]), "+f"(d[3])
    : "n"(N) : "memory");
}
template<int N> __device__ __forceinline__ void mma_wait(float (&d)[16]) {
  asm volatile("wgmma.wait_group.sync.aligned %16;"
    : "+f"(d[0]), "+f"(d[1]), "+f"(d[2]), "+f"(d[3]), "+f"(d[4]), "+f"(d[5]), "+f"(d[6]), "+f"(d[7]), "+f"(d[8]), "+f"(d[9]), "+f"(d[10]), "+f"(d[11]), "+f"(d[12]), "+f"(d[13]), "+f"(d[14]), "+f"(d[15])
    : "n"(N) : "memory");
}
template<int N> __device__ __forceinline__ void mma_wait(float (&d)[20]) {
  asm volatile("wgmma.wait_group.sync.aligned %20;"
    : "+f"(d[0]), "+f"(d[1]), "+f"(d[2]), "+f"(d[3]), "+f"(d[4]), "+f"(d[5]), "+f"(d[6]), "+f"(d[7]), "+f"(d[8]), "+f"(d[9]), "+f"(d[10]), "+f"(d[11]), "+f"(d[12]), "+f"(d[13]), "+f"(d[14]), "+f"(d[15]), "+f"(d[16]), "+f"(d[17]), "+f"(d[18]), "+f"(d[19])
    : "n"(N) : "memory");
}
template<int N> __device__ __forceinline__ void mma_wait(float (&d)[24]) {
  asm volatile("wgmma.wait_group.sync.aligned %24;"
    : "+f"(d[0]), "+f"(d[1]), "+f"(d[2]), "+f"(d[3]), "+f"(d[4]), "+f"(d[5]), "+f"(d[6]), "+f"(d[7]), "+f"(d[8]), "+f"(d[9]), "+f"(d[10]), "+f"(d[11]), "+f"(d[12]), "+f"(d[13]), "+f"(d[14]), "+f"(d[15]), "+f"(d[16]), "+f"(d[17]), "+f"(d[18]), "+f"(d[19]), "+f"(d[20]), "+f"(d[21]), "+f"(d[22]), "+f"(d[23])
    : "n"(N) : "memory");
}
template<int N> __device__ __forceinline__ void mma_wait(float (&d)[28]) {
  asm volatile("wgmma.wait_group.sync.aligned %28;"
    : "+f"(d[0]), "+f"(d[1]), "+f"(d[2]), "+f"(d[3]), "+f"(d[4]), "+f"(d[5]), "+f"(d[6]), "+f"(d[7]), "+f"(d[8]), "+f"(d[9]), "+f"(d[10]), "+f"(d[11]), "+f"(d[12]), "+f"(d[13]), "+f"(d[14]), "+f"(d[15]), "+f"(d[16]), "+f"(d[17]), "+f"(d[18]), "+f"(d[19]), "+f"(d[20]), "+f"(d[21]), "+f"(d[22]), "+f"(d[23]), "+f"(d[24]), "+f"(d[25]), "+f"(d[26]), "+f"(d[27])
    : "n"(N) : "memory");
}
template<int N> __device__ __forceinline__ void mma_wait(float (&d)[32]) {
  asm volatile("wgmma.wait_group.sync.aligned %32;"
    : "+f"(d[0]), "+f"(d[1]), "+f"(d[2]), "+f"(d[3]), "+f"(d[4]), "+f"(d[5]), "+f"(d[6]), "+f"(d[7]), "+f"(d[8]), "+f"(d[9]), "+f"(d[10]), "+f"(d[11]), "+f"(d[12]), "+f"(d[13]), "+f"(d[14]), "+f"(d[15]), "+f"(d[16]), "+f"(d[17]), "+f"(d[18]), "+f"(d[19]), "+f"(d[20]), "+f"(d[21]), "+f"(d[22]), "+f"(d[23]), "+f"(d[24]), "+f"(d[25]), "+f"(d[26]), "+f"(d[27]), "+f"(d[28]), "+f"(d[29]), "+f"(d[30]), "+f"(d[31])
    : "n"(N) : "memory");
}
template<int N> __device__ __forceinline__ void mma_wait(float (&d)[36]) {
  asm volatile("wgmma.wait_group.sync.aligned %36;"
    : "+f"(d[0]), "+f"(d[1]), "+f"(d[2]), "+f"(d[3]), "+f"(d[4]), "+f"(d[5]), "+f"(d[6]), "+f"(d[7]), "+f"(d[8]), "+f"(d[9]), "+f"(d[10]), "+f"(d[11]), "+f"(d[12]), "+f"(d[13]), "+f"(d[14]), "+f"(d[15]), "+f"(d[16]), "+f"(d[17]), "+f"(d[18]), "+f"(d[19]), "+f"(d[20]), "+f"(d[21]), "+f"(d[22]), "+f"(d[23]), "+f"(d[24]), "+f"(d[25]), "+f"(d[26]), "+f"(d[27]), "+f"(d[28]), "+f"(d[29]), "+f"(d[30]), "+f"(d[31]), "+f"(d[32]), "+f"(d[33]), "+f"(d[34]), "+f"(d[35])
    : "n"(N) : "memory");
}
template<int N> __device__ __forceinline__ void mma_wait(float (&d)[44]) {
  asm volatile("wgmma.wait_group.sync.aligned %44;"
    : "+f"(d[0]), "+f"(d[1]), "+f"(d[2]), "+f"(d[3]), "+f"(d[4]), "+f"(d[5]), "+f"(d[6]), "+f"(d[7]), "+f"(d[8]), "+f"(d[9]), "+f"(d[10]), "+f"(d[11]), "+f"(d[12]), "+f"(d[13]), "+f"(d[14]), "+f"(d[15]), "+f"(d[16]), "+f"(d[17]), "+f"(d[18]), "+f"(d[19]), "+f"(d[20]), "+f"(d[21]), "+f"(d[22]), "+f"(d[23]), "+f"(d[24]), "+f"(d[25]), "+f"(d[26]), "+f"(d[27]), "+f"(d[28]), "+f"(d[29]), "+f"(d[30]), "+f"(d[31]), "+f"(d[32]), "+f"(d[33]), "+f"(d[34]), "+f"(d[35]), "+f"(d[36]), "+f"(d[37]), "+f"(d[38]), "+f"(d[39]), "+f"(d[40]), "+f"(d[41]), "+f"(d[42]), "+f"(d[43])
    : "n"(N) : "memory");
}
__device__ __forceinline__ void mma_fence() { asm volatile("wgmma.fence.sync.aligned;" ::: "memory"); }

__device__ __forceinline__ uint32_t smem_u32(const void* p) { return (uint32_t)__cvta_generic_to_shared(p); }

__device__ __forceinline__ void mbar_init(uint32_t bar, uint32_t cnt) {
  asm volatile("mbarrier.init.shared::cta.b64 [%0], %1;" :: "r"(bar), "r"(cnt) : "memory");
}
__device__ __forceinline__ void mbar_arrive(uint32_t bar) {
  asm volatile("mbarrier.arrive.shared::cta.b64 _, [%0];" :: "r"(bar) : "memory");
}
__device__ __forceinline__ void mbar_wait(uint32_t bar, uint32_t parity) {
  asm volatile("{\n.reg .pred p;\n.reg .u32 n;\n"
               "mov.u32 n, 0;\n"
               "WAIT_LOOP:\n"
               "mbarrier.try_wait.parity.shared::cta.b64 p, [%0], %1;\n"
               "@p bra.uni WAIT_DONE;\n"
               "add.u32 n, n, 1;\n"
               "setp.lt.u32 p, n, 0x1000000;\n"
               "@p bra.uni WAIT_LOOP;\n"
               "trap;\n"
               "WAIT_DONE:\n}\n"
               :: "r"(bar), "r"(parity) : "memory");
}
__device__ __forceinline__ void mbar_wait_unless(uint32_t ok, uint32_t bar, uint32_t parity) {
  asm volatile("{\n.reg .pred p;\n.reg .u32 n;\n"
               "setp.ne.u32 p, %2, 0;\n"
               "@p bra.uni WAIT_DONE;\n"
               "mov.u32 n, 0;\n"
               "WAIT_LOOP:\n"
               "mbarrier.try_wait.parity.shared::cta.b64 p, [%0], %1;\n"
               "@p bra.uni WAIT_DONE;\n"
               "add.u32 n, n, 1;\n"
               "setp.lt.u32 p, n, 0x1000000;\n"
               "@p bra.uni WAIT_LOOP;\n"
               "trap;\n"
               "WAIT_DONE:\n}\n"
               :: "r"(bar), "r"(parity), "r"(ok) : "memory");
}
__device__ __forceinline__ uint32_t mbar_test(uint32_t bar, uint32_t parity) {
  uint32_t ok;
  asm volatile("{\n.reg .pred p;\nmbarrier.test_wait.parity.shared::cta.b64 p, [%1], %2;\nselp.u32 %0, 1, 0, p;\n}\n"
               : "=r"(ok) : "r"(bar), "r"(parity) : "memory");
  return ok;
}
__device__ __forceinline__ void cp_async16(uint32_t dst, const void* src) {
  asm volatile("cp.async.cg.shared.global [%0], [%1], 16;" :: "r"(dst), "l"(src) : "memory");
}
#define DIN_ADDR4                                                                        \
  "mov.b64 {x, y}, %0;\ndp4a.u32.u32 x, %8, 0x80, %11;\nmov.b64 %0, {x, y};\n"           \
  "mov.b64 {x, y}, %1;\ndp4a.u32.u32 x, %8, 0x8000, %11;\nmov.b64 %1, {x, y};\n"         \
  "mov.b64 {x, y}, %2;\ndp4a.u32.u32 x, %8, 0x800000, %11;\nmov.b64 %2, {x, y};\n"       \
  "mov.b64 {x, y}, %3;\ndp4a.u32.u32 x, %8, 0x80000000, %11;\nmov.b64 %3, {x, y};\n"
template<int T>
__device__ __forceinline__ void cp_group(const uint32_t (&dst)[4], uint64_t (&a)[4], uint32_t rows4, uint32_t base, uint64_t pol) {
  asm volatile("{\n.reg .u32 x, y;\n" DIN_ADDR4
               "cp.async.cg.shared.global.L2::cache_hint [%4 + %10], [%0], 16, %9;\n"
               "cp.async.cg.shared.global.L2::cache_hint [%5 + %10], [%1], 16, %9;\n"
               "cp.async.cg.shared.global.L2::cache_hint [%6 + %10], [%2], 16, %9;\n"
               "cp.async.cg.shared.global.L2::cache_hint [%7 + %10], [%3], 16, %9;\n}\n"
               : "+l"(a[0]), "+l"(a[1]), "+l"(a[2]), "+l"(a[3])
               : "r"(dst[0]), "r"(dst[1]), "r"(dst[2]), "r"(dst[3]), "r"(rows4), "l"(pol), "n"(T * 2048), "r"(base) : "memory");
}
template<int T>
__device__ __forceinline__ void cp_group_z(const uint32_t (&dst)[4], uint64_t (&a)[4], uint32_t rows4, uint32_t base, int left, uint64_t pol) {
  asm volatile("{\n.reg .u32 x, y;\n.reg .pred p0, p1, p2, p3;\n" DIN_ADDR4
               "setp.le.s32 p0, %12, %13;\nsetp.le.s32 p1, %12, %13 + 1;\nsetp.le.s32 p2, %12, %13 + 2;\nsetp.le.s32 p3, %12, %13 + 3;\n"
               "cp.async.cg.shared.global.L2::cache_hint [%4 + %10], [%0], 16, p0, %9;\n"
               "cp.async.cg.shared.global.L2::cache_hint [%5 + %10], [%1], 16, p1, %9;\n"
               "cp.async.cg.shared.global.L2::cache_hint [%6 + %10], [%2], 16, p2, %9;\n"
               "cp.async.cg.shared.global.L2::cache_hint [%7 + %10], [%3], 16, p3, %9;\n}\n"
               : "+l"(a[0]), "+l"(a[1]), "+l"(a[2]), "+l"(a[3])
               : "r"(dst[0]), "r"(dst[1]), "r"(dst[2]), "r"(dst[3]), "r"(rows4), "l"(pol), "n"(T * 2048), "r"(base),
                 "r"(left), "n"(T * 16) : "memory");
}
__device__ __forceinline__ uint32_t prmt(uint32_t a, uint32_t b, uint32_t sel) {
  uint32_t d;
  asm("prmt.b32 %0, %1, %2, %3;" : "=r"(d) : "r"(a), "r"(b), "r"(sel));
  return d;
}
__device__ __forceinline__ uint32_t ballot_bit(uint32_t x, uint32_t bit) {
  uint32_t d;
  asm volatile("{\n.reg .pred p;\n.reg .u32 t;\nand.b32 t, %1, %2;\nsetp.ne.u32 p, t, 0;\nvote.sync.ballot.b32 %0, p, 0xffffffff;\n}\n"
               : "=r"(d) : "r"(x), "r"(bit));
  return d;
}
__device__ __forceinline__ uint4 load_mask(const void* mask, uint32_t b, uint32_t i) {
  uint4 m;
  asm volatile("ld.global.nc.L1::no_allocate.v4.u32 {%0,%1,%2,%3}, [%4];"
               : "=r"(m.x), "=r"(m.y), "=r"(m.z), "=r"(m.w) : "l"(reinterpret_cast<const uint4*>(mask) + (b * 25u + i)));
  return m;
}
__device__ __forceinline__ uint32_t nonzero_as_one(uint32_t x) {
  uint32_t d;
  asm("set.neu.bf16x2.bf16x2 %0, %1, %2;" : "=r"(d) : "r"(x), "r"(0u));
  return d;
}
__device__ __forceinline__ void cp_async_arrive_noinc(uint32_t bar) {
  asm volatile("cp.async.mbarrier.arrive.noinc.shared::cta.b64 [%0];" :: "r"(bar) : "memory");
}
__device__ __forceinline__ void ldsm_x4(uint32_t addr, uint32_t& r0, uint32_t& r1, uint32_t& r2, uint32_t& r3) {
  asm volatile("ldmatrix.sync.aligned.m8n8.x4.shared.b16 {%0,%1,%2,%3}, [%4];"
               : "=r"(r0), "=r"(r1), "=r"(r2), "=r"(r3) : "r"(addr) : "memory");
}
__device__ __forceinline__ void ldsm_x4_t(uint32_t addr, uint32_t& r0, uint32_t& r1, uint32_t& r2, uint32_t& r3) {
  asm volatile("ldmatrix.sync.aligned.m8n8.x4.trans.shared.b16 {%0,%1,%2,%3}, [%4];"
               : "=r"(r0), "=r"(r1), "=r"(r2), "=r"(r3) : "r"(addr) : "memory");
}
__device__ __forceinline__ void stsm_x4(uint32_t addr, uint32_t r0, uint32_t r1, uint32_t r2, uint32_t r3) {
  asm volatile("stmatrix.sync.aligned.m8n8.x4.shared.b16 [%0], {%1,%2,%3,%4};"
               :: "r"(addr), "r"(r0), "r"(r1), "r"(r2), "r"(r3) : "memory");
}
__device__ __forceinline__ void stsm_x2(uint32_t addr, uint32_t r0, uint32_t r1) {
  asm volatile("stmatrix.sync.aligned.m8n8.x2.shared.b16 [%0], {%1,%2};"
               :: "r"(addr), "r"(r0), "r"(r1) : "memory");
}
__device__ __forceinline__ uint32_t hfma2_bf16(uint32_t a, uint32_t b, uint32_t c) {
  uint32_t d;
  asm volatile("fma.rn.bf16x2 %0, %1, %2, %3;" : "=r"(d) : "r"(a), "r"(b), "r"(c));
  return d;
}
__device__ __forceinline__ uint32_t pack_bf16(float lo, float hi) {
  uint32_t d;
  asm("cvt.rn.bf16x2.f32 %0, %1, %2;" : "=r"(d) : "f"(hi), "f"(lo));
  return d;
}
__device__ __forceinline__ uint32_t lds32(uint32_t a) {
  uint32_t v; asm volatile("ld.shared.u32 %0, [%1];" : "=r"(v) : "r"(a) : "memory"); return v;
}
__device__ __forceinline__ uint32_t lds16(uint32_t a) {
  uint32_t v; asm volatile("ld.shared.u16 %0, [%1];" : "=r"(v) : "r"(a) : "memory"); return v;
}
__device__ __forceinline__ void sts32(uint32_t a, uint32_t v) {
  asm volatile("st.shared.u32 [%0], %1;" :: "r"(a), "r"(v) : "memory");
}
__device__ __forceinline__ void sts16(uint32_t a, uint32_t v) {
  asm volatile("st.shared.u16 [%0], %1;" :: "r"(a), "h"((unsigned short)v) : "memory");
}
__device__ __forceinline__ void sts8(uint32_t a, uint32_t v) {
  asm volatile("st.shared.u8 [%0], %1;" :: "r"(a), "r"(v) : "memory");
}
constexpr uint32_t DESC_ROWS = 0x40000040u, DESC_HALVES = 0x80000020u;
__device__ __forceinline__ uint32_t desc_lo(uint32_t addr) { return ((addr & 0x3FFFF) >> 4) | (1u << 16); }

__device__ __forceinline__ uint4 lds128(uint32_t a) {
  uint4 v;
  asm volatile("ld.shared.v4.u32 {%0,%1,%2,%3}, [%4];" : "=r"(v.x), "=r"(v.y), "=r"(v.z), "=r"(v.w) : "r"(a) : "memory");
  return v;
}
__device__ __forceinline__ void sts128(uint32_t a, uint4 v) {
  asm volatile("st.shared.v4.u32 [%0], {%1,%2,%3,%4};" :: "r"(a), "r"(v.x), "r"(v.y), "r"(v.z), "r"(v.w) : "memory");
}
__device__ __forceinline__ void prefetch_l2(const void* p, uint32_t bytes) {
  asm volatile("cp.async.bulk.prefetch.L2.global [%0], %1;" :: "l"(p), "r"(bytes) : "memory");
}

template<int ND>
__device__ __forceinline__ void tanh_groups(float (&d)[ND], int i0, int i1) {
#pragma unroll
  for (int i = 4 * i0; i < 4 * i1; i++) asm volatile("tanh.approx.f32 %0, %0;" : "+f"(d[i ^ 2]));
}
template<int ND>
__device__ __forceinline__ uint32_t mix(const float (&d)[ND], int i, float w2a, float w2b, float c32) {
  uint32_t p;
  asm volatile("{\n.reg .f32 x, y;\nfma.rn.f32 x, %3, %6, %7;\nfma.rn.f32 y, %4, %6, %7;\n"
               "fma.rn.f32 x, %1, %5, x;\nfma.rn.f32 y, %2, %5, y;\ncvt.rn.bf16x2.f32 %0, y, x;\n}\n"
               : "=r"(p) : "f"(d[4 * i]), "f"(d[4 * i + 1]), "f"(d[4 * i + 2]), "f"(d[4 * i + 3]), "f"(w2a), "f"(w2b), "f"(c32));
  return p;
}
template<int K> __device__ __forceinline__ uint32_t keep(uint32_t x) { return K ? __shfl_sync(0xffffffffu, x, 0) : x; }
template<int V> struct Int { static constexpr int value = V; };

__global__ void __launch_bounds__(NTHREADS, 1)
din_kernel(const __nv_bfloat16* __restrict__ mask, const __nv_bfloat16* __restrict__ target, int B, int grid,
           uint32_t pf_mask, uint32_t pf_tgt, const __nv_bfloat16* __restrict__ w1, const __nv_bfloat16* __restrict__ hist,
           const __nv_bfloat16* __restrict__ b1, const __nv_bfloat16* __restrict__ w2,
           const __nv_bfloat16* __restrict__ b2, __nv_bfloat16* __restrict__ out, unsigned int* counter, int pace,
           int slow_from, int pace_slow, int spread) {
  {
    const char* pm = reinterpret_cast<const char*>(mask) + (size_t)blockIdx.x * pf_mask;
    const char* pt = reinterpret_cast<const char*>(target) + (size_t)blockIdx.x * pf_tgt;
    const uint32_t o = threadIdx.x * 128;
    asm volatile("{\n.reg .pred p;\nsetp.lt.u32 p, %1, %2;\n@p prefetch.global.L2 [%0];\n}\n" :: "l"(pm + o), "r"(o), "r"(pf_mask));
    asm volatile("{\n.reg .pred p;\nsetp.lt.u32 p, %1, %2;\n@p prefetch.global.L2 [%0];\n}\n" :: "l"(pt + o), "r"(o), "r"(pf_tgt));
  }
  extern __shared__ unsigned char smem_raw[];
  const uint32_t sb = (smem_u32(smem_raw) + 1023u) & ~1023u;
  const int tid = threadIdx.x, lane = tid & 31;
  const int warp = __shfl_sync(0xffffffffu, tid >> 5, 0);
#define ACT NCW
  const int bstep = ACT * grid;

  STAMP(0);
  if (warp < NCW * 4) {
    const int wg = warp >> 2, w = warp & 3;
    const int g = lane >> 2;
    const uint32_t ring = sb + wg * RING_BYTES;
    const bool active = wg * grid + (int)blockIdx.x < B && wg < ACT;
    {
      const int t = tid & 127;
      const uint32_t dst = sb + ((t ^ ((t >> 3) & 7)) << 4);
      const char* src = reinterpret_cast<const char*>(w1) + t * 16;
#pragma unroll
      for (int i = 0; i < 4; i++) cp_async16(dst + w1_at(i) + wg * 2048, src + i * 8192 + wg * 2048);
      cp_async16(dst + w1_at(0) + (wg >> 1) * RING_BYTES + (wg & 1) * SLOT_BYTES + 6144, src + wg * 8192 + 6144);
      if (wg == 0) cp_async16(dst + w1_at(3) + 6144, src + 3 * 8192 + 6144);
      if (lane < 8) {
        if (w == 0 && active) cp_async16(ring + R_TGT0 + lane * 16, target + (size_t)(wg * grid + blockIdx.x) * kD + lane * 8);
        if (w == 1 && wg < 2) cp_async16(ring + R_VEC + lane * 16, (wg ? w2 : b1) + lane * 8);
      }
    }
    if (w == 2) sts32(ring + R_SEL + lane * 4, 0x3f803f80u);
    uint32_t rb2;
    asm volatile("ld.global.nc.u16 %0, [%1];" : "=r"(rb2) : "l"(b2));
    asm volatile("setmaxnreg.inc.sync.aligned.u32 %0;" :: "n"(CONS_REGS));
    asm volatile("cp.async.wait_all;" ::: "memory");
    STAMP(5);
    asm volatile("bar.sync 1, %0;" :: "n"(NCW * 160) : "memory");
    const uint32_t half2 = 0x3f003f00u, nhalf2 = 0xbf00bf00u, nzero2 = 0x80008000u;
    const uint32_t vec = sb + R_VEC + (16 * w + g) * 2;
    const float w2a = 0.5f * __uint_as_float(lds16(vec + RING_BYTES) << 16);
    const float w2b = 0.5f * __uint_as_float(lds16(vec + RING_BYTES + 16) << 16);
    const uint32_t rw2 = lds32(sb + RING_BYTES + R_VEC + lane * 4);
    float c32 = __uint_as_float(rw2 << 16) + __uint_as_float(rw2 & 0xffff0000u);
#pragma unroll
    for (int o = 16; o; o >>= 1) c32 += __shfl_xor_sync(0xffffffffu, c32, o);
    c32 = (0.5f * c32 + __uint_as_float(rb2 << 16)) * (1.0f / 32.0f);
    uint32_t bq[4];
    bq[2] = hfma2_bf16(lds16(vec), half2, nzero2);
    bq[3] = hfma2_bf16(lds16(vec + 16), half2, nzero2);
    if (lane & 3) bq[2] = bq[3] = 0;
    uint32_t wac[16], wd[16], wbc[16];
    {
      const int mi = lane >> 3, rr = lane & 7;
      const uint32_t a0 = sb + (8 * (mi >> 1) + rr) * 128 + (((2 * w + (mi & 1)) ^ rr) << 4);
#pragma unroll
      for (int ks = 0; ks < 4; ks++) {
        uint32_t A[4], Bm[4], C[4], Dm[4];
        ldsm_x4_t(a0 + ks * 2048 + w1_at(0), A[0], A[1], A[2], A[3]);
        ldsm_x4_t(a0 + ks * 2048 + w1_at(1), Bm[0], Bm[1], Bm[2], Bm[3]);
        ldsm_x4_t(a0 + ks * 2048 + w1_at(2), C[0], C[1], C[2], C[3]);
        ldsm_x4_t(a0 + ks * 2048 + w1_at(3), Dm[0], Dm[1], Dm[2], Dm[3]);
#pragma unroll
        for (int e = 0; e < 4; e++) {
          wac[4 * ks + e] = hfma2_bf16(A[e], half2, hfma2_bf16(C[e], half2, nzero2));
          wbc[4 * ks + e] = hfma2_bf16(Bm[e], half2, hfma2_bf16(C[e], nhalf2, nzero2));
          wd[4 * ks + e] = hfma2_bf16(Dm[e], half2, nzero2);
        }
      }
    }
    asm volatile("fence.proxy.async.shared::cta;" ::: "memory");
    asm volatile("bar.sync 5, %0;" :: "n"(NCW * 128) : "memory");

    const uint32_t ln = __shfl_sync(0xffffffffu, lane, lane);
    const uint32_t q0 = __shfl_sync(0xffffffffu, (lane & 3) ? 0u : 0xffffffffu, lane);
    const uint32_t meta = __shfl_sync(0xffffffffu, 0x88dddd88u + (grid >> 20), lane);
    const uint32_t zr = grid >> 20;
    const uint32_t sel = keep<K_SEL>(((ring + R_SEL) & 0x3FFFF) >> 4);
    const uint32_t ost = __shfl_sync(0xffffffffu, w * 2048 + lane * 16, lane);
    const uint32_t first = keep<K_FIRST>(ring);
    const uint32_t last = keep<K_LAST>(first + (NSLOT - 1) * SLOT_BYTES);
    uint32_t sa = first, phase = 0;
    uint32_t we[16];
    auto make_weff = [&](uint32_t ta) {
      uint32_t t[8];
      ta += (ln & 24) << 1;
      ldsm_x4(ta, t[0], t[1], t[2], t[3]);
      ldsm_x4(ta + 64, t[4], t[5], t[6], t[7]);
#pragma unroll
      for (int i = 0; i < 16; i++) we[i] = hfma2_bf16(t[i >> 1], wd[i], wac[i]);
    };
    auto make_bq = [&](const float (&bz)[4]) {
#pragma unroll
      for (int e = 0; e < 2; e++) {
        const uint32_t v = __float_as_uint(bz[2 * e]) & q0;
        const float hi = __uint_as_float(v & 0xffff0000u);
        bq[e] = pack_bf16(__uint_as_float(v) - hi, hi);
      }
    };
    if (active) {
      {
        float bz[4];
        uint64_t d0 = (uint64_t)DESC_ROWS << 32 | (ring + R_TGT0) >> 4;
        mma_fence();
        cbias<0>(bz, wbc, d0);
        make_weff(ring + R_TGT0);
        mma_wait<0>(bz);
        make_bq(bz);
      }
      STAMP(1);
      mbar_wait(ring + S_FULL, 0);
      uint32_t raw = lds32(ring + S_HDR), cur, hdr;
      uint32_t full = 0;
      while (true) {
        hdr = __shfl_sync(0xffffffffu, raw, 0);
        cur = sa;
        auto chunk = [&](auto groups) {
          constexpr int N8 = decltype(groups)::value, NY = N8 - NA;
          constexpr int KT = (N8 + 1) / 2, E2 = KT - (N8 < 16 ? KL : 3), E1 = E2 - (N8 < 16 ? KM : 0), E0 = K0 && N8 < 16 ? K0 : E1;
          float x[4 * NA], y[4 * NY], bz[4], o[16];
          uint32_t a[4 * E0], a1[E1 > E0 ? 4 * (E1 - E0) : 4], a2[E2 > E1 ? 4 * (E2 - E1) : 4], a3[4 * (KT - E2)];
          auto M = [&](int i0, int i1) {
#pragma unroll
            for (int i = i0; i < i1; i++) {
              uint32_t p = i < NA ? mix(x, i, w2a, w2b, c32) : i < N8 ? mix(y, i - NA, w2a, w2b, c32) : 0;
              if (N8 == 16) {
                uint32_t m = 0x3f803f80u;
                asm volatile("{\n.reg .pred p;\nsetp.ne.u32 p, %1, 0;\n@p ld.shared.u32 %0, [%2];\n}\n"
                             : "+r"(m) : "r"(hdr & H_GENERAL), "r"(cur + S_MASK + i * 16 + (ln & 3) * 4) : "memory");
                p = hfma2_bf16(p, m, 0x80008000u);
              }
              if (i < 2 * E0) a[2 * i] = a[2 * i + 1] = p;
              else if (i < 2 * E1) a1[2 * i - 4 * E0] = a1[2 * i - 4 * E0 + 1] = p;
              else if (i < 2 * E2) a2[2 * i - 4 * E1] = a2[2 * i - 4 * E1 + 1] = p;
              else a3[2 * i - 4 * E2] = a3[2 * i - 4 * E2 + 1] = p;
            }
          };
          int done = 0;
          auto T = [&](int upto) {
            upto = upto < 4 * NY ? upto : 4 * NY;
#pragma unroll
            for (int i = done; i < upto; i++) asm volatile("tanh.approx.f32 %0, %0;" : "+f"(y[i ^ 2]));
            done = upto > done ? upto : done;
          };
          auto pin4 = [&](uint32_t r0, uint32_t r1, uint32_t r2, uint32_t r3) {
            asm volatile("{\n.reg .pred p;\nsetp.ne.u32 p, %4, 0;\n@p st.shared.v4.u32 [%4], {%0,%1,%2,%3};\n}\n"
                         :: "r"(r0), "r"(r1), "r"(r2), "r"(r3), "r"(zr) : "memory");
          };
          uint64_t d1 = (uint64_t)(DESC_ROWS + (cur >> 24)) << 32 | ((cur >> 4) - DOFF);
          const uint32_t par = phase;
          phase ^= sa == last;
          sa = sa == last ? first : sa + SLOT_BYTES;
          mma_fence();
          sel_clr(x, bq, sel, 0);
          sel_clr(y, bq, sel, NY == NA ? zr : 0);
          if (EA) mbar_wait_unless(full, cur + S_FULL, par);
          else mbar_wait(cur + S_FULL, par);
          LOGT(0);
          DURT(sub);
          mma_fence();
          c1_acc<DOFF>(x, we, d1);
          if (SPLIT) {
            cbias<DOFF + S_TGT / 16>(bz, wbc, d1);
            mma_wait<1>(x);
            auto TX = [&](int i0, int i1) {
#pragma unroll
              for (int i = i0; i < i1; i++) asm volatile("tanh.approx.f32 %0, %0;" : "+f"(x[i ^ 2]));
            };
            auto PX = [&](int i0, int i1) {
#pragma unroll
              for (int i = i0; i < i1; i += 4) pin4(__float_as_uint(x[i]), __float_as_uint(x[i + 1]), __float_as_uint(x[i + 2]), __float_as_uint(x[i + 3]));
            };
            if (EARLY) {
              TX(0, 4 * SA - EARLY);
              const uint32_t ok = mbar_test(cur + S_REST, par);
              TX(4 * SA - EARLY, 4 * SA);
              mbar_wait_unless(ok, cur + S_REST, par);
            } else {
              TX(0, 4 * SA);
              mbar_wait(cur + S_REST, par);
            }
            mma_fence();
            c1_acc<DOFF + 64 * NA>(y, we, d1);
            TX(4 * SA, 4 * (SA + SB));
            if (__builtin_expect(zr != 0, 0)) {
              __nanosleep(zr);
#pragma unroll
              for (int i = 4 * (SA + SB); i < 4 * NA; i++) asm volatile("mov.b32 %0, %1;" : "=f"(x[i]) : "r"(ln));
            }
            if (BQE) { mma_wait<1>(bz); make_bq(bz); }
            TX(4 * (SA + SB), 4 * NA);
          } else {
            c1_acc<DOFF + 64 * NA>(y, we, d1);
            mma_wait<1>(x);
            cbias<DOFF + S_TGT / 16>(bz, wbc, d1);
            tanh_groups(x, 0, NA);
          }
          M(0, 4);
          if (PIN2) {
            if (__builtin_expect(zr != 0, 0)) {
              __nanosleep(zr);
#pragma unroll
              for (int i = 0; i < 8; i += 2) sts32(zr + i, a[i]);
#pragma unroll
              for (int i = 16; i < 4 * NA; i++) sts32(zr + i, __float_as_uint(x[i]));
              if (SPLIT && BQE) { sts32(zr, bq[0]); sts32(zr, bq[1]); }
            }
          } else {
          pin4(a[0], a[1], a[2], a[3]);
          pin4(a[4], a[5], a[6], a[7]);
          }
          mma_wait<SPLIT ? 0 : 1>(y);
          T(4 * (2 * E0 - NA));
          if (WP == 0) make_weff(cur + S_TGT);
          M(4, 2 * E0);
          asm volatile("{\n.reg .b32 lo, hi;\nmov.b64 {lo, hi}, %0;\nadd.u32 hi, hi, %1;\nmov.b64 %0, {lo, hi};\n}\n" : "+l"(d1) : "n"(DESC_HALVES - DESC_ROWS));
          auto after = [&](uint32_t g) {
            asm volatile("{\n.reg .b32 lo, hi, z;\n.reg .pred p;\nand.b32 z, %1, %2;\nsetp.ne.u32 p, z, 0;\nvote.sync.ballot.b32 z, p, 0xffffffff;\n"
                         "mov.b64 {lo, hi}, %0;\nadd.u32 " GATE_HALF ", z;\nmov.b64 %0, {lo, hi};\n}\n" : "+l"(d1) : "r"(g), "r"(zr));
          };
          auto any = [&](auto& v, int n) { return v[n - 2] | v[n - 4] | (n > 4 ? v[n - 6] : 0) | (n > 4 && GW4 ? v[n - 8] : 0); };
          if (GA & 1) after(any(a, 4 * E0));
          c2_first<DOFF>(o, a, d1, meta);
          if (WP == 1) make_weff(cur + S_TGT);
          if constexpr (E1 > E0) {
            T(4 * (2 * E1 - NA));
            M(2 * E0, 2 * E1);
            if (GA & 2) after(any(a1, 4 * (E1 - E0)));
            c2_more<DOFF + 128 * E0>(o, a1, d1, meta);
          }
          if (WP == 2) make_weff(cur + S_TGT);
          if constexpr (E2 > E1) {
            T(4 * (2 * E2 - NA));
            M(2 * E1, 2 * E2);
            if (GA & 4) after(any(a2, 4 * (E2 - E1)));
            c2_more<DOFF + 128 * E1>(o, a2, d1, meta);
          }
          if (TP) {
            T(4 * (NY - TP));
            M(2 * E2, N8 - TP - 1);
            if (__builtin_expect(zr != 0, 0)) {
              __nanosleep(zr);
#pragma unroll
              for (int i = 0; i < 16; i++) sts32(zr + i, we[i]);
#pragma unroll
              for (int i = 2 * E2; i < N8 - TP - 1; i++) { sts32(zr + i, a3[2 * i - 4 * E2]); asm volatile("mov.b32 %0, %1;" : "=r"(a3[2 * i - 4 * E2 + 1]) : "r"(ln)); }
#pragma unroll
              for (int i = 4 * (NY - TP - 1); i < 4 * (NY - TP); i++) sts32(zr + i, __float_as_uint(y[i]));
#pragma unroll
              for (int i = 4 * (NY - TP); i < 4 * NY; i++) asm volatile("mov.b32 %0, %1;" : "=f"(y[i]) : "r"(ln));
            }
            T(4 * NY);
            M(N8 - TP - 1, 2 * KT);
          } else {
          T(4 * NY);
          M(2 * E2, 2 * KT);
          }
          c2_more<DOFF + 128 * E2>(o, a3, d1, meta);
          if (!(SPLIT && BQE)) {
          mma_wait<2 + (E1 > E0) + (E2 > E1)>(bz);
          make_bq(bz);
          }
          raw = lds32(sa + S_HDR);
          if (LC) raw = (raw >> 31) == phase ? 0 : raw;
          if (EA) full = mbar_test(sa + S_FULL, phase);
          mma_wait<0>(o);
#pragma unroll
          for (int j = 0; j < 4; j++)
            sts128(cur + S_OUT + j * 512 + ost,
                   make_uint4(__float_as_uint(o[4 * j]), __float_as_uint(o[4 * j + 1]), __float_as_uint(o[4 * j + 2]), __float_as_uint(o[4 * j + 3])));
          if (LC) {
            __syncwarp();
            asm volatile("{\n.reg .pred p;\nsetp.eq.u32 p, %1, 0;\n@p mbarrier.arrive.shared::cta.b64 _, [%0];\n}\n"
                         :: "r"(cur + S_EMPTY), "r"(ln | (hdr & H_SELF)) : "memory");
          }
        };
        if (hdr & 0x2000) { chunk(Int<13>()); if (hdr & H_FINAL) break; }
        else if (hdr & 0x1fff) { chunk(Int<12>()); if (hdr & H_FINAL) break; }
        else if (hdr & 0x4000) { chunk(Int<14>()); if (hdr & H_FINAL) break; }
        else if (hdr) { chunk(Int<16>()); if (hdr & H_FINAL) break; }
        else {
          uint32_t spins = 0;
          do {
            if (++spins > 0x1000000) __trap();
            __nanosleep(32);
            raw = lds32(sa + S_HDR);
          } while ((raw >> 31) == phase);
        }
        continue;
        LOGT(1);
        if (hdr & H_FINAL) break;
        __syncwarp();
        if (ln == 0) mbar_arrive(cur + S_EMPTY);
        for (uint32_t spins = 0; (raw >> 31) == phase; spins++) {
          if (spins > 0x1000000) __trap();
          __nanosleep(32);
          raw = lds32(sa + S_HDR);
        }
      }
      asm volatile("bar.sync %0, 128;" :: "r"(2 + wg) : "memory");
      const uint32_t ra = cur + S_OUT + w * 512 + ln * 4;
      float v[16];
#pragma unroll
      for (int i = 0; i < 16; i++) v[i] = __uint_as_float(lds32(ra + (i >> 2) * 2048 + (i & 3) * 128));
      __nv_bfloat16* dst = out + (lds32(cur + S_ROW + (hdr >> 31) * 4) * kD + 8 * w + ((ln >> 1) & 6) + (ln & 1) + (ln & 2) * 16);
#pragma unroll
      for (int k = 1; k < 16; k *= 2)
#pragma unroll
        for (int i = 0; i < 16; i += 2 * k) v[i] += v[i + k];
      v[0] += __shfl_xor_sync(0xffffffffu, v[0], 16);
      asm volatile("{\n.reg .pred p;\nsetp.lt.u32 p, %2, %3;\n@p st.global.u16 [%0], %1;\n}\n"
                   :: "l"(dst), "h"(__bfloat16_as_ushort(__float2bfloat16(v[0]))), "r"(ln), "r"(hdr & H_SELF ? 16 : 0) : "memory");
      if (!LC && !(hdr & H_SELF) && ln == 0) mbar_arrive(cur + S_EMPTY);
    }
    STAMP(4);
  } else {
    const int pw = warp - NCW * 4;
    const uint32_t ring = sb + pw * RING_BYTES;
    asm volatile("setmaxnreg.dec.sync.aligned.u32 %0;" :: "n"(PROD_REGS));
    if (pw < NCW) {
      int b = pw * grid + blockIdx.x, bn = b + bstep;
      uint4 mw = load_mask(mask, min(b, B - 1), min(lane, 24));
      if (lane == 0) {
#pragma unroll
        for (int i = 0; i < NSLOT; i++) {
          mbar_init(ring + i * SLOT_BYTES + S_FULL, 34);
          mbar_init(ring + i * SLOT_BYTES + S_REST, 32);
          mbar_init(ring + i * SLOT_BYTES + S_EMPTY, 4);
          mbar_arrive(ring + i * SLOT_BYTES + S_FULL);
          sts32(ring + i * SLOT_BYTES + S_HDR, 0);
        }
        sts32(ring + R_STOP, b < B && pw < ACT ? 0 : ring);
      }
      sts32(sb + R_PACE + lane * 4, 0);
      asm volatile("bar.arrive 1, %0;" :: "n"(NCW * 160) : "memory");
      asm volatile("bar.arrive 6, 128;" ::: "memory");
      if (pw >= ACT) return;
      const uint32_t list = ring + R_LIST;
      uint32_t lt;
      asm("mov.u32 %0, %%lanemask_lt;" : "=r"(lt));
      const uint32_t ln = __shfl_sync(0xffffffffu, lane, lane);
      const uint32_t r4 = (ln >> 3) * 4, c16 = (ln & 7) * 16, l25 = min(ln, 24u);
      const uint32_t pick = ln < 25 ? 0xeca8 : 0x9999;
      uint32_t dst[4];
#pragma unroll
      for (int i = 0; i < 4; i++) dst[i] = ring + (r4 + i) * 128 + (c16 ^ (((r4 + i) & 7) << 4));
      uint64_t pol;
      asm("createpolicy.fractional.L2::evict_first.b64 %0, 1.0;" : "=l"(pol));
      uint32_t sa = ring, phase = 1;
      const uint32_t wrap = (uint32_t)(max(B - NSTATIC * bstep, 0) + bstep - 1);
      auto next_slot = [&]() {
        const bool wrapped = sa == ring + (NSLOT - 1) * SLOT_BYTES;
        const int step = wrapped ? -(NSLOT - 1) * SLOT_BYTES : SLOT_BYTES;
        sa += step;
        phase ^= wrapped;
#pragma unroll
        for (int i = 0; i < 4; i++) dst[i] += step;
      };
      uint32_t claimer = ln;
      uint32_t drawn, started = 0;
      auto draw = [&]() {
        drawn = B;
        asm volatile("{\n.reg .pred p;\nsetp.eq.u32 p, %3, 0;\n@p atom.global.inc.u32 %0, [%1], %2;\n}\n"
                     : "+r"(drawn) : "l"(counter), "r"(wrap), "r"(claimer) : "memory");
      };
      if (b >= B) draw();
      while (b < B) {
        const uint32_t e0 = nonzero_as_one(mw.x), e1 = nonzero_as_one(mw.y);
        const uint32_t e2 = nonzero_as_one(mw.z), e3 = nonzero_as_one(mw.w);
        const uint32_t nonbin = (e0 ^ mw.x) | (e1 ^ mw.y) | (e2 ^ mw.z) | (e3 ^ mw.w);
        const uint32_t sA = prmt(e0, e1, pick), sB = prmt(e2, e3, pick);
        const uint32_t pA = (sA & 0x01010101u) * 0x01010101u;
        const uint32_t pB = ((sB & 0x01010101u) + (pA >> 24)) * 0x01010101u;
        uint32_t pos = 0;
        int n = 0;
#pragma unroll
        for (int k = 0; k < 4; k++) {
          const uint32_t bal = ballot_bit(pB, 0x01000000u << k);
          pos += __popc(bal & lt) << k;
          n += __popc(bal) << k;
        }
        const uint32_t general = __any_sync(0xffffffffu, nonbin != 0);
        const uint32_t aA = (pA + pos * 0x01010101u) | ~sA, aB = (pB + pos * 0x01010101u) | ~sB;
#pragma unroll
        for (int i = 0; i < 8; i++) sts8(list - 1 + prmt(i < 4 ? aA : aB, 0, 0x4440 + (i & 3)), 8 * ln + i);
        __syncwarp();

        const uint64_t src = reinterpret_cast<uint64_t>(hist) + (uint64_t)b * (kL * kD * 2);
        const bool no_carry = (uint32_t)src <= 0xffffffffu - kL * kD * 2;
        auto begin_fill = [&](uint32_t h, uint32_t part, int nc, int bt, auto extra) {
          LOGT(0);
          mbar_wait(sa + S_EMPTY, phase);
          if (bt >= B) {
            h |= H_FINAL;
            if (!part) { h |= H_SELF; sts32(ring + R_STOP, sa + (phase ^ 1)); }
          }
          extra();
          sts32(sa + S_HDR, h | phase << 31);
          sts32(sa + S_ROW + phase * 4, b | part);
          asm volatile("{\n.reg .pred p;\nsetp.eq.u32 p, %1, 0;\n@p mbarrier.arrive.shared::cta.b64 _, [%0];\n}\n"
                       :: "r"(sa + S_FULL), "r"(ln) : "memory");
          asm volatile("{\n.reg .u32 f, c;\n.reg .s32 d;\n.reg .pred p;\n"
                       "mov.u32 c, %%globaltimer_lo;\n"
                       "red.shared.max.u32 [%1], c;\n"
                       "atom.shared.add.u32 f, [%1], %2;\n"
                       "shfl.sync.idx.b32 f, f, 0, 31, 0xffffffff;\n"
                       "mov.u32 %0, f;\n"
                       "SPIN:\n"
                       "mov.u32 c, %%globaltimer_lo;\n"
                       "sub.s32 d, c, f;\n"
                       "setp.gt.u32 p, d, %3;\n"
                       "@p bra.uni SPIN;\n}\n" : "=r"(started) : "r"(sb + R_PACE + ln * 4), "r"(nc * (bn >= slow_from ? pace_slow : pace) >> 4), "r"(~(pace * (CHUNK / 4))) : "memory");
          if (!(part & ROW_REST)) {
            mw = load_mask(mask, min(bn, B - 1), l25);
            draw();
          }
          LOGT(1);
          asm volatile("cp.async.ca.shared.global [%0], [%1], 4;"
                       :: "r"(sa + S_TGT + ln * 4), "l"(reinterpret_cast<const uint32_t*>(target) + ((uint32_t)min(bt, B - 1) * 32u + ln)) : "memory");
        };
        auto end_fill = [&](int nc) {
          cp_async_arrive_noinc(sa + (SPLIT ? S_REST : S_FULL));
          next_slot();
          LOGT(2);
        };
        if (__builtin_expect(no_carry && !general, 1)) {
          int nc = n <= CHUNK ? n : n <= 160 ? 64 : 96;
          uint32_t la = list + r4, part = n <= CHUNK ? 0 : ROW_MORE;
#pragma unroll 1
          while (true) {
            uint32_t idx[7];
#pragma unroll
            for (int t = 0; t < 7; t++) idx[t] = lds32(la + t * 16);
            begin_fill(1u << ((nc + 7) >> 3), part, nc, part == ROW_MORE ? b : bn, [](){});
            const int left = nc - r4;
            const uint32_t base = (uint32_t)src + c16;
            uint64_t a[4];
            a[0] = a[1] = a[2] = a[3] = (uint64_t)((uint32_t)(src >> 32) + (ln >> 5)) << 32;
            if (__builtin_expect(nc >= 64, 1)) {
              cp_group<0>(dst, a, idx[0], base, pol);
              cp_group<1>(dst, a, idx[1], base, pol);
              cp_group<2>(dst, a, idx[2], base, pol);
              if (SPLIT) cp_async_arrive_noinc(sa + S_FULL);
              asm volatile("{\n.reg .u32 c;\n.reg .s32 d;\n.reg .pred p;\n"
                           "SPIN:\n"
                           "mov.u32 c, %%globaltimer_lo;\n"
                           "sub.s32 d, c, %0;\n"
                           "setp.lt.u32 p, d, %1;\n"
                           "@p bra.uni SPIN;\n}\n" :: "r"(started), "r"(min(max(bn - slow_from, 0) * SPREAD_UP >> 10, spread)) : "memory");
              cp_group<3>(dst, a, idx[3], base, pol);
              cp_group_z<4>(dst, a, idx[4], base, left, pol);
              cp_group_z<5>(dst, a, idx[5], base, left, pol);
              if (nc > 96) {
                cp_group_z<6>(dst, a, idx[6], base, left, pol);
                if (nc > 112) cp_group_z<7>(dst, a, lds32(la + 112), base, left, pol);
              }
            } else {
              cp_group_z<0>(dst, a, idx[0], base, left, pol);
              cp_group_z<1>(dst, a, idx[1], base, left, pol);
              cp_group_z<2>(dst, a, idx[2], base, left, pol);
              if (SPLIT) cp_async_arrive_noinc(sa + S_FULL);
              cp_group_z<3>(dst, a, idx[3], base, left, pol);
              cp_group_z<4>(dst, a, 0, base, left, pol);
              cp_group_z<5>(dst, a, 0, base, left, pol);
            }
            end_fill(nc);
            if (part != ROW_MORE) break;
            la += nc;
            nc = n - nc;
            part = ROW_REST;
          }
        } else {
          int r0 = 0;
#pragma unroll 1
          do {
            const int nc = min(n - r0, CHUNK);
            const bool more = r0 + CHUNK < n;
            begin_fill(general ? H_GENERAL : 1u << ((nc + 7) >> 3), (more ? ROW_MORE : 0u) | (r0 ? ROW_REST : 0u), nc, more ? b : bn, [&]() {
#pragma unroll 1
              for (int z = ln; general && z < CHUNK; z += 32) {
                uint32_t v = 0;
                if (z < nc) {
                  uint32_t row;
                  asm volatile("ld.shared.u8 %0, [%1];" : "=r"(row) : "r"(list + r0 + z) : "memory");
                  v = __bfloat16_as_ushort(mask[(size_t)b * kL + row]);
                }
                sts16(sa + S_MASK + z * 2, v);
              }
              __syncwarp();
            });
#pragma unroll 1
            for (int z = r4 >> 2; z < CHUNK; z += 4) {
              uint32_t row;
              asm volatile("ld.shared.u8 %0, [%1];" : "=r"(row) : "r"(list + r0 + z) : "memory");
              asm volatile("cp.async.cg.shared.global [%0], [%1], 16, %2;"
                           :: "r"(sa + z * 128 + (c16 ^ ((z & 7) << 4))), "l"(src + c16 + (z < nc ? row : 0) * 128),
                              "r"(z < nc ? 16 : 0) : "memory");
            }
            if (SPLIT) cp_async_arrive_noinc(sa + S_FULL);
            end_fill(nc);
            r0 += CHUNK;
          } while (r0 < n);
        }
        b = bn;
        bn = __shfl_sync(0xffffffffu, drawn, 0) + NSTATIC * bstep;
        if (bn >= B) claimer = 1;
      }
      STAMP(3);
      if (lds32(ring + R_STOP) == 0) sts32(ring + R_STOP, sa + (phase ^ 1));
      asm volatile("cp.async.wait_all;" ::: "memory");
      STAMP(4);
    } else {
      uint32_t due = clock();
      int s0 = NSTATIC * bstep + (PF_EARLY * grid + blockIdx.x) * PF_ROWS;
      auto prefetch = [&]() {
        const int cnt = min(PF_ROWS, B - s0);
        if (lane == 0) {
          prefetch_l2(mask + (size_t)s0 * kL, cnt * kL * 2);
          prefetch_l2(target + (size_t)s0 * kD, cnt * kD * 2);
        }
        s0 += grid * PF_ROWS;
      };
#pragma unroll 1
      for (int j = PF_EARLY; j < PF_FAST && s0 < B; j++) {
        while ((int)(due - (uint32_t)clock()) > 0) {}
        prefetch();
        due += PF_CYCLES;
      }
      due += (PF_FAST - 1) * PF_SLOW - (PF_FAST - PF_EARLY) * PF_CYCLES + (blockIdx.x & 255) * (PF_SLOW / 256);
      asm volatile("bar.sync 6, 128;" ::: "memory");
      static_assert(NCW == 3 && NSLOT < 4, "");
      uint32_t at = sb, at1 = sb + RING_BYTES, at2 = sb + 2 * RING_BYTES;
      const uint32_t ln = __shfl_sync(0xffffffffu, lane, lane);
      const uint32_t rd = __shfl_sync(0xffffffffu, S_OUT + (lane >> 3) * 512 + (lane & 7) * 16, lane);
      uint32_t* const dst = reinterpret_cast<uint32_t*>(out) + ((lane & 4) * 4 + (lane >> 3) * 4 + (lane & 3));
      uint32_t idle = 0;
#pragma unroll 1
      while (at | at1 | at2) {
        const uint32_t sa = at & ~7u;
        if (at == 0) {
        } else if (__any_sync(0xffffffffu, mbar_test(sa + S_EMPTY, at & 1))) {
          const uint32_t row = lds32(sa + S_ROW + 4 - (at & 1) * 4);
          float v[4];
#pragma unroll
          for (int i = 0; i < 2; i++) {
            uint4 u[8];
#pragma unroll
            for (int k = 0; k < 8; k++) u[k] = lds128(sa + rd + i * 4096 + (k >> 2) * 2048 + (k & 3) * 128);
#define DIN_SUM8(m) (((__uint_as_float(u[0].m) + __uint_as_float(u[1].m)) + (__uint_as_float(u[2].m) + __uint_as_float(u[3].m))) + \
                     ((__uint_as_float(u[4].m) + __uint_as_float(u[5].m)) + (__uint_as_float(u[6].m) + __uint_as_float(u[7].m))))
            v[0] = i ? v[0] + DIN_SUM8(x) : DIN_SUM8(x);
            v[1] = i ? v[1] + DIN_SUM8(y) : DIN_SUM8(y);
            v[2] = i ? v[2] + DIN_SUM8(z) : DIN_SUM8(z);
            v[3] = i ? v[3] + DIN_SUM8(w) : DIN_SUM8(w);
          }
          const bool hi = ln & 4;
          float e0 = (hi ? v[2] : v[0]) + __shfl_xor_sync(0xffffffffu, hi ? v[0] : v[2], 4);
          float e1 = (hi ? v[3] : v[1]) + __shfl_xor_sync(0xffffffffu, hi ? v[1] : v[3], 4);
          __syncwarp();
          if (ln == 0) mbar_arrive(sa + S_FULL);
          at += SLOT_BYTES + 2;
          if ((at & 6) == 2 * NSLOT) at = (at - RING_BYTES - 2 * NSLOT) ^ 1;
          if (__builtin_expect(row >= ROW_REST, 0)) {
            const uint32_t carry = (at & ~7u) - (at & 6) * (SLOT_BYTES / 2) + R_CARRY + ln * 8;
            if (row & ROW_REST) { e0 += __uint_as_float(lds32(carry)); e1 += __uint_as_float(lds32(carry + 4)); }
            sts32(carry, __float_as_uint(e0));
            sts32(carry + 4, __float_as_uint(e1));
          }
          if (row < ROW_MORE) dst[(size_t)(row & (ROW_REST - 1)) * 32] = pack_bf16(e0, e1);
          idle = 0;
        } else {
          if (lds32(sa - (at & 6) * (SLOT_BYTES / 2) + R_STOP) == (at & ~6u)) at = 0;
          if (++idle > 2) {
            if (idle > 0x4000000) __trap();
            if (s0 < B && (int)(due - (uint32_t)clock()) <= 0) { prefetch(); due += PF_SLOW; }
            __nanosleep(RED_SLEEP);
          }
        }
        const uint32_t t = at; at = at1; at1 = at2; at2 = t;
      }
      STAMP(4);
    }
  }
}

}

extern "C" void kernel_launch(void* const* d_in, const int* in_sizes, int n_in, void* d_out, int out_size) {
  const __nv_bfloat16* target = (const __nv_bfloat16*)d_in[0];
  const __nv_bfloat16* hist = (const __nv_bfloat16*)d_in[1];
  const __nv_bfloat16* mask = (const __nv_bfloat16*)d_in[2];
  const __nv_bfloat16* w1 = (const __nv_bfloat16*)d_in[3];
  const __nv_bfloat16* b1 = (const __nv_bfloat16*)d_in[4];
  const __nv_bfloat16* w2 = (const __nv_bfloat16*)d_in[5];
  const __nv_bfloat16* b2 = (const __nv_bfloat16*)d_in[6];
  const int B = in_sizes[0] / din::kD;
  if (B <= 0) return;
  static int sms = 0, pace = 0;
  static unsigned int* counter = nullptr;
  if (sms == 0) {
    int dev = 0, khz = 0, bits = 0;
    cudaGetDevice(&dev);
    cudaDeviceGetAttribute(&sms, cudaDevAttrMultiProcessorCount, dev);
    cudaDeviceGetAttribute(&khz, cudaDevAttrMemoryClockRate, dev);
    cudaDeviceGetAttribute(&bits, cudaDevAttrGlobalMemoryBusWidth, dev);
    if (khz > 0 && bits > 0) pace = (int)(16.0 * 128.0 * sms / (khz * 1e-6 * 2.0 * bits / 8.0));
    if (pace > 256) pace = 0;
    cudaGetSymbolAddress((void**)&counter, din::g_next);
    cudaFuncSetAttribute(din::din_kernel, cudaFuncAttributeMaxDynamicSharedMemorySize, din::SMEM_BYTES);
  }
  const long long early = (long long)(din::NSTATIC * NCW + PF_EARLY * PF_ROWS) * sms, line = 128LL * sms;
  long long pf_mask = (early * din::kL * 2 + line - 1) / line, pf_tgt = early * din::kD * 2 / line;
  if (pf_mask > (long long)B * din::kL * 2 / line) pf_mask = (long long)B * din::kL * 2 / line;
  if (pf_tgt > (long long)B * din::kD * 2 / line) pf_tgt = (long long)B * din::kD * 2 / line;
  din::din_kernel<<<sms, din::NTHREADS, din::SMEM_BYTES>>>(mask, target, B, sms, (uint32_t)pf_mask * 128, (uint32_t)pf_tgt * 128,
                                                          w1, hist, b1, w2, b2, (__nv_bfloat16*)d_out, counter, pace,
                                                          B - SLOW_ROUNDS * NCW * sms / 2, pace + (pace * SLOW_BY + 40) / 80,
                                                          pace * SPREAD / 16);
}
```

```cpp
#include <cuda_runtime.h>
#include <cuda_bf16.h>
#include <stdint.h>

namespace din {

constexpr int kL = 200, kD = 64;
#define NCW 3
#define NSLOT 3
constexpr int CHUNK = 128;
constexpr int NTHREADS = NCW * 128 + 128;
#define PREGS 56
#define CREGS 152
constexpr int PROD_REGS = PREGS, CONS_REGS = CREGS;
#define PF_ROWS 8
#define PF_FAST 10
#define PF_SLOW 2000
#define PF_CYCLES 280
#define RED_SLEEP 40
#define K_SEL 0
#define K_FIRST 0
#define K_LAST 0
#define K_LO 1
#define K_HI1 1
#define K_HI2 1
#define K_ADV 0
#define KL 2
#define KM 0
#define GA 1
#define GW4 1
#define SPLIT 1
#define SA 2
#define SB 1
#define EARLY 4
#define PIN2 1
#define SPREAD 80
#define SPREAD_UP 600
#define DOFF 0
#define BQE 0
#define TP 0
#define LC 1
#define EA 1
#define V11 0
#define V15 1
#define KV 16
#define WARM 0
#define G0 0
#define ME 0
#define K0 3
#define WP 0
#define GATE_HALF "hi, hi"
#define SLOW_ROUNDS 12
#define SLOW_BY 9
#define PF_EARLY 3
constexpr int NSTATIC = 2;
constexpr int S_TGT = CHUNK * 128;
constexpr int S_HDR = S_TGT + 128;
constexpr int S_FULL = S_HDR + 8;
constexpr int S_EMPTY = S_HDR + 16;
constexpr int S_ROW = S_HDR + 24;
constexpr int S_REST = S_HDR + 32;
constexpr int S_MASK = S_TGT + 256;
constexpr int S_OUT = S_TGT + 1024;
constexpr int SLOT_BYTES = S_OUT + 8192;
constexpr int RING_BYTES_ = NSLOT * SLOT_BYTES;
constexpr int R_PACE = 2 * RING_BYTES_ + S_TGT + 768;
constexpr int R_STOP = S_HDR + 44;
constexpr int R_LIST = S_TGT + 512;
constexpr int R_VEC = S_TGT + 768;
constexpr int R_SEL = S_TGT + 896;
constexpr int R_CARRY = SLOT_BYTES + S_TGT + 512;
constexpr int R_TGT0 = (NSLOT - 1) * SLOT_BYTES + S_OUT;
constexpr int RING_BYTES = NSLOT * SLOT_BYTES;
constexpr int SMEM_BYTES = NCW * RING_BYTES + 1024;
__device__ constexpr int w1_at(int i) { return (i >> 1) * RING_BYTES + (i & 1) * SLOT_BYTES + S_OUT; }
#define LOGT(slot)
static_assert(SMEM_BYTES <= 232448, "shared memory");
constexpr uint32_t H_GENERAL = 1u << 17, H_FINAL = 1u << 18, H_SELF = 1u << 19;
constexpr uint32_t ROW_REST = 1u << 30, ROW_MORE = 1u << 31;

__device__ unsigned int g_next;

#define STAMP(k)

#define DURT(sign)
#define STR2(x) #x
#define STR(x) STR2(x)
constexpr int NX = 5;
__device__ __forceinline__ void sel_clr(float (&d)[20], const uint32_t (&a)[4], uint32_t lo, uint32_t hi) {
  asm volatile("{\n.reg .b64 db;\n.reg .b32 lo, hi;\n"
    "mov.b32 hi, %25;\n"
    "add.u32 lo, %24, 0;\nmov.b64 db, {lo, hi};\n"
    "wgmma.mma_async.sync.aligned.m64n40k16.f32.bf16.bf16 {%0, %1, %2, %3, %4, %5, %6, %7, %8, %9, %10, %11, %12, %13, %14, %15, %16, %17, %18, %19}, {%20, %21, %22, %23}, db, 0, 1, 1, 0;\n"
    "}\n"
    : "=f"(d[0]), "=f"(d[1]), "=f"(d[2]), "=f"(d[3]), "=f"(d[4]), "=f"(d[5]), "=f"(d[6]), "=f"(d[7]), "=f"(d[8]), "=f"(d[9]), "=f"(d[10]), "=f"(d[11]), "=f"(d[12]), "=f"(d[13]), "=f"(d[14]), "=f"(d[15]), "=f"(d[16]), "=f"(d[17]), "=f"(d[18]), "=f"(d[19])
    : "r"(a[0]), "r"(a[1]), "r"(a[2]), "r"(a[3]), "r"(lo), "r"(hi)
    : "memory");
}
__device__ __forceinline__ void sel_clr(float (&d)[24], const uint32_t (&a)[4], uint32_t lo, uint32_t hi) {
  asm volatile("{\n.reg .b64 db;\n.reg .b32 lo, hi;\n"
    "mov.b32 hi, %29;\n"
    "add.u32 lo, %28, 0;\nmov.b64 db, {lo, hi};\n"
    "wgmma.mma_async.sync.aligned.m64n48k16.f32.bf16.bf16 {%0, %1, %2, %3, %4, %5, %6, %7, %8, %9, %10, %11, %12, %13, %14, %15, %16, %17, %18, %19, %20, %21, %22, %23}, {%24, %25, %26, %27}, db, 0, 1, 1, 0;\n"
    "}\n"
    : "=f"(d[0]), "=f"(d[1]), "=f"(d[2]), "=f"(d[3]), "=f"(d[4]), "=f"(d[5]), "=f"(d[6]), "=f"(d[7]), "=f"(d[8]), "=f"(d[9]), "=f"(d[10]), "=f"(d[11]), "=f"(d[12]), "=f"(d[13]), "=f"(d[14]), "=f"(d[15]), "=f"(d[16]), "=f"(d[17]), "=f"(d[18]), "=f"(d[19]), "=f"(d[20]), "=f"(d[21]), "=f"(d[22]), "=f"(d[23])
    : "r"(a[0]), "r"(a[1]), "r"(a[2]), "r"(a[3]), "r"(lo), "r"(hi)
    : "memory");
}
__device__ __forceinline__ void sel_clr(float (&d)[28], const uint32_t (&a)[4], uint32_t lo, uint32_t hi) {
  asm volatile("{\n.reg .b64 db;\n.reg .b32 lo, hi;\n"
    "mov.b32 hi, %33;\n"
    "add.u32 lo, %32, 0;\nmov.b64 db, {lo, hi};\n"
    "wgmma.mma_async.sync.aligned.m64n56k16.f32.bf16.bf16 {%0, %1, %2, %3, %4, %5, %6, %7, %8, %9, %10, %11, %12, %13, %14, %15, %16, %17, %18, %19, %20, %21, %22, %23, %24, %25, %26, %27}, {%28, %29, %30, %31}, db, 0, 1, 1, 0;\n"
    "}\n"
    : "=f"(d[0]), "=f"(d[1]), "=f"(d[2]), "=f"(d[3]), "=f"(d[4]), "=f"(d[5]), "=f"(d[6]), "=f"(d[7]), "=f"(d[8]), "=f"(d[9]), "=f"(d[10]), "=f"(d[11]), "=f"(d[12]), "=f"(d[13]), "=f"(d[14]), "=f"(d[15]), "=f"(d[16]), "=f"(d[17]), "=f"(d[18]), "=f"(d[19]), "=f"(d[20]), "=f"(d[21]), "=f"(d[22]), "=f"(d[23]), "=f"(d[24]), "=f"(d[25]), "=f"(d[26]), "=f"(d[27])
    : "r"(a[0]), "r"(a[1]), "r"(a[2]), "r"(a[3]), "r"(lo), "r"(hi)
    : "memory");
}
__device__ __forceinline__ void sel_clr(float (&d)[32], const uint32_t (&a)[4], uint32_t lo, uint32_t hi) {
  asm volatile("{\n.reg .b64 db;\n.reg .b32 lo, hi;\n"
    "mov.b32 hi, %37;\n"
    "add.u32 lo, %36, 0;\nmov.b64 db, {lo, hi};\n"
    "wgmma.mma_async.sync.aligned.m64n64k16.f32.bf16.bf16 {%0, %1, %2, %3, %4, %5, %6, %7, %8, %9, %10, %11, %12, %13, %14, %15, %16, %17, %18, %19, %20, %21, %22, %23, %24, %25, %26, %27, %28, %29, %30, %31}, {%32, %33, %34, %35}, db, 0, 1, 1, 0;\n"
    "}\n"
    : "=f"(d[0]), "=f"(d[1]), "=f"(d[2]), "=f"(d[3]), "=f"(d[4]), "=f"(d[5]), "=f"(d[6]), "=f"(d[7]), "=f"(d[8]), "=f"(d[9]), "=f"(d[10]), "=f"(d[11]), "=f"(d[12]), "=f"(d[13]), "=f"(d[14]), "=f"(d[15]), "=f"(d[16]), "=f"(d[17]), "=f"(d[18]), "=f"(d[19]), "=f"(d[20]), "=f"(d[21]), "=f"(d[22]), "=f"(d[23]), "=f"(d[24]), "=f"(d[25]), "=f"(d[26]), "=f"(d[27]), "=f"(d[28]), "=f"(d[29]), "=f"(d[30]), "=f"(d[31])
    : "r"(a[0]), "r"(a[1]), "r"(a[2]), "r"(a[3]), "r"(lo), "r"(hi)
    : "memory");
}
__device__ __forceinline__ void sel_clr(float (&d)[36], const uint32_t (&a)[4], uint32_t lo, uint32_t hi) {
  asm volatile("{\n.reg .b64 db;\n.reg .b32 lo, hi;\n"
    "mov.b32 hi, %41;\n"
    "add.u32 lo, %40, 0;\nmov.b64 db, {lo, hi};\n"
    "wgmma.mma_async.sync.aligned.m64n72k16.f32.bf16.bf16 {%0, %1, %2, %3, %4, %5, %6, %7, %8, %9, %10, %11, %12, %13, %14, %15, %16, %17, %18, %19, %20, %21, %22, %23, %24, %25, %26, %27, %28, %29, %30, %31, %32, %33, %34, %35}, {%36, %37, %38, %39}, db, 0, 1, 1, 0;\n"
    "}\n"
    : "=f"(d[0]), "=f"(d[1]), "=f"(d[2]), "=f"(d[3]), "=f"(d[4]), "=f"(d[5]), "=f"(d[6]), "=f"(d[7]), "=f"(d[8]), "=f"(d[9]), "=f"(d[10]), "=f"(d[11]), "=f"(d[12]), "=f"(d[13]), "=f"(d[14]), "=f"(d[15]), "=f"(d[16]), "=f"(d[17]), "=f"(d[18]), "=f"(d[19]), "=f"(d[20]), "=f"(d[21]), "=f"(d[22]), "=f"(d[23]), "=f"(d[24]), "=f"(d[25]), "=f"(d[26]), "=f"(d[27]), "=f"(d[28]), "=f"(d[29]), "=f"(d[30]), "=f"(d[31]), "=f"(d[32]), "=f"(d[33]), "=f"(d[34]), "=f"(d[35])
    : "r"(a[0]), "r"(a[1]), "r"(a[2]), "r"(a[3]), "r"(lo), "r"(hi)
    : "memory");
}
__device__ __forceinline__ void sel_clr(float (&d)[40], const uint32_t (&a)[4], uint32_t lo, uint32_t hi) {
  asm volatile("{\n.reg .b64 db;\n.reg .b32 lo, hi;\n"
    "mov.b32 hi, %45;\n"
    "add.u32 lo, %44, 0;\nmov.b64 db, {lo, hi};\n"
    "wgmma.mma_async.sync.aligned.m64n80k16.f32.bf16.bf16 {%0, %1, %2, %3, %4, %5, %6, %7, %8, %9, %10, %11, %12, %13, %14, %15, %16, %17, %18, %19, %20, %21, %22, %23, %24, %25, %26, %27, %28, %29, %30, %31, %32, %33, %34, %35, %36, %37, %38, %39}, {%40, %41, %42, %43}, db, 0, 1, 1, 0;\n"
    "}\n"
    : "=f"(d[0]), "=f"(d[1]), "=f"(d[2]), "=f"(d[3]), "=f"(d[4]), "=f"(d[5]), "=f"(d[6]), "=f"(d[7]), "=f"(d[8]), "=f"(d[9]), "=f"(d[10]), "=f"(d[11]), "=f"(d[12]), "=f"(d[13]), "=f"(d[14]), "=f"(d[15]), "=f"(d[16]), "=f"(d[17]), "=f"(d[18]), "=f"(d[19]), "=f"(d[20]), "=f"(d[21]), "=f"(d[22]), "=f"(d[23]), "=f"(d[24]), "=f"(d[25]), "=f"(d[26]), "=f"(d[27]), "=f"(d[28]), "=f"(d[29]), "=f"(d[30]), "=f"(d[31]), "=f"(d[32]), "=f"(d[33]), "=f"(d[34]), "=f"(d[35]), "=f"(d[36]), "=f"(d[37]), "=f"(d[38]), "=f"(d[39])
    : "r"(a[0]), "r"(a[1]), "r"(a[2]), "r"(a[3]), "r"(lo), "r"(hi)
    : "memory");
}
__device__ __forceinline__ void sel_clr(float (&d)[44], const uint32_t (&a)[4], uint32_t lo, uint32_t hi) {
  asm volatile("{\n.reg .b64 db;\n.reg .b32 lo, hi;\n"
    "mov.b32 hi, %49;\n"
    "add.u32 lo, %48, 0;\nmov.b64 db, {lo, hi};\n"
    "wgmma.mma_async.sync.aligned.m64n88k16.f32.bf16.bf16 {%0, %1, %2, %3, %4, %5, %6, %7, %8, %9, %10, %11, %12, %13, %14, %15, %16, %17, %18, %19, %20, %21, %22, %23, %24, %25, %26, %27, %28, %29, %30, %31, %32, %33, %34, %35, %36, %37, %38, %39, %40, %41, %42, %43}, {%44, %45, %46, %47}, db, 0, 1, 1, 0;\n"
    "}\n"
    : "=f"(d[0]), "=f"(d[1]), "=f"(d[2]), "=f"(d[3]), "=f"(d[4]), "=f"(d[5]), "=f"(d[6]), "=f"(d[7]), "=f"(d[8]), "=f"(d[9]), "=f"(d[10]), "=f"(d[11]), "=f"(d[12]), "=f"(d[13]), "=f"(d[14]), "=f"(d[15]), "=f"(d[16]), "=f"(d[17]), "=f"(d[18]), "=f"(d[19]), "=f"(d[20]), "=f"(d[21]), "=f"(d[22]), "=f"(d[23]), "=f"(d[24]), "=f"(d[25]), "=f"(d[26]), "=f"(d[27]), "=f"(d[28]), "=f"(d[29]), "=f"(d[30]), "=f"(d[31]), "=f"(d[32]), "=f"(d[33]), "=f"(d[34]), "=f"(d[35]), "=f"(d[36]), "=f"(d[37]), "=f"(d[38]), "=f"(d[39]), "=f"(d[40]), "=f"(d[41]), "=f"(d[42]), "=f"(d[43])
    : "r"(a[0]), "r"(a[1]), "r"(a[2]), "r"(a[3]), "r"(lo), "r"(hi)
    : "memory");
}
template<int D> __device__ __forceinline__ void c1_acc(float (&d)[20], const uint32_t (&a)[16], uint64_t db) {
  asm volatile("{\n.reg .b64 db;\n"
    "add.s64 db, %36, %37 + 0;\n"
    "wgmma.mma_async.sync.aligned.m64n40k16.f32.bf16.bf16 {%0, %1, %2, %3, %4, %5, %6, %7, %8, %9, %10, %11, %12, %13, %14, %15, %16, %17, %18, %19}, {%20, %21, %22, %23}, db, 1, 1, 1, 0;\n"
    "add.s64 db, %36, %37 + 2;\n"
    "wgmma.mma_async.sync.aligned.m64n40k16.f32.bf16.bf16 {%0, %1, %2, %3, %4, %5, %6, %7, %8, %9, %10, %11, %12, %13, %14, %15, %16, %17, %18, %19}, {%24, %25, %26, %27}, db, 1, 1, 1, 0;\n"
    "add.s64 db, %36, %37 + 4;\n"
    "wgmma.mma_async.sync.aligned.m64n40k16.f32.bf16.bf16 {%0, %1, %2, %3, %4, %5, %6, %7, %8, %9, %10, %11, %12, %13, %14, %15, %16, %17, %18, %19}, {%28, %29, %30, %31}, db, 1, 1, 1, 0;\n"
    "add.s64 db, %36, %37 + 6;\n"
    "wgmma.mma_async.sync.aligned.m64n40k16.f32.bf16.bf16 {%0, %1, %2, %3, %4, %5, %6, %7, %8, %9, %10, %11, %12, %13, %14, %15, %16, %17, %18, %19}, {%32, %33, %34, %35}, db, 1, 1, 1, 0;\n"
    "wgmma.commit_group.sync.aligned;\n}\n"
    : "+f"(d[0]), "+f"(d[1]), "+f"(d[2]), "+f"(d[3]), "+f"(d[4]), "+f"(d[5]), "+f"(d[6]), "+f"(d[7]), "+f"(d[8]), "+f"(d[9]), "+f"(d[10]), "+f"(d[11]), "+f"(d[12]), "+f"(d[13]), "+f"(d[14]), "+f"(d[15]), "+f"(d[16]), "+f"(d[17]), "+f"(d[18]), "+f"(d[19])
    : "r"(a[0]), "r"(a[1]), "r"(a[2]), "r"(a[3]), "r"(a[4]), "r"(a[5]), "r"(a[6]), "r"(a[7]), "r"(a[8]), "r"(a[9]), "r"(a[10]), "r"(a[11]), "r"(a[12]), "r"(a[13]), "r"(a[14]), "r"(a[15]), "l"(db), "n"(D)
    : "memory");
}
template<int D> __device__ __forceinline__ void c1_acc(float (&d)[24], const uint32_t (&a)[16], uint64_t db) {
  asm volatile("{\n.reg .b64 db;\n"
    "add.s64 db, %40, %41 + 0;\n"
    "wgmma.mma_async.sync.aligned.m64n48k16.f32.bf16.bf16 {%0, %1, %2, %3, %4, %5, %6, %7, %8, %9, %10, %11, %12, %13, %14, %15, %16, %17, %18, %19, %20, %21, %22, %23}, {%24, %25, %26, %27}, db, 1, 1, 1, 0;\n"
    "add.s64 db, %40, %41 + 2;\n"
    "wgmma.mma_async.sync.aligned.m64n48k16.f32.bf16.bf16 {%0, %1, %2, %3, %4, %5, %6, %7, %8, %9, %10, %11, %12, %13, %14, %15, %16, %17, %18, %19, %20, %21, %22, %23}, {%28, %29, %30, %31}, db, 1, 1, 1, 0;\n"
    "add.s64 db, %40, %41 + 4;\n"
    "wgmma.mma_async.sync.aligned.m64n48k16.f32.bf16.bf16 {%0, %1, %2, %3, %4, %5, %6, %7, %8, %9, %10, %11, %12, %13, %14, %15, %16, %17, %18, %19, %20, %21, %22, %23}, {%32, %33, %34, %35}, db, 1, 1, 1, 0;\n"
    "add.s64 db, %40, %41 + 6;\n"
    "wgmma.mma_async.sync.aligned.m64n48k16.f32.bf16.bf16 {%0, %1, %2, %3, %4, %5, %6, %7, %8, %9, %10, %11, %12, %13, %14, %15, %16, %17, %18, %19, %20, %21, %22, %23}, {%36, %37, %38, %39}, db, 1, 1, 1, 0;\n"
    "wgmma.commit_group.sync.aligned;\n}\n"
    : "+f"(d[0]), "+f"(d[1]), "+f"(d[2]), "+f"(d[3]), "+f"(d[4]), "+f"(d[5]), "+f"(d[6]), "+f"(d[7]), "+f"(d[8]), "+f"(d[9]), "+f"(d[10]), "+f"(d[11]), "+f"(d[12]), "+f"(d[13]), "+f"(d[14]), "+f"(d[15]), "+f"(d[16]), "+f"(d[17]), "+f"(d[18]), "+f"(d[19]), "+f"(d[20]), "+f"(d[21]), "+f"(d[22]), "+f"(d[23])
    : "r"(a[0]), "r"(a[1]), "r"(a[2]), "r"(a[3]), "r"(a[4]), "r"(a[5]), "r"(a[6]), "r"(a[7]), "r"(a[8]), "r"(a[9]), "r"(a[10]), "r"(a[11]), "r"(a[12]), "r"(a[13]), "r"(a[14]), "r"(a[15]), "l"(db), "n"(D)
    : "memory");
}
template<int D> __device__ __forceinline__ void c1_acc(float (&d)[28], const uint32_t (&a)[16], uint64_t db) {
  asm volatile("{\n.reg .b64 db;\n"
    "add.s64 db, %44, %45 + 0;\n"
    "wgmma.mma_async.sync.aligned.m64n56k16.f32.bf16.bf16 {%0, %1, %2, %3, %4, %5, %6, %7, %8, %9, %10, %11, %12, %13, %14, %15, %16, %17, %18, %19, %20, %21, %22, %23, %24, %25, %26, %27}, {%28, %29, %30, %31}, db, 1, 1, 1, 0;\n"
    "add.s64 db, %44, %45 + 2;\n"
    "wgmma.mma_async.sync.aligned.m64n56k16.f32.bf16.bf16 {%0, %1, %2, %3, %4, %5, %6, %7, %8, %9, %10, %11, %12, %13, %14, %15, %16, %17, %18, %19, %20, %21, %22, %23, %24, %25, %26, %27}, {%32, %33, %34, %35}, db, 1, 1, 1, 0;\n"
    "add.s64 db, %44, %45 + 4;\n"
    "wgmma.mma_async.sync.aligned.m64n56k16.f32.bf16.bf16 {%0, %1, %2, %3, %4, %5, %6, %7, %8, %9, %10, %11, %12, %13, %14, %15, %16, %17, %18, %19, %20, %21, %22, %23, %24, %25, %26, %27}, {%36, %37, %38, %39}, db, 1, 1, 1, 0;\n"
    "add.s64 db, %44, %45 + 6;\n"
    "wgmma.mma_async.sync.aligned.m64n56k16.f32.bf16.bf16 {%0, %1, %2, %3, %4, %5, %6, %7, %8, %9, %10, %11, %12, %13, %14, %15, %16, %17, %18, %19, %20, %21, %22, %23, %24, %25, %26, %27}, {%40, %41, %42, %43}, db, 1, 1, 1, 0;\n"
    "wgmma.commit_group.sync.aligned;\n}\n"
    : "+f"(d[0]), "+f"(d[1]), "+f"(d[2]), "+f"(d[3]), "+f"(d[4]), "+f"(d[5]), "+f"(d[6]), "+f"(d[7]), "+f"(d[8]), "+f"(d[9]), "+f"(d[10]), "+f"(d[11]), "+f"(d[12]), "+f"(d[13]), "+f"(d[14]), "+f"(d[15]), "+f"(d[16]), "+f"(d[17]), "+f"(d[18]), "+f"(d[19]), "+f"(d[20]), "+f"(d[21]), "+f"(d[22]), "+f"(d[23]), "+f"(d[24]), "+f"(d[25]), "+f"(d[26]), "+f"(d[27])
    : "r"(a[0]), "r"(a[1]), "r"(a[2]), "r"(a[3]), "r"(a[4]), "r"(a[5]), "r"(a[6]), "r"(a[7]), "r"(a[8]), "r"(a[9]), "r"(a[10]), "r"(a[11]), "r"(a[12]), "r"(a[13]), "r"(a[14]), "r"(a[15]), "l"(db), "n"(D)
    : "memory");
}
template<int D> __device__ __forceinline__ void c1_acc(float (&d)[32], const uint32_t (&a)[16], uint64_t db) {
  asm volatile("{\n.reg .b64 db;\n"
    "add.s64 db, %48, %49 + 0;\n"
    "wgmma.mma_async.sync.aligned.m64n64k16.f32.bf16.bf16 {%0, %1, %2, %3, %4, %5, %6, %7, %8, %9, %10, %11, %12, %13, %14, %15, %16, %17, %18, %19, %20, %21, %22, %23, %24, %25, %26, %27, %28, %29, %30, %31}, {%32, %33, %34, %35}, db, 1, 1, 1, 0;\n"
    "add.s64 db, %48, %49 + 2;\n"
    "wgmma.mma_async.sync.aligned.m64n64k16.f32.bf16.bf16 {%0, %1, %2, %3, %4, %5, %6, %7, %8, %9, %10, %11, %12, %13, %14, %15, %16, %17, %18, %19, %20, %21, %22, %23, %24, %25, %26, %27, %28, %29, %30, %31}, {%36, %37, %38, %39}, db, 1, 1, 1, 0;\n"
    "add.s64 db, %48, %49 + 4;\n"
    "wgmma.mma_async.sync.aligned.m64n64k16.f32.bf16.bf16 {%0, %1, %2, %3, %4, %5, %6, %7, %8, %9, %10, %11, %12, %13, %14, %15, %16, %17, %18, %19, %20, %21, %22, %23, %24, %25, %26, %27, %28, %29, %30, %31}, {%40, %41, %42, %43}, db, 1, 1, 1, 0;\n"
    "add.s64 db, %48, %49 + 6;\n"
    "wgmma.mma_async.sync.aligned.m64n64k16.f32.bf16.bf16 {%0, %1, %2, %3, %4, %5, %6, %7, %8, %9, %10, %11, %12, %13, %14, %15, %16, %17, %18, %19, %20, %21, %22, %23, %24, %25, %26, %27, %28, %29, %30, %31}, {%44, %45, %46, %47}, db, 1, 1, 1, 0;\n"
    "wgmma.commit_group.sync.aligned;\n}\n"
    : "+f"(d[0]), "+f"(d[1]), "+f"(d[2]), "+f"(d[3]), "+f"(d[4]), "+f"(d[5]), "+f"(d[6]), "+f"(d[7]), "+f"(d[8]), "+f"(d[9]), "+f"(d[10]), "+f"(d[11]), "+f"(d[12]), "+f"(d[13]), "+f"(d[14]), "+f"(d[15]), "+f"(d[16]), "+f"(d[17]), "+f"(d[18]), "+f"(d[19]), "+f"(d[20]), "+f"(d[21]), "+f"(d[22]), "+f"(d[23]), "+f"(d[24]), "+f"(d[25]), "+f"(d[26]), "+f"(d[27]), "+f"(d[28]), "+f"(d[29]), "+f"(d[30]), "+f"(d[31])
    : "r"(a[0]), "r"(a[1]), "r"(a[2]), "r"(a[3]), "r"(a[4]), "r"(a[5]), "r"(a[6]), "r"(a[7]), "r"(a[8]), "r"(a[9]), "r"(a[10]), "r"(a[11]), "r"(a[12]), "r"(a[13]), "r"(a[14]), "r"(a[15]), "l"(db), "n"(D)
    : "memory");
}
template<int D> __device__ __forceinline__ void c1_acc(float (&d)[36], const uint32_t (&a)[16], uint64_t db) {
  asm volatile("{\n.reg .b64 db;\n"
    "add.s64 db, %52, %53 + 0;\n"
    "wgmma.mma_async.sync.aligned.m64n72k16.f32.bf16.bf16 {%0, %1, %2, %3, %4, %5, %6, %7, %8, %9, %10, %11, %12, %13, %14, %15, %16, %17, %18, %19, %20, %21, %22, %23, %24, %25, %26, %27, %28, %29, %30, %31, %32, %33, %34, %35}, {%36, %37, %38, %39}, db, 1, 1, 1, 0;\n"
    "add.s64 db, %52, %53 + 2;\n"
    "wgmma.mma_async.sync.aligned.m64n72k16.f32.bf16.bf16 {%0, %1, %2, %3, %4, %5, %6, %7, %8, %9, %10, %11, %12, %13, %14, %15, %16, %17, %18, %19, %20, %21, %22, %23, %24, %25, %26, %27, %28, %29, %30, %31, %32, %33, %34, %35}, {%40, %41, %42, %43}, db, 1, 1, 1, 0;\n"
    "add.s64 db, %52, %53 + 4;\n"
    "wgmma.mma_async.sync.aligned.m64n72k16.f32.bf16.bf16 {%0, %1, %2, %3, %4, %5, %6, %7, %8, %9, %10, %11, %12, %13, %14, %15, %16, %17, %18, %19, %20, %21, %22, %23, %24, %25, %26, %27, %28, %29, %30, %31, %32, %33, %34, %35}, {%44, %45, %46, %47}, db, 1, 1, 1, 0;\n"
    "add.s64 db, %52, %53 + 6;\n"
    "wgmma.mma_async.sync.aligned.m64n72k16.f32.bf16.bf16 {%0, %1, %2, %3, %4, %5, %6, %7, %8, %9, %10, %11, %12, %13, %14, %15, %16, %17, %18, %19, %20, %21, %22, %23, %24, %25, %26, %27, %28, %29, %30, %31, %32, %33, %34, %35}, {%48, %49, %50, %51}, db, 1, 1, 1, 0;\n"
    "wgmma.commit_group.sync.aligned;\n}\n"
    : "+f"(d[0]), "+f"(d[1]), "+f"(d[2]), "+f"(d[3]), "+f"(d[4]), "+f"(d[5]), "+f"(d[6]), "+f"(d[7]), "+f"(d[8]), "+f"(d[9]), "+f"(d[10]), "+f"(d[11]), "+f"(d[12]), "+f"(d[13]), "+f"(d[14]), "+f"(d[15]), "+f"(d[16]), "+f"(d[17]), "+f"(d[18]), "+f"(d[19]), "+f"(d[20]), "+f"(d[21]), "+f"(d[22]), "+f"(d[23]), "+f"(d[24]), "+f"(d[25]), "+f"(d[26]), "+f"(d[27]), "+f"(d[28]), "+f"(d[29]), "+f"(d[30]), "+f"(d[31]), "+f"(d[32]), "+f"(d[33]), "+f"(d[34]), "+f"(d[35])
    : "r"(a[0]), "r"(a[1]), "r"(a[2]), "r"(a[3]), "r"(a[4]), "r"(a[5]), "r"(a[6]), "r"(a[7]), "r"(a[8]), "r"(a[9]), "r"(a[10]), "r"(a[11]), "r"(a[12]), "r"(a[13]), "r"(a[14]), "r"(a[15]), "l"(db), "n"(D)
    : "memory");
}
template<int D> __device__ __forceinline__ void c1_acc(float (&d)[40], const uint32_t (&a)[16], uint64_t db) {
  asm volatile("{\n.reg .b64 db;\n"
    "add.s64 db, %56, %57 + 0;\n"
    "wgmma.mma_async.sync.aligned.m64n80k16.f32.bf16.bf16 {%0, %1, %2, %3, %4, %5, %6, %7, %8, %9, %10, %11, %12, %13, %14, %15, %16, %17, %18, %19, %20, %21, %22, %23, %24, %25, %26, %27, %28, %29, %30, %31, %32, %33, %34, %35, %36, %37, %38, %39}, {%40, %41, %42, %43}, db, 1, 1, 1, 0;\n"
    "add.s64 db, %56, %57 + 2;\n"
    "wgmma.mma_async.sync.aligned.m64n80k16.f32.bf16.bf16 {%0, %1, %2, %3, %4, %5, %6, %7, %8, %9, %10, %11, %12, %13, %14, %15, %16, %17, %18, %19, %20, %21, %22, %23, %24, %25, %26, %27, %28, %29, %30, %31, %32, %33, %34, %35, %36, %37, %38, %39}, {%44, %45, %46, %47}, db, 1, 1, 1, 0;\n"
    "add.s64 db, %56, %57 + 4;\n"
    "wgmma.mma_async.sync.aligned.m64n80k16.f32.bf16.bf16 {%0, %1, %2, %3, %4, %5, %6, %7, %8, %9, %10, %11, %12, %13, %14, %15, %16, %17, %18, %19, %20, %21, %22, %23, %24, %25, %26, %27, %28, %29, %30, %31, %32, %33, %34, %35, %36, %37, %38, %39}, {%48, %49, %50, %51}, db, 1, 1, 1, 0;\n"
    "add.s64 db, %56, %57 + 6;\n"
    "wgmma.mma_async.sync.aligned.m64n80k16.f32.bf16.bf16 {%0, %1, %2, %3, %4, %5, %6, %7, %8, %9, %10, %11, %12, %13, %14, %15, %16, %17, %18, %19, %20, %21, %22, %23, %24, %25, %26, %27, %28, %29, %30, %31, %32, %33, %34, %35, %36, %37, %38, %39}, {%52, %53, %54, %55}, db, 1, 1, 1, 0;\n"
    "wgmma.commit_group.sync.aligned;\n}\n"
    : "+f"(d[0]), "+f"(d[1]), "+f"(d[2]), "+f"(d[3]), "+f"(d[4]), "+f"(d[5]), "+f"(d[6]), "+f"(d[7]), "+f"(d[8]), "+f"(d[9]), "+f"(d[10]), "+f"(d[11]), "+f"(d[12]), "+f"(d[13]), "+f"(d[14]), "+f"(d[15]), "+f"(d[16]), "+f"(d[17]), "+f"(d[18]), "+f"(d[19]), "+f"(d[20]), "+f"(d[21]), "+f"(d[22]), "+f"(d[23]), "+f"(d[24]), "+f"(d[25]), "+f"(d[26]), "+f"(d[27]), "+f"(d[28]), "+f"(d[29]), "+f"(d[30]), "+f"(d[31]), "+f"(d[32]), "+f"(d[33]), "+f"(d[34]), "+f"(d[35]), "+f"(d[36]), "+f"(d[37]), "+f"(d[38]), "+f"(d[39])
    : "r"(a[0]), "r"(a[1]), "r"(a[2]), "r"(a[3]), "r"(a[4]), "r"(a[5]), "r"(a[6]), "r"(a[7]), "r"(a[8]), "r"(a[9]), "r"(a[10]), "r"(a[11]), "r"(a[12]), "r"(a[13]), "r"(a[14]), "r"(a[15]), "l"(db), "n"(D)
    : "memory");
}
template<int D> __device__ __forceinline__ void c1_acc(float (&d)[44], const uint32_t (&a)[16], uint64_t db) {
  asm volatile("{\n.reg .b64 db;\n"
    "add.s64 db, %60, %61 + 0;\n"
    "wgmma.mma_async.sync.aligned.m64n88k16.f32.bf16.bf16 {%0, %1, %2, %3, %4, %5, %6, %7, %8, %9, %10, %11, %12, %13, %14, %15, %16, %17, %18, %19, %20, %21, %22, %23, %24, %25, %26, %27, %28, %29, %30, %31, %32, %33, %34, %35, %36, %37, %38, %39, %40, %41, %42, %43}, {%44, %45, %46, %47}, db, 1, 1, 1, 0;\n"
    "add.s64 db, %60, %61 + 2;\n"
    "wgmma.mma_async.sync.aligned.m64n88k16.f32.bf16.bf16 {%0, %1, %2, %3, %4, %5, %6, %7, %8, %9, %10, %11, %12, %13, %14, %15, %16, %17, %18, %19, %20, %21, %22, %23, %24, %25, %26, %27, %28, %29, %30, %31, %32, %33, %34, %35, %36, %37, %38, %39, %40, %41, %42, %43}, {%48, %49, %50, %51}, db, 1, 1, 1, 0;\n"
    "add.s64 db, %60, %61 + 4;\n"
    "wgmma.mma_async.sync.aligned.m64n88k16.f32.bf16.bf16 {%0, %1, %2, %3, %4, %5, %6, %7, %8, %9, %10, %11, %12, %13, %14, %15, %16, %17, %18, %19, %20, %21, %22, %23, %24, %25, %26, %27, %28, %29, %30, %31, %32, %33, %34, %35, %36, %37, %38, %39, %40, %41, %42, %43}, {%52, %53, %54, %55}, db, 1, 1, 1, 0;\n"
    "add.s64 db, %60, %61 + 6;\n"
    "wgmma.mma_async.sync.aligned.m64n88k16.f32.bf16.bf16 {%0, %1, %2, %3, %4, %5, %6, %7, %8, %9, %10, %11, %12, %13, %14, %15, %16, %17, %18, %19, %20, %21, %22, %23, %24, %25, %26, %27, %28, %29, %30, %31, %32, %33, %34, %35, %36, %37, %38, %39, %40, %41, %42, %43}, {%56, %57, %58, %59}, db, 1, 1, 1, 0;\n"
    "wgmma.commit_group.sync.aligned;\n}\n"
    : "+f"(d[0]), "+f"(d[1]), "+f"(d[2]), "+f"(d[3]), "+f"(d[4]), "+f"(d[5]), "+f"(d[6]), "+f"(d[7]), "+f"(d[8]), "+f"(d[9]), "+f"(d[10]), "+f"(d[11]), "+f"(d[12]), "+f"(d[13]), "+f"(d[14]), "+f"(d[15]), "+f"(d[16]), "+f"(d[17]), "+f"(d[18]), "+f"(d[19]), "+f"(d[20]), "+f"(d[21]), "+f"(d[22]), "+f"(d[23]), "+f"(d[24]), "+f"(d[25]), "+f"(d[26]), "+f"(d[27]), "+f"(d[28]), "+f"(d[29]), "+f"(d[30]), "+f"(d[31]), "+f"(d[32]), "+f"(d[33]), "+f"(d[34]), "+f"(d[35]), "+f"(d[36]), "+f"(d[37]), "+f"(d[38]), "+f"(d[39]), "+f"(d[40]), "+f"(d[41]), "+f"(d[42]), "+f"(d[43])
    : "r"(a[0]), "r"(a[1]), "r"(a[2]), "r"(a[3]), "r"(a[4]), "r"(a[5]), "r"(a[6]), "r"(a[7]), "r"(a[8]), "r"(a[9]), "r"(a[10]), "r"(a[11]), "r"(a[12]), "r"(a[13]), "r"(a[14]), "r"(a[15]), "l"(db), "n"(D)
    : "memory");
}
template<int D> __device__ __forceinline__ void cbias(float (&d)[4], const uint32_t (&a)[16], uint64_t db) {
  asm volatile("{\n.reg .b64 db;\n"
    "add.s64 db, %20, %21 + 0;\n"
    "wgmma.mma_async.sync.aligned.m64n8k16.f32.bf16.bf16 {%0, %1, %2, %3}, {%4, %5, %6, %7}, db, 0, 1, 1, 0;\n"
    "add.s64 db, %20, %21 + 2;\n"
    "wgmma.mma_async.sync.aligned.m64n8k16.f32.bf16.bf16 {%0, %1, %2, %3}, {%8, %9, %10, %11}, db, 1, 1, 1, 0;\n"
    "add.s64 db, %20, %21 + 4;\n"
    "wgmma.mma_async.sync.aligned.m64n8k16.f32.bf16.bf16 {%0, %1, %2, %3}, {%12, %13, %14, %15}, db, 1, 1, 1, 0;\n"
    "add.s64 db, %20, %21 + 6;\n"
    "wgmma.mma_async.sync.aligned.m64n8k16.f32.bf16.bf16 {%0, %1, %2, %3}, {%16, %17, %18, %19}, db, 1, 1, 1, 0;\n"
    "wgmma.commit_group.sync.aligned;\n}\n"
    : "=f"(d[0]), "=f"(d[1]), "=f"(d[2]), "=f"(d[3])
    : "r"(a[0]), "r"(a[1]), "r"(a[2]), "r"(a[3]), "r"(a[4]), "r"(a[5]), "r"(a[6]), "r"(a[7]), "r"(a[8]), "r"(a[9]), "r"(a[10]), "r"(a[11]), "r"(a[12]), "r"(a[13]), "r"(a[14]), "r"(a[15]), "l"(db), "n"(D)
    : "memory");
}
template<int D> __device__ __forceinline__ void c2_first(float (&d)[16], const uint32_t (&a)[4], uint64_t db, uint32_t meta) {
  asm volatile("{\n.reg .b64 db;\n"
    "wgmma.fence.sync.aligned;\n"
    "add.s64 db, %20, %21 + 0;\n"
    "wgmma.mma_async.sp.sync.aligned.m64n32k32.f32.bf16.bf16 {%0, %1, %2, %3, %4, %5, %6, %7, %8, %9, %10, %11, %12, %13, %14, %15}, {%16, %17, %18, %19}, db, %22, 0, 0, 1, 1, 1;\n"
    "wgmma.commit_group.sync.aligned;\n}\n"
    : "=f"(d[0]), "=f"(d[1]), "=f"(d[2]), "=f"(d[3]), "=f"(d[4]), "=f"(d[5]), "=f"(d[6]), "=f"(d[7]), "=f"(d[8]), "=f"(d[9]), "=f"(d[10]), "=f"(d[11]), "=f"(d[12]), "=f"(d[13]), "=f"(d[14]), "=f"(d[15])
    : "r"(a[0]), "r"(a[1]), "r"(a[2]), "r"(a[3]), "l"(db), "n"(D), "r"(meta)
    : "memory");
}
template<int D> __device__ __forceinline__ void c2_more(float (&d)[16], const uint32_t (&a)[4], uint64_t db, uint32_t meta) {
  asm volatile("{\n.reg .b64 db;\n"
    "wgmma.fence.sync.aligned;\n"
    "add.s64 db, %20, %21 + 0;\n"
    "wgmma.mma_async.sp.sync.aligned.m64n32k32.f32.bf16.bf16 {%0, %1, %2, %3, %4, %5, %6, %7, %8, %9, %10, %11, %12, %13, %14, %15}, {%16, %17, %18, %19}, db, %22, 0, 1, 1, 1, 1;\n"
    "wgmma.commit_group.sync.aligned;\n}\n"
    : "+f"(d[0]), "+f"(d[1]), "+f"(d[2]), "+f"(d[3]), "+f"(d[4]), "+f"(d[5]), "+f"(d[6]), "+f"(d[7]), "+f"(d[8]), "+f"(d[9]), "+f"(d[10]), "+f"(d[11]), "+f"(d[12]), "+f"(d[13]), "+f"(d[14]), "+f"(d[15])
    : "r"(a[0]), "r"(a[1]), "r"(a[2]), "r"(a[3]), "l"(db), "n"(D), "r"(meta)
    : "memory");
}
template<int D> __device__ __forceinline__ void c2_first(float (&d)[16], const uint32_t (&a)[8], uint64_t db, uint32_t meta) {
  asm volatile("{\n.reg .b64 db;\n"
    "wgmma.fence.sync.aligned;\n"
    "add.s64 db, %24, %25 + 0;\n"
    "wgmma.mma_async.sp.sync.aligned.m64n32k32.f32.bf16.bf16 {%0, %1, %2, %3, %4, %5, %6, %7, %8, %9, %10, %11, %12, %13, %14, %15}, {%16, %17, %18, %19}, db, %26, 0, 0, 1, 1, 1;\n"
    "add.s64 db, %24, %25 + 128;\n"
    "wgmma.mma_async.sp.sync.aligned.m64n32k32.f32.bf16.bf16 {%0, %1, %2, %3, %4, %5, %6, %7, %8, %9, %10, %11, %12, %13, %14, %15}, {%20, %21, %22, %23}, db, %26, 0, 1, 1, 1, 1;\n"
    "wgmma.commit_group.sync.aligned;\n}\n"
    : "=f"(d[0]), "=f"(d[1]), "=f"(d[2]), "=f"(d[3]), "=f"(d[4]), "=f"(d[5]), "=f"(d[6]), "=f"(d[7]), "=f"(d[8]), "=f"(d[9]), "=f"(d[10]), "=f"(d[11]), "=f"(d[12]), "=f"(d[13]), "=f"(d[14]), "=f"(d[15])
    : "r"(a[0]), "r"(a[1]), "r"(a[2]), "r"(a[3]), "r"(a[4]), "r"(a[5]), "r"(a[6]), "r"(a[7]), "l"(db), "n"(D), "r"(meta)
    : "memory");
}
template<int D> __device__ __forceinline__ void c2_more(float (&d)[16], const uint32_t (&a)[8], uint64_t db, uint32_t meta) {
  asm volatile("{\n.reg .b64 db;\n"
    "wgmma.fence.sync.aligned;\n"
    "add.s64 db, %24, %25 + 0;\n"
    "wgmma.mma_async.sp.sync.aligned.m64n32k32.f32.bf16.bf16 {%0, %1, %2, %3, %4, %5, %6, %7, %8, %9, %10, %11, %12, %13, %14, %15}, {%16, %17, %18, %19}, db, %26, 0, 1, 1, 1, 1;\n"
    "add.s64 db, %24, %25 + 128;\n"
    "wgmma.mma_async.sp.sync.aligned.m64n32k32.f32.bf16.bf16 {%0, %1, %2, %3, %4, %5, %6, %7, %8, %9, %10, %11, %12, %13, %14, %15}, {%20, %21, %22, %23}, db, %26, 0, 1, 1, 1, 1;\n"
    "wgmma.commit_group.sync.aligned;\n}\n"
    : "+f"(d[0]), "+f"(d[1]), "+f"(d[2]), "+f"(d[3]), "+f"(d[4]), "+f"(d[5]), "+f"(d[6]), "+f"(d[7]), "+f"(d[8]), "+f"(d[9]), "+f"(d[10]), "+f"(d[11]), "+f"(d[12]), "+f"(d[13]), "+f"(d[14]), "+f"(d[15])
    : "r"(a[0]), "r"(a[1]), "r"(a[2]), "r"(a[3]), "r"(a[4]), "r"(a[5]), "r"(a[6]), "r"(a[7]), "l"(db), "n"(D), "r"(meta)
    : "memory");
}
template<int D> __device__ __forceinline__ void c2_first(float (&d)[16], const uint32_t (&a)[12], uint64_t db, uint32_t meta) {
  asm volatile("{\n.reg .b64 db;\n"
    "wgmma.fence.sync.aligned;\n"
    "add.s64 db, %28, %29 + 0;\n"
    "wgmma.mma_async.sp.sync.aligned.m64n32k32.f32.bf16.bf16 {%0, %1, %2, %3, %4, %5, %6, %7, %8, %9, %10, %11, %12, %13, %14, %15}, {%16, %17, %18, %19}, db, %30, 0, 0, 1, 1, 1;\n"
    "add.s64 db, %28, %29 + 128;\n"
    "wgmma.mma_async.sp.sync.aligned.m64n32k32.f32.bf16.bf16 {%0, %1, %2, %3, %4, %5, %6, %7, %8, %9, %10, %11, %12, %13, %14, %15}, {%20, %21, %22, %23}, db, %30, 0, 1, 1, 1, 1;\n"
    "add.s64 db, %28, %29 + 256;\n"
    "wgmma.mma_async.sp.sync.aligned.m64n32k32.f32.bf16.bf16 {%0, %1, %2, %3, %4, %5, %6, %7, %8, %9, %10, %11, %12, %13, %14, %15}, {%24, %25, %26, %27}, db, %30, 0, 1, 1, 1, 1;\n"
    "wgmma.commit_group.sync.aligned;\n}\n"
    : "=f"(d[0]), "=f"(d[1]), "=f"(d[2]), "=f"(d[3]), "=f"(d[4]), "=f"(d[5]), "=f"(d[6]), "=f"(d[7]), "=f"(d[8]), "=f"(d[9]), "=f"(d[10]), "=f"(d[11]), "=f"(d[12]), "=f"(d[13]), "=f"(d[14]), "=f"(d[15])
    : "r"(a[0]), "r"(a[1]), "r"(a[2]), "r"(a[3]), "r"(a[4]), "r"(a[5]), "r"(a[6]), "r"(a[7]), "r"(a[8]), "r"(a[9]), "r"(a[10]), "r"(a[11]), "l"(db), "n"(D), "r"(meta)
    : "memory");
}
template<int D> __device__ __forceinline__ void c2_more(float (&d)[16], const uint32_t (&a)[12], uint64_t db, uint32_t meta) {
  asm volatile("{\n.reg .b64 db;\n"
    "wgmma.fence.sync.aligned;\n"
    "add.s64 db, %28, %29 + 0;\n"
    "wgmma.mma_async.sp.sync.aligned.m64n32k32.f32.bf16.bf16 {%0, %1, %2, %3, %4, %5, %6, %7, %8, %9, %10, %11, %12, %13, %14, %15}, {%16, %17, %18, %19}, db, %30, 0, 1, 1, 1, 1;\n"
    "add.s64 db, %28, %29 + 128;\n"
    "wgmma.mma_async.sp.sync.aligned.m64n32k32.f32.bf16.bf16 {%0, %1, %2, %3, %4, %5, %6, %7, %8, %9, %10, %11, %12, %13, %14, %15}, {%20, %21, %22, %23}, db, %30, 0, 1, 1, 1, 1;\n"
    "add.s64 db, %28, %29 + 256;\n"
    "wgmma.mma_async.sp.sync.aligned.m64n32k32.f32.bf16.bf16 {%0, %1, %2, %3, %4, %5, %6, %7, %8, %9, %10, %11, %12, %13, %14, %15}, {%24, %25, %26, %27}, db, %30, 0, 1, 1, 1, 1;\n"
    "wgmma.commit_group.sync.aligned;\n}\n"
    : "+f"(d[0]), "+f"(d[1]), "+f"(d[2]), "+f"(d[3]), "+f"(d[4]), "+f"(d[5]), "+f"(d[6]), "+f"(d[7]), "+f"(d[8]), "+f"(d[9]), "+f"(d[10]), "+f"(d[11]), "+f"(d[12]), "+f"(d[13]), "+f"(d[14]), "+f"(d[15])
    : "r"(a[0]), "r"(a[1]), "r"(a[2]), "r"(a[3]), "r"(a[4]), "r"(a[5]), "r"(a[6]), "r"(a[7]), "r"(a[8]), "r"(a[9]), "r"(a[10]), "r"(a[11]), "l"(db), "n"(D), "r"(meta)
    : "memory");
}
template<int D> __device__ __forceinline__ void c2_first(float (&d)[16], const uint32_t (&a)[16], uint64_t db, uint32_t meta) {
  asm volatile("{\n.reg .b64 db;\n"
    "wgmma.fence.sync.aligned;\n"
    "add.s64 db, %32, %33 + 0;\n"
    "wgmma.mma_async.sp.sync.aligned.m64n32k32.f32.bf16.bf16 {%0, %1, %2, %3, %4, %5, %6, %7, %8, %9, %10, %11, %12, %13, %14, %15}, {%16, %17, %18, %19}, db, %34, 0, 0, 1, 1, 1;\n"
    "add.s64 db, %32, %33 + 128;\n"
    "wgmma.mma_async.sp.sync.aligned.m64n32k32.f32.bf16.bf16 {%0, %1, %2, %3, %4, %5, %6, %7, %8, %9, %10, %11, %12, %13, %14, %15}, {%20, %21, %22, %23}, db, %34, 0, 1, 1, 1, 1;\n"
    "add.s64 db, %32, %33 + 256;\n"
    "wgmma.mma_async.sp.sync.aligned.m64n32k32.f32.bf16.bf16 {%0, %1, %2, %3, %4, %5, %6, %7, %8, %9, %10, %11, %12, %13, %14, %15}, {%24, %25, %26, %27}, db, %34, 0, 1, 1, 1, 1;\n"
    "add.s64 db, %32, %33 + 384;\n"
    "wgmma.mma_async.sp.sync.aligned.m64n32k32.f32.bf16.bf16 {%0, %1, %2, %3, %4, %5, %6, %7, %8, %9, %10, %11, %12, %13, %14, %15}, {%28, %29, %30, %31}, db, %34, 0, 1, 1, 1, 1;\n"
    "wgmma.commit_group.sync.aligned;\n}\n"
    : "=f"(d[0]), "=f"(d[1]), "=f"(d[2]), "=f"(d[3]), "=f"(d[4]), "=f"(d[5]), "=f"(d[6]), "=f"(d[7]), "=f"(d[8]), "=f"(d[9]), "=f"(d[10]), "=f"(d[11]), "=f"(d[12]), "=f"(d[13]), "=f"(d[14]), "=f"(d[15])
    : "r"(a[0]), "r"(a[1]), "r"(a[2]), "r"(a[3]), "r"(a[4]), "r"(a[5]), "r"(a[6]), "r"(a[7]), "r"(a[8]), "r"(a[9]), "r"(a[10]), "r"(a[11]), "r"(a[12]), "r"(a[13]), "r"(a[14]), "r"(a[15]), "l"(db), "n"(D), "r"(meta)
    : "memory");
}
template<int D> __device__ __forceinline__ void c2_more(float (&d)[16], const uint32_t (&a)[16], uint64_t db, uint32_t meta) {
  asm volatile("{\n.reg .b64 db;\n"
    "wgmma.fence.sync.aligned;\n"
    "add.s64 db, %32, %33 + 0;\n"
    "wgmma.mma_async.sp.sync.aligned.m64n32k32.f32.bf16.bf16 {%0, %1, %2, %3, %4, %5, %6, %7, %8, %9, %10, %11, %12, %13, %14, %15}, {%16, %17, %18, %19}, db, %34, 0, 1, 1, 1, 1;\n"
    "add.s64 db, %32, %33 + 128;\n"
    "wgmma.mma_async.sp.sync.aligned.m64n32k32.f32.bf16.bf16 {%0, %1, %2, %3, %4, %5, %6, %7, %8, %9, %10, %11, %12, %13, %14, %15}, {%20, %21, %22, %23}, db, %34, 0, 1, 1, 1, 1;\n"
    "add.s64 db, %32, %33 + 256;\n"
    "wgmma.mma_async.sp.sync.aligned.m64n32k32.f32.bf16.bf16 {%0, %1, %2, %3, %4, %5, %6, %7, %8, %9, %10, %11, %12, %13, %14, %15}, {%24, %25, %26, %27}, db, %34, 0, 1, 1, 1, 1;\n"
    "add.s64 db, %32, %33 + 384;\n"
    "wgmma.mma_async.sp.sync.aligned.m64n32k32.f32.bf16.bf16 {%0, %1, %2, %3, %4, %5, %6, %7, %8, %9, %10, %11, %12, %13, %14, %15}, {%28, %29, %30, %31}, db, %34, 0, 1, 1, 1, 1;\n"
    "wgmma.commit_group.sync.aligned;\n}\n"
    : "+f"(d[0]), "+f"(d[1]), "+f"(d[2]), "+f"(d[3]), "+f"(d[4]), "+f"(d[5]), "+f"(d[6]), "+f"(d[7]), "+f"(d[8]), "+f"(d[9]), "+f"(d[10]), "+f"(d[11]), "+f"(d[12]), "+f"(d[13]), "+f"(d[14]), "+f"(d[15])
    : "r"(a[0]), "r"(a[1]), "r"(a[2]), "r"(a[3]), "r"(a[4]), "r"(a[5]), "r"(a[6]), "r"(a[7]), "r"(a[8]), "r"(a[9]), "r"(a[10]), "r"(a[11]), "r"(a[12]), "r"(a[13]), "r"(a[14]), "r"(a[15]), "l"(db), "n"(D), "r"(meta)
    : "memory");
}
template<int D> __device__ __forceinline__ void c2_first(float (&d)[16], const uint32_t (&a)[20], uint64_t db, uint32_t meta) {
  asm volatile("{\n.reg .b64 db;\n"
    "wgmma.fence.sync.aligned;\n"
    "add.s64 db, %36, %37 + 0;\n"
    "wgmma.mma_async.sp.sync.aligned.m64n32k32.f32.bf16.bf16 {%0, %1, %2, %3, %4, %5, %6, %7, %8, %9, %10, %11, %12, %13, %14, %15}, {%16, %17, %18, %19}, db, %38, 0, 0, 1, 1, 1;\n"
    "add.s64 db, %36, %37 + 128;\n"
    "wgmma.mma_async.sp.sync.aligned.m64n32k32.f32.bf16.bf16 {%0, %1, %2, %3, %4, %5, %6, %7, %8, %9, %10, %11, %12, %13, %14, %15}, {%20, %21, %22, %23}, db, %38, 0, 1, 1, 1, 1;\n"
    "add.s64 db, %36, %37 + 256;\n"
    "wgmma.mma_async.sp.sync.aligned.m64n32k32.f32.bf16.bf16 {%0, %1, %2, %3, %4, %5, %6, %7, %8, %9, %10, %11, %12, %13, %14, %15}, {%24, %25, %26, %27}, db, %38, 0, 1, 1, 1, 1;\n"
    "add.s64 db, %36, %37 + 384;\n"
    "wgmma.mma_async.sp.sync.aligned.m64n32k32.f32.bf16.bf16 {%0, %1, %2, %3, %4, %5, %6, %7, %8, %9, %10, %11, %12, %13, %14, %15}, {%28, %29, %30, %31}, db, %38, 0, 1, 1, 1, 1;\n"
    "add.s64 db, %36, %37 + 512;\n"
    "wgmma.mma_async.sp.sync.aligned.m64n32k32.f32.bf16.bf16 {%0, %1, %2, %3, %4, %5, %6, %7, %8, %9, %10, %11, %12, %13, %14, %15}, {%32, %33, %34, %35}, db, %38, 0, 1, 1, 1, 1;\n"
    "wgmma.commit_group.sync.aligned;\n}\n"
    : "=f"(d[0]), "=f"(d[1]), "=f"(d[2]), "=f"(d[3]), "=f"(d[4]), "=f"(d[5]), "=f"(d[6]), "=f"(d[7]), "=f"(d[8]), "=f"(d[9]), "=f"(d[10]), "=f"(d[11]), "=f"(d[12]), "=f"(d[13]), "=f"(d[14]), "=f"(d[15])
    : "r"(a[0]), "r"(a[1]), "r"(a[2]), "r"(a[3]), "r"(a[4]), "r"(a[5]), "r"(a[6]), "r"(a[7]), "r"(a[8]), "r"(a[9]), "r"(a[10]), "r"(a[11]), "r"(a[12]), "r"(a[13]), "r"(a[14]), "r"(a[15]), "r"(a[16]), "r"(a[17]), "r"(a[18]), "r"(a[19]), "l"(db), "n"(D), "r"(meta)
    : "memory");
}
template<int D> __device__ __forceinline__ void c2_more(float (&d)[16], const uint32_t (&a)[20], uint64_t db, uint32_t meta) {
  asm volatile("{\n.reg .b64 db;\n"
    "wgmma.fence.sync.aligned;\n"
    "add.s64 db, %36, %37 + 0;\n"
    "wgmma.mma_async.sp.sync.aligned.m64n32k32.f32.bf16.bf16 {%0, %1, %2, %3, %4, %5, %6, %7, %8, %9, %10, %11, %12, %13, %14, %15}, {%16, %17, %18, %19}, db, %38, 0, 1, 1, 1, 1;\n"
    "add.s64 db, %36, %37 + 128;\n"
    "wgmma.mma_async.sp.sync.aligned.m64n32k32.f32.bf16.bf16 {%0, %1, %2, %3, %4, %5, %6, %7, %8, %9, %10, %11, %12, %13, %14, %15}, {%20, %21, %22, %23}, db, %38, 0, 1, 1, 1, 1;\n"
    "add.s64 db, %36, %37 + 256;\n"
    "wgmma.mma_async.sp.sync.aligned.m64n32k32.f32.bf16.bf16 {%0, %1, %2, %3, %4, %5, %6, %7, %8, %9, %10, %11, %12, %13, %14, %15}, {%24, %25, %26, %27}, db, %38, 0, 1, 1, 1, 1;\n"
    "add.s64 db, %36, %37 + 384;\n"
    "wgmma.mma_async.sp.sync.aligned.m64n32k32.f32.bf16.bf16 {%0, %1, %2, %3, %4, %5, %6, %7, %8, %9, %10, %11, %12, %13, %14, %15}, {%28, %29, %30, %31}, db, %38, 0, 1, 1, 1, 1;\n"
    "add.s64 db, %36, %37 + 512;\n"
    "wgmma.mma_async.sp.sync.aligned.m64n32k32.f32.bf16.bf16 {%0, %1, %2, %3, %4, %5, %6, %7, %8, %9, %10, %11, %12, %13, %14, %15}, {%32, %33, %34, %35}, db, %38, 0, 1, 1, 1, 1;\n"
    "wgmma.commit_group.sync.aligned;\n}\n"
    : "+f"(d[0]), "+f"(d[1]), "+f"(d[2]), "+f"(d[3]), "+f"(d[4]), "+f"(d[5]), "+f"(d[6]), "+f"(d[7]), "+f"(d[8]), "+f"(d[9]), "+f"(d[10]), "+f"(d[11]), "+f"(d[12]), "+f"(d[13]), "+f"(d[14]), "+f"(d[15])
    : "r"(a[0]), "r"(a[1]), "r"(a[2]), "r"(a[3]), "r"(a[4]), "r"(a[5]), "r"(a[6]), "r"(a[7]), "r"(a[8]), "r"(a[9]), "r"(a[10]), "r"(a[11]), "r"(a[12]), "r"(a[13]), "r"(a[14]), "r"(a[15]), "r"(a[16]), "r"(a[17]), "r"(a[18]), "r"(a[19]), "l"(db), "n"(D), "r"(meta)
    : "memory");
}
template<int D> __device__ __forceinline__ void c2_first(float (&d)[16], const uint32_t (&a)[24], uint64_t db, uint32_t meta) {
  asm volatile("{\n.reg .b64 db;\n"
    "wgmma.fence.sync.aligned;\n"
    "add.s64 db, %40, %41 + 0;\n"
    "wgmma.mma_async.sp.sync.aligned.m64n32k32.f32.bf16.bf16 {%0, %1, %2, %3, %4, %5, %6, %7, %8, %9, %10, %11, %12, %13, %14, %15}, {%16, %17, %18, %19}, db, %42, 0, 0, 1, 1, 1;\n"
    "add.s64 db, %40, %41 + 128;\n"
    "wgmma.mma_async.sp.sync.aligned.m64n32k32.f32.bf16.bf16 {%0, %1, %2, %3, %4, %5, %6, %7, %8, %9, %10, %11, %12, %13, %14, %15}, {%20, %21, %22, %23}, db, %42, 0, 1, 1, 1, 1;\n"
    "add.s64 db, %40, %41 + 256;\n"
    "wgmma.mma_async.sp.sync.aligned.m64n32k32.f32.bf16.bf16 {%0, %1, %2, %3, %4, %5, %6, %7, %8, %9, %10, %11, %12, %13, %14, %15}, {%24, %25, %26, %27}, db, %42, 0, 1, 1, 1, 1;\n"
    "add.s64 db, %40, %41 + 384;\n"
    "wgmma.mma_async.sp.sync.aligned.m64n32k32.f32.bf16.bf16 {%0, %1, %2, %3, %4, %5, %6, %7, %8, %9, %10, %11, %12, %13, %14, %15}, {%28, %29, %30, %31}, db, %42, 0, 1, 1, 1, 1;\n"
    "add.s64 db, %40, %41 + 512;\n"
    "wgmma.mma_async.sp.sync.aligned.m64n32k32.f32.bf16.bf16 {%0, %1, %2, %3, %4, %5, %6, %7, %8, %9, %10, %11, %12, %13, %14, %15}, {%32, %33, %34, %35}, db, %42, 0, 1, 1, 1, 1;\n"
    "add.s64 db, %40, %41 + 640;\n"
    "wgmma.mma_async.sp.sync.aligned.m64n32k32.f32.bf16.bf16 {%0, %1, %2, %3, %4, %5, %6, %7, %8, %9, %10, %11, %12, %13, %14, %15}, {%36, %37, %38, %39}, db, %42, 0, 1, 1, 1, 1;\n"
    "wgmma.commit_group.sync.aligned;\n}\n"
    : "=f"(d[0]), "=f"(d[1]), "=f"(d[2]), "=f"(d[3]), "=f"(d[4]), "=f"(d[5]), "=f"(d[6]), "=f"(d[7]), "=f"(d[8]), "=f"(d[9]), "=f"(d[10]), "=f"(d[11]), "=f"(d[12]), "=f"(d[13]), "=f"(d[14]), "=f"(d[15])
    : "r"(a[0]), "r"(a[1]), "r"(a[2]), "r"(a[3]), "r"(a[4]), "r"(a[5]), "r"(a[6]), "r"(a[7]), "r"(a[8]), "r"(a[9]), "r"(a[10]), "r"(a[11]), "r"(a[12]), "r"(a[13]), "r"(a[14]), "r"(a[15]), "r"(a[16]), "r"(a[17]), "r"(a[18]), "r"(a[19]), "r"(a[20]), "r"(a[21]), "r"(a[22]), "r"(a[23]), "l"(db), "n"(D), "r"(meta)
    : "memory");
}
template<int D> __device__ __forceinline__ void c2_more(float (&d)[16], const uint32_t (&a)[24], uint64_t db, uint32_t meta) {
  asm volatile("{\n.reg .b64 db;\n"
    "wgmma.fence.sync.aligned;\n"
    "add.s64 db, %40, %41 + 0;\n"
    "wgmma.mma_async.sp.sync.aligned.m64n32k32.f32.bf16.bf16 {%0, %1, %2, %3, %4, %5, %6, %7, %8, %9, %10, %11, %12, %13, %14, %15}, {%16, %17, %18, %19}, db, %42, 0, 1, 1, 1, 1;\n"
    "add.s64 db, %40, %41 + 128;\n"
    "wgmma.mma_async.sp.sync.aligned.m64n32k32.f32.bf16.bf16 {%0, %1, %2, %3, %4, %5, %6, %7, %8, %9, %10, %11, %12, %13, %14, %15}, {%20, %21, %22, %23}, db, %42, 0, 1, 1, 1, 1;\n"
    "add.s64 db, %40, %41 + 256;\n"
    "wgmma.mma_async.sp.sync.aligned.m64n32k32.f32.bf16.bf16 {%0, %1, %2, %3, %4, %5, %6, %7, %8, %9, %10, %11, %12, %13, %14, %15}, {%24, %25, %26, %27}, db, %42, 0, 1, 1, 1, 1;\n"
    "add.s64 db, %40, %41 + 384;\n"
    "wgmma.mma_async.sp.sync.aligned.m64n32k32.f32.bf16.bf16 {%0, %1, %2, %3, %4, %5, %6, %7, %8, %9, %10, %11, %12, %13, %14, %15}, {%28, %29, %30, %31}, db, %42, 0, 1, 1, 1, 1;\n"
    "add.s64 db, %40, %41 + 512;\n"
    "wgmma.mma_async.sp.sync.aligned.m64n32k32.f32.bf16.bf16 {%0, %1, %2, %3, %4, %5, %6, %7, %8, %9, %10, %11, %12, %13, %14, %15}, {%32, %33, %34, %35}, db, %42, 0, 1, 1, 1, 1;\n"
    "add.s64 db, %40, %41 + 640;\n"
    "wgmma.mma_async.sp.sync.aligned.m64n32k32.f32.bf16.bf16 {%0, %1, %2, %3, %4, %5, %6, %7, %8, %9, %10, %11, %12, %13, %14, %15}, {%36, %37, %38, %39}, db, %42, 0, 1, 1, 1, 1;\n"
    "wgmma.commit_group.sync.aligned;\n}\n"
    : "+f"(d[0]), "+f"(d[1]), "+f"(d[2]), "+f"(d[3]), "+f"(d[4]), "+f"(d[5]), "+f"(d[6]), "+f"(d[7]), "+f"(d[8]), "+f"(d[9]), "+f"(d[10]), "+f"(d[11]), "+f"(d[12]), "+f"(d[13]), "+f"(d[14]), "+f"(d[15])
    : "r"(a[0]), "r"(a[1]), "r"(a[2]), "r"(a[3]), "r"(a[4]), "r"(a[5]), "r"(a[6]), "r"(a[7]), "r"(a[8]), "r"(a[9]), "r"(a[10]), "r"(a[11]), "r"(a[12]), "r"(a[13]), "r"(a[14]), "r"(a[15]), "r"(a[16]), "r"(a[17]), "r"(a[18]), "r"(a[19]), "r"(a[20]), "r"(a[21]), "r"(a[22]), "r"(a[23]), "l"(db), "n"(D), "r"(meta)
    : "memory");
}
template<int D> __device__ __forceinline__ void c2_first(float (&d)[16], const uint32_t (&a)[28], uint64_t db, uint32_t meta) {
  asm volatile("{\n.reg .b64 db;\n"
    "wgmma.fence.sync.aligned;\n"
    "add.s64 db, %44, %45 + 0;\n"
    "wgmma.mma_async.sp.sync.aligned.m64n32k32.f32.bf16.bf16 {%0, %1, %2, %3, %4, %5, %6, %7, %8, %9, %10, %11, %12, %13, %14, %15}, {%16, %17, %18, %19}, db, %46, 0, 0, 1, 1, 1;\n"
    "add.s64 db, %44, %45 + 128;\n"
    "wgmma.mma_async.sp.sync.aligned.m64n32k32.f32.bf16.bf16 {%0, %1, %2, %3, %4, %5, %6, %7, %8, %9, %10, %11, %12, %13, %14, %15}, {%20, %21, %22, %23}, db, %46, 0, 1, 1, 1, 1;\n"
    "add.s64 db, %44, %45 + 256;\n"
    "wgmma.mma_async.sp.sync.aligned.m64n32k32.f32.bf16.bf16 {%0, %1, %2, %3, %4, %5, %6, %7, %8, %9, %10, %11, %12, %13, %14, %15}, {%24, %25, %26, %27}, db, %46, 0, 1, 1, 1, 1;\n"
    "add.s64 db, %44, %45 + 384;\n"
    "wgmma.mma_async.sp.sync.aligned.m64n32k32.f32.bf16.bf16 {%0, %1, %2, %3, %4, %5, %6, %7, %8, %9, %10, %11, %12, %13, %14, %15}, {%28, %29, %30, %31}, db, %46, 0, 1, 1, 1, 1;\n"
    "add.s64 db, %44, %45 + 512;\n"
    "wgmma.mma_async.sp.sync.aligned.m64n32k32.f32.bf16.bf16 {%0, %1, %2, %3, %4, %5, %6, %7, %8, %9, %10, %11, %12, %13, %14, %15}, {%32, %33, %34, %35}, db, %46, 0, 1, 1, 1, 1;\n"
    "add.s64 db, %44, %45 + 640;\n"
    "wgmma.mma_async.sp.sync.aligned.m64n32k32.f32.bf16.bf16 {%0, %1, %2, %3, %4, %5, %6, %7, %8, %9, %10, %11, %12, %13, %14, %15}, {%36, %37, %38, %39}, db, %46, 0, 1, 1, 1, 1;\n"
    "add.s64 db, %44, %45 + 768;\n"
    "wgmma.mma_async.sp.sync.aligned.m64n32k32.f32.bf16.bf16 {%0, %1, %2, %3, %4, %5, %6, %7, %8, %9, %10, %11, %12, %13, %14, %15}, {%40, %41, %42, %43}, db, %46, 0, 1, 1, 1, 1;\n"
    "wgmma.commit_group.sync.aligned;\n}\n"
    : "=f"(d[0]), "=f"(d[1]), "=f"(d[2]), "=f"(d[3]), "=f"(d[4]), "=f"(d[5]), "=f"(d[6]), "=f"(d[7]), "=f"(d[8]), "=f"(d[9]), "=f"(d[10]), "=f"(d[11]), "=f"(d[12]), "=f"(d[13]), "=f"(d[14]), "=f"(d[15])
    : "r"(a[0]), "r"(a[1]), "r"(a[2]), "r"(a[3]), "r"(a[4]), "r"(a[5]), "r"(a[6]), "r"(a[7]), "r"(a[8]), "r"(a[9]), "r"(a[10]), "r"(a[11]), "r"(a[12]), "r"(a[13]), "r"(a[14]), "r"(a[15]), "r"(a[16]), "r"(a[17]), "r"(a[18]), "r"(a[19]), "r"(a[20]), "r"(a[21]), "r"(a[22]), "r"(a[23]), "r"(a[24]), "r"(a[25]), "r"(a[26]), "r"(a[27]), "l"(db), "n"(D), "r"(meta)
    : "memory");
}
template<int D> __device__ __forceinline__ void c2_more(float (&d)[16], const uint32_t (&a)[28], uint64_t db, uint32_t meta) {
  asm volatile("{\n.reg .b64 db;\n"
    "wgmma.fence.sync.aligned;\n"
    "add.s64 db, %44, %45 + 0;\n"
    "wgmma.mma_async.sp.sync.aligned.m64n32k32.f32.bf16.bf16 {%0, %1, %2, %3, %4, %5, %6, %7, %8, %9, %10, %11, %12, %13, %14, %15}, {%16, %17, %18, %19}, db, %46, 0, 1, 1, 1, 1;\n"
    "add.s64 db, %44, %45 + 128;\n"
    "wgmma.mma_async.sp.sync.aligned.m64n32k32.f32.bf16.bf16 {%0, %1, %2, %3, %4, %5, %6, %7, %8, %9, %10, %11, %12, %13, %14, %15}, {%20, %21, %22, %23}, db, %46, 0, 1, 1, 1, 1;\n"
    "add.s64 db, %44, %45 + 256;\n"
    "wgmma.mma_async.sp.sync.aligned.m64n32k32.f32.bf16.bf16 {%0, %1, %2, %3, %4, %5, %6, %7, %8, %9, %10, %11, %12, %13, %14, %15}, {%24, %25, %26, %27}, db, %46, 0, 1, 1, 1, 1;\n"
    "add.s64 db, %44, %45 + 384;\n"
    "wgmma.mma_async.sp.sync.aligned.m64n32k32.f32.bf16.bf16 {%0, %1, %2, %3, %4, %5, %6, %7, %8, %9, %10, %11, %12, %13, %14, %15}, {%28, %29, %30, %31}, db, %46, 0, 1, 1, 1, 1;\n"
    "add.s64 db, %44, %45 + 512;\n"
    "wgmma.mma_async.sp.sync.aligned.m64n32k32.f32.bf16.bf16 {%0, %1, %2, %3, %4, %5, %6, %7, %8, %9, %10, %11, %12, %13, %14, %15}, {%32, %33, %34, %35}, db, %46, 0, 1, 1, 1, 1;\n"
    "add.s64 db, %44, %45 + 640;\n"
    "wgmma.mma_async.sp.sync.aligned.m64n32k32.f32.bf16.bf16 {%0, %1, %2, %3, %4, %5, %6, %7, %8, %9, %10, %11, %12, %13, %14, %15}, {%36, %37, %38, %39}, db, %46, 0, 1, 1, 1, 1;\n"
    "add.s64 db, %44, %45 + 768;\n"
    "wgmma.mma_async.sp.sync.aligned.m64n32k32.f32.bf16.bf16 {%0, %1, %2, %3, %4, %5, %6, %7, %8, %9, %10, %11, %12, %13, %14, %15}, {%40, %41, %42, %43}, db, %46, 0, 1, 1, 1, 1;\n"
    "wgmma.commit_group.sync.aligned;\n}\n"
    : "+f"(d[0]), "+f"(d[1]), "+f"(d[2]), "+f"(d[3]), "+f"(d[4]), "+f"(d[5]), "+f"(d[6]), "+f"(d[7]), "+f"(d[8]), "+f"(d[9]), "+f"(d[10]), "+f"(d[11]), "+f"(d[12]), "+f"(d[13]), "+f"(d[14]), "+f"(d[15])
    : "r"(a[0]), "r"(a[1]), "r"(a[2]), "r"(a[3]), "r"(a[4]), "r"(a[5]), "r"(a[6]), "r"(a[7]), "r"(a[8]), "r"(a[9]), "r"(a[10]), "r"(a[11]), "r"(a[12]), "r"(a[13]), "r"(a[14]), "r"(a[15]), "r"(a[16]), "r"(a[17]), "r"(a[18]), "r"(a[19]), "r"(a[20]), "r"(a[21]), "r"(a[22]), "r"(a[23]), "r"(a[24]), "r"(a[25]), "r"(a[26]), "r"(a[27]), "l"(db), "n"(D), "r"(meta)
    : "memory");
}
template<int N> __device__ __forceinline__ void mma_wait(float (&d)[4]) {
  asm volatile("wgmma.wait_group.sync.aligned %4;"
    : "+f"(d[0]), "+f"(d[1]), "+f"(d[2]), "+f"(d[3])
    : "n"(N) : "memory");
}
template<int N> __device__ __forceinline__ void mma_wait(float (&d)[16]) {
  asm volatile("wgmma.wait_group.sync.aligned %16;"
    : "+f"(d[0]), "+f"(d[1]), "+f"(d[2]), "+f"(d[3]), "+f"(d[4]), "+f"(d[5]), "+f"(d[6]), "+f"(d[7]), "+f"(d[8]), "+f"(d[9]), "+f"(d[10]), "+f"(d[11]), "+f"(d[12]), "+f"(d[13]), "+f"(d[14]), "+f"(d[15])
    : "n"(N) : "memory");
}
template<int N> __device__ __forceinline__ void mma_wait(float (&d)[20]) {
  asm volatile("wgmma.wait_group.sync.aligned %20;"
    : "+f"(d[0]), "+f"(d[1]), "+f"(d[2]), "+f"(d[3]), "+f"(d[4]), "+f"(d[5]), "+f"(d[6]), "+f"(d[7]), "+f"(d[8]), "+f"(d[9]), "+f"(d[10]), "+f"(d[11]), "+f"(d[12]), "+f"(d[13]), "+f"(d[14]), "+f"(d[15]), "+f"(d[16]), "+f"(d[17]), "+f"(d[18]), "+f"(d[19])
    : "n"(N) : "memory");
}
template<int N> __device__ __forceinline__ void mma_wait(float (&d)[24]) {
  asm volatile("wgmma.wait_group.sync.aligned %24;"
    : "+f"(d[0]), "+f"(d[1]), "+f"(d[2]), "+f"(d[3]), "+f"(d[4]), "+f"(d[5]), "+f"(d[6]), "+f"(d[7]), "+f"(d[8]), "+f"(d[9]), "+f"(d[10]), "+f"(d[11]), "+f"(d[12]), "+f"(d[13]), "+f"(d[14]), "+f"(d[15]), "+f"(d[16]), "+f"(d[17]), "+f"(d[18]), "+f"(d[19]), "+f"(d[20]), "+f"(d[21]), "+f"(d[22]), "+f"(d[23])
    : "n"(N) : "memory");
}
template<int N> __device__ __forceinline__ void mma_wait(float (&d)[28]) {
  asm volatile("wgmma.wait_group.sync.aligned %28;"
    : "+f"(d[0]), "+f"(d[1]), "+f"(d[2]), "+f"(d[3]), "+f"(d[4]), "+f"(d[5]), "+f"(d[6]), "+f"(d[7]), "+f"(d[8]), "+f"(d[9]), "+f"(d[10]), "+f"(d[11]), "+f"(d[12]), "+f"(d[13]), "+f"(d[14]), "+f"(d[15]), "+f"(d[16]), "+f"(d[17]), "+f"(d[18]), "+f"(d[19]), "+f"(d[20]), "+f"(d[21]), "+f"(d[22]), "+f"(d[23]), "+f"(d[24]), "+f"(d[25]), "+f"(d[26]), "+f"(d[27])
    : "n"(N) : "memory");
}
template<int N> __device__ __forceinline__ void mma_wait(float (&d)[32]) {
  asm volatile("wgmma.wait_group.sync.aligned %32;"
    : "+f"(d[0]), "+f"(d[1]), "+f"(d[2]), "+f"(d[3]), "+f"(d[4]), "+f"(d[5]), "+f"(d[6]), "+f"(d[7]), "+f"(d[8]), "+f"(d[9]), "+f"(d[10]), "+f"(d[11]), "+f"(d[12]), "+f"(d[13]), "+f"(d[14]), "+f"(d[15]), "+f"(d[16]), "+f"(d[17]), "+f"(d[18]), "+f"(d[19]), "+f"(d[20]), "+f"(d[21]), "+f"(d[22]), "+f"(d[23]), "+f"(d[24]), "+f"(d[25]), "+f"(d[26]), "+f"(d[27]), "+f"(d[28]), "+f"(d[29]), "+f"(d[30]), "+f"(d[31])
    : "n"(N) : "memory");
}
template<int N> __device__ __forceinline__ void mma_wait(float (&d)[36]) {
  asm volatile("wgmma.wait_group.sync.aligned %36;"
    : "+f"(d[0]), "+f"(d[1]), "+f"(d[2]), "+f"(d[3]), "+f"(d[4]), "+f"(d[5]), "+f"(d[6]), "+f"(d[7]), "+f"(d[8]), "+f"(d[9]), "+f"(d[10]), "+f"(d[11]), "+f"(d[12]), "+f"(d[13]), "+f"(d[14]), "+f"(d[15]), "+f"(d[16]), "+f"(d[17]), "+f"(d[18]), "+f"(d[19]), "+f"(d[20]), "+f"(d[21]), "+f"(d[22]), "+f"(d[23]), "+f"(d[24]), "+f"(d[25]), "+f"(d[26]), "+f"(d[27]), "+f"(d[28]), "+f"(d[29]), "+f"(d[30]), "+f"(d[31]), "+f"(d[32]), "+f"(d[33]), "+f"(d[34]), "+f"(d[35])
    : "n"(N) : "memory");
}
template<int N> __device__ __forceinline__ void mma_wait(float (&d)[40]) {
  asm volatile("wgmma.wait_group.sync.aligned %40;"
    : "+f"(d[0]), "+f"(d[1]), "+f"(d[2]), "+f"(d[3]), "+f"(d[4]), "+f"(d[5]), "+f"(d[6]), "+f"(d[7]), "+f"(d[8]), "+f"(d[9]), "+f"(d[10]), "+f"(d[11]), "+f"(d[12]), "+f"(d[13]), "+f"(d[14]), "+f"(d[15]), "+f"(d[16]), "+f"(d[17]), "+f"(d[18]), "+f"(d[19]), "+f"(d[20]), "+f"(d[21]), "+f"(d[22]), "+f"(d[23]), "+f"(d[24]), "+f"(d[25]), "+f"(d[26]), "+f"(d[27]), "+f"(d[28]), "+f"(d[29]), "+f"(d[30]), "+f"(d[31]), "+f"(d[32]), "+f"(d[33]), "+f"(d[34]), "+f"(d[35]), "+f"(d[36]), "+f"(d[37]), "+f"(d[38]), "+f"(d[39])
    : "n"(N) : "memory");
}
template<int N> __device__ __forceinline__ void mma_wait(float (&d)[44]) {
  asm volatile("wgmma.wait_group.sync.aligned %44;"
    : "+f"(d[0]), "+f"(d[1]), "+f"(d[2]), "+f"(d[3]), "+f"(d[4]), "+f"(d[5]), "+f"(d[6]), "+f"(d[7]), "+f"(d[8]), "+f"(d[9]), "+f"(d[10]), "+f"(d[11]), "+f"(d[12]), "+f"(d[13]), "+f"(d[14]), "+f"(d[15]), "+f"(d[16]), "+f"(d[17]), "+f"(d[18]), "+f"(d[19]), "+f"(d[20]), "+f"(d[21]), "+f"(d[22]), "+f"(d[23]), "+f"(d[24]), "+f"(d[25]), "+f"(d[26]), "+f"(d[27]), "+f"(d[28]), "+f"(d[29]), "+f"(d[30]), "+f"(d[31]), "+f"(d[32]), "+f"(d[33]), "+f"(d[34]), "+f"(d[35]), "+f"(d[36]), "+f"(d[37]), "+f"(d[38]), "+f"(d[39]), "+f"(d[40]), "+f"(d[41]), "+f"(d[42]), "+f"(d[43])
    : "n"(N) : "memory");
}
__device__ __forceinline__ void mma_fence() { asm volatile("wgmma.fence.sync.aligned;" ::: "memory"); }

__device__ __forceinline__ uint32_t smem_u32(const void* p) { return (uint32_t)__cvta_generic_to_shared(p); }

__device__ __forceinline__ void mbar_init(uint32_t bar, uint32_t cnt) {
  asm volatile("mbarrier.init.shared::cta.b64 [%0], %1;" :: "r"(bar), "r"(cnt) : "memory");
}
__device__ __forceinline__ void mbar_arrive(uint32_t bar) {
  asm volatile("mbarrier.arrive.shared::cta.b64 _, [%0];" :: "r"(bar) : "memory");
}
__device__ __forceinline__ void mbar_wait(uint32_t bar, uint32_t parity) {
  asm volatile("{\n.reg .pred p;\n.reg .u32 n;\n"
               "mov.u32 n, 0;\n"
               "WAIT_LOOP:\n"
               "mbarrier.try_wait.parity.shared::cta.b64 p, [%0], %1;\n"
               "@p bra.uni WAIT_DONE;\n"
               "add.u32 n, n, 1;\n"
               "setp.lt.u32 p, n, 0x1000000;\n"
               "@p bra.uni WAIT_LOOP;\n"
               "trap;\n"
               "WAIT_DONE:\n}\n"
               :: "r"(bar), "r"(parity) : "memory");
}
__device__ __forceinline__ void mbar_wait_unless(uint32_t ok, uint32_t bar, uint32_t parity) {
  asm volatile("{\n.reg .pred p;\n.reg .u32 n;\n"
               "setp.ne.u32 p, %2, 0;\n"
               "@p bra.uni WAIT_DONE;\n"
               "mov.u32 n, 0;\n"
               "WAIT_LOOP:\n"
               "mbarrier.try_wait.parity.shared::cta.b64 p, [%0], %1;\n"
               "@p bra.uni WAIT_DONE;\n"
               "add.u32 n, n, 1;\n"
               "setp.lt.u32 p, n, 0x1000000;\n"
               "@p bra.uni WAIT_LOOP;\n"
               "trap;\n"
               "WAIT_DONE:\n}\n"
               :: "r"(bar), "r"(parity), "r"(ok) : "memory");
}
__device__ __forceinline__ uint32_t mbar_test(uint32_t bar, uint32_t parity) {
  uint32_t ok;
  asm volatile("{\n.reg .pred p;\nmbarrier.test_wait.parity.shared::cta.b64 p, [%1], %2;\nselp.u32 %0, 1, 0, p;\n}\n"
               : "=r"(ok) : "r"(bar), "r"(parity) : "memory");
  return ok;
}
__device__ __forceinline__ void cp_async16(uint32_t dst, const void* src) {
  asm volatile("cp.async.cg.shared.global [%0], [%1], 16;" :: "r"(dst), "l"(src) : "memory");
}
#define DIN_ADDR4                                                                        \
  "mov.b64 {x, y}, %0;\ndp4a.u32.u32 x, %8, 0x80, %11;\nmov.b64 %0, {x, y};\n"           \
  "mov.b64 {x, y}, %1;\ndp4a.u32.u32 x, %8, 0x8000, %11;\nmov.b64 %1, {x, y};\n"         \
  "mov.b64 {x, y}, %2;\ndp4a.u32.u32 x, %8, 0x800000, %11;\nmov.b64 %2, {x, y};\n"       \
  "mov.b64 {x, y}, %3;\ndp4a.u32.u32 x, %8, 0x80000000, %11;\nmov.b64 %3, {x, y};\n"
template<int T>
__device__ __forceinline__ void cp_group(const uint32_t (&dst)[4], uint64_t (&a)[4], uint32_t rows4, uint32_t base, uint64_t pol) {
  asm volatile("{\n.reg .u32 x, y;\n" DIN_ADDR4
               "cp.async.cg.shared.global.L2::cache_hint [%4 + %10], [%0], 16, %9;\n"
               "cp.async.cg.shared.global.L2::cache_hint [%5 + %10], [%1], 16, %9;\n"
               "cp.async.cg.shared.global.L2::cache_hint [%6 + %10], [%2], 16, %9;\n"
               "cp.async.cg.shared.global.L2::cache_hint [%7 + %10], [%3], 16, %9;\n}\n"
               : "+l"(a[0]), "+l"(a[1]), "+l"(a[2]), "+l"(a[3])
               : "r"(dst[0]), "r"(dst[1]), "r"(dst[2]), "r"(dst[3]), "r"(rows4), "l"(pol), "n"(T * 2048), "r"(base) : "memory");
}
template<int T>
__device__ __forceinline__ void cp_group_z(const uint32_t (&dst)[4], uint64_t (&a)[4], uint32_t rows4, uint32_t base, int left, uint64_t pol) {
  asm volatile("{\n.reg .u32 x, y;\n.reg .pred p0, p1, p2, p3;\n" DIN_ADDR4
               "setp.le.s32 p0, %12, %13;\nsetp.le.s32 p1, %12, %13 + 1;\nsetp.le.s32 p2, %12, %13 + 2;\nsetp.le.s32 p3, %12, %13 + 3;\n"
               "cp.async.cg.shared.global.L2::cache_hint [%4 + %10], [%0], 16, p0, %9;\n"
               "cp.async.cg.shared.global.L2::cache_hint [%5 + %10], [%1], 16, p1, %9;\n"
               "cp.async.cg.shared.global.L2::cache_hint [%6 + %10], [%2], 16, p2, %9;\n"
               "cp.async.cg.shared.global.L2::cache_hint [%7 + %10], [%3], 16, p3, %9;\n}\n"
               : "+l"(a[0]), "+l"(a[1]), "+l"(a[2]), "+l"(a[3])
               : "r"(dst[0]), "r"(dst[1]), "r"(dst[2]), "r"(dst[3]), "r"(rows4), "l"(pol), "n"(T * 2048), "r"(base),
                 "r"(left), "n"(T * 16) : "memory");
}
__device__ __forceinline__ uint32_t prmt(uint32_t a, uint32_t b, uint32_t sel) {
  uint32_t d;
  asm("prmt.b32 %0, %1, %2, %3;" : "=r"(d) : "r"(a), "r"(b), "r"(sel));
  return d;
}
__device__ __forceinline__ uint32_t ballot_bit(uint32_t x, uint32_t bit) {
  uint32_t d;
  asm volatile("{\n.reg .pred p;\n.reg .u32 t;\nand.b32 t, %1, %2;\nsetp.ne.u32 p, t, 0;\nvote.sync.ballot.b32 %0, p, 0xffffffff;\n}\n"
               : "=r"(d) : "r"(x), "r"(bit));
  return d;
}
__device__ __forceinline__ uint4 load_mask(const void* mask, uint32_t b, uint32_t i) {
  uint4 m;
  asm volatile("ld.global.nc.L1::no_allocate.v4.u32 {%0,%1,%2,%3}, [%4];"
               : "=r"(m.x), "=r"(m.y), "=r"(m.z), "=r"(m.w) : "l"(reinterpret_cast<const uint4*>(mask) + (b * 25u + i)));
  return m;
}
__device__ __forceinline__ uint32_t nonzero_as_one(uint32_t x) {
  uint32_t d;
  asm("set.neu.bf16x2.bf16x2 %0, %1, %2;" : "=r"(d) : "r"(x), "r"(0u));
  return d;
}
__device__ __forceinline__ void cp_async_arrive_noinc(uint32_t bar) {
  asm volatile("cp.async.mbarrier.arrive.noinc.shared::cta.b64 [%0];" :: "r"(bar) : "memory");
}
__device__ __forceinline__ void ldsm_x4(uint32_t addr, uint32_t& r0, uint32_t& r1, uint32_t& r2, uint32_t& r3) {
  asm volatile("ldmatrix.sync.aligned.m8n8.x4.shared.b16 {%0,%1,%2,%3}, [%4];"
               : "=r"(r0), "=r"(r1), "=r"(r2), "=r"(r3) : "r"(addr) : "memory");
}
__device__ __forceinline__ void ldsm_x4_t(uint32_t addr, uint32_t& r0, uint32_t& r1, uint32_t& r2, uint32_t& r3) {
  asm volatile("ldmatrix.sync.aligned.m8n8.x4.trans.shared.b16 {%0,%1,%2,%3}, [%4];"
               : "=r"(r0), "=r"(r1), "=r"(r2), "=r"(r3) : "r"(addr) : "memory");
}
__device__ __forceinline__ void stsm_x4(uint32_t addr, uint32_t r0, uint32_t r1, uint32_t r2, uint32_t r3) {
  asm volatile("stmatrix.sync.aligned.m8n8.x4.shared.b16 [%0], {%1,%2,%3,%4};"
               :: "r"(addr), "r"(r0), "r"(r1), "r"(r2), "r"(r3) : "memory");
}
__device__ __forceinline__ void stsm_x2(uint32_t addr, uint32_t r0, uint32_t r1) {
  asm volatile("stmatrix.sync.aligned.m8n8.x2.shared.b16 [%0], {%1,%2};"
               :: "r"(addr), "r"(r0), "r"(r1) : "memory");
}
__device__ __forceinline__ uint32_t hfma2_bf16(uint32_t a, uint32_t b, uint32_t c) {
  uint32_t d;
  asm volatile("fma.rn.bf16x2 %0, %1, %2, %3;" : "=r"(d) : "r"(a), "r"(b), "r"(c));
  return d;
}
__device__ __forceinline__ uint32_t pack_bf16(float lo, float hi) {
  uint32_t d;
  asm("cvt.rn.bf16x2.f32 %0, %1, %2;" : "=r"(d) : "f"(hi), "f"(lo));
  return d;
}
__device__ __forceinline__ uint32_t lds32(uint32_t a) {
  uint32_t v; asm volatile("ld.shared.u32 %0, [%1];" : "=r"(v) : "r"(a) : "memory"); return v;
}
__device__ __forceinline__ uint32_t lds16(uint32_t a) {
  uint32_t v; asm volatile("ld.shared.u16 %0, [%1];" : "=r"(v) : "r"(a) : "memory"); return v;
}
__device__ __forceinline__ void sts32(uint32_t a, uint32_t v) {
  asm volatile("st.shared.u32 [%0], %1;" :: "r"(a), "r"(v) : "memory");
}
__device__ __forceinline__ void sts16(uint32_t a, uint32_t v) {
  asm volatile("st.shared.u16 [%0], %1;" :: "r"(a), "h"((unsigned short)v) : "memory");
}
__device__ __forceinline__ void sts8(uint32_t a, uint32_t v) {
  asm volatile("st.shared.u8 [%0], %1;" :: "r"(a), "r"(v) : "memory");
}
constexpr uint32_t DESC_ROWS = 0x40000040u, DESC_HALVES = 0x80000020u;
__device__ __forceinline__ uint32_t desc_lo(uint32_t addr) { return ((addr & 0x3FFFF) >> 4) | (1u << 16); }

__device__ __forceinline__ uint4 lds128(uint32_t a) {
  uint4 v;
  asm volatile("ld.shared.v4.u32 {%0,%1,%2,%3}, [%4];" : "=r"(v.x), "=r"(v.y), "=r"(v.z), "=r"(v.w) : "r"(a) : "memory");
  return v;
}
__device__ __forceinline__ void sts128(uint32_t a, uint4 v) {
  asm volatile("st.shared.v4.u32 [%0], {%1,%2,%3,%4};" :: "r"(a), "r"(v.x), "r"(v.y), "r"(v.z), "r"(v.w) : "memory");
}
__device__ __forceinline__ void prefetch_l2(const void* p, uint32_t bytes) {
  asm volatile("cp.async.bulk.prefetch.L2.global [%0], %1;" :: "l"(p), "r"(bytes) : "memory");
}

template<int ND>
__device__ __forceinline__ void tanh_groups(float (&d)[ND], int i0, int i1) {
#pragma unroll
  for (int i = 4 * i0; i < 4 * i1; i++) asm volatile("tanh.approx.f32 %0, %0;" : "+f"(d[i ^ 2]));
}
template<int ND>
__device__ __forceinline__ uint32_t mix(const float (&d)[ND], int i, float w2a, float w2b, float c32) {
  uint32_t p;
  asm volatile("{\n.reg .f32 x, y;\nfma.rn.f32 x, %3, %6, %7;\nfma.rn.f32 y, %4, %6, %7;\n"
               "fma.rn.f32 x, %1, %5, x;\nfma.rn.f32 y, %2, %5, y;\ncvt.rn.bf16x2.f32 %0, y, x;\n}\n"
               : "=r"(p) : "f"(d[4 * i]), "f"(d[4 * i + 1]), "f"(d[4 * i + 2]), "f"(d[4 * i + 3]), "f"(w2a), "f"(w2b), "f"(c32));
  return p;
}
template<int K> __device__ __forceinline__ uint32_t keep(uint32_t x) { return K ? __shfl_sync(0xffffffffu, x, 0) : x; }
template<int V> struct Int { static constexpr int value = V; };

__global__ void __launch_bounds__(NTHREADS, 1)
din_kernel(const __nv_bfloat16* __restrict__ mask, const __nv_bfloat16* __restrict__ target, int B, int grid,
           uint32_t pf_mask, uint32_t pf_tgt, const __nv_bfloat16* __restrict__ w1, const __nv_bfloat16* __restrict__ hist,
           const __nv_bfloat16* __restrict__ b1, const __nv_bfloat16* __restrict__ w2,
           const __nv_bfloat16* __restrict__ b2, __nv_bfloat16* __restrict__ out, unsigned int* counter, int pace,
           int slow_from, int pace_slow, int spread) {
  {
    const char* pm = reinterpret_cast<const char*>(mask) + (size_t)blockIdx.x * pf_mask;
    const char* pt = reinterpret_cast<const char*>(target) + (size_t)blockIdx.x * pf_tgt;
    const uint32_t o = threadIdx.x * 128;
    asm volatile("{\n.reg .pred p;\nsetp.lt.u32 p, %1, %2;\n@p prefetch.global.L2 [%0];\n}\n" :: "l"(pm + o), "r"(o), "r"(pf_mask));
    asm volatile("{\n.reg .pred p;\nsetp.lt.u32 p, %1, %2;\n@p prefetch.global.L2 [%0];\n}\n" :: "l"(pt + o), "r"(o), "r"(pf_tgt));
  }
  extern __shared__ unsigned char smem_raw[];
  const uint32_t sb = (smem_u32(smem_raw) + 1023u) & ~1023u;
  const int tid = threadIdx.x, lane = tid & 31;
  const int warp = __shfl_sync(0xffffffffu, tid >> 5, 0);
#define ACT NCW
  const int bstep = ACT * grid;

  STAMP(0);
  if (warp < NCW * 4) {
    const int wg = warp >> 2, w = warp & 3;
    const int g = lane >> 2;
    const uint32_t ring = sb + wg * RING_BYTES;
    const bool active = wg * grid + (int)blockIdx.x < B && wg < ACT;
    {
      const int t = tid & 127;
      const uint32_t dst = sb + ((t ^ ((t >> 3) & 7)) << 4);
      const char* src = reinterpret_cast<const char*>(w1) + t * 16;
#pragma unroll
      for (int i = 0; i < 4; i++) cp_async16(dst + w1_at(i) + wg * 2048, src + i * 8192 + wg * 2048);
      cp_async16(dst + w1_at(0) + (wg >> 1) * RING_BYTES + (wg & 1) * SLOT_BYTES + 6144, src + wg * 8192 + 6144);
      if (wg == 0) cp_async16(dst + w1_at(3) + 6144, src + 3 * 8192 + 6144);
      if (lane < 8) {
        if (w == 0 && active) cp_async16(ring + R_TGT0 + lane * 16, target + (size_t)(wg * grid + blockIdx.x) * kD + lane * 8);
        if (w == 1 && wg < 2) cp_async16(ring + R_VEC + lane * 16, (wg ? w2 : b1) + lane * 8);
      }
    }
    if (w == 2) sts32(ring + R_SEL + lane * 4, 0x3f803f80u);
    uint32_t rb2;
    asm volatile("ld.global.nc.u16 %0, [%1];" : "=r"(rb2) : "l"(b2));
    asm volatile("setmaxnreg.inc.sync.aligned.u32 %0;" :: "n"(CONS_REGS));
    asm volatile("cp.async.wait_all;" ::: "memory");
    STAMP(5);
    asm volatile("bar.sync 1, %0;" :: "n"(NCW * 160) : "memory");
    const uint32_t half2 = 0x3f003f00u, nhalf2 = 0xbf00bf00u, nzero2 = 0x80008000u;
    const uint32_t vec = sb + R_VEC + (16 * w + g) * 2;
    const float w2a = 0.5f * __uint_as_float(lds16(vec + RING_BYTES) << 16);
    const float w2b = 0.5f * __uint_as_float(lds16(vec + RING_BYTES + 16) << 16);
    const uint32_t rw2 = lds32(sb + RING_BYTES + R_VEC + lane * 4);
    float c32 = __uint_as_float(rw2 << 16) + __uint_as_float(rw2 & 0xffff0000u);
#pragma unroll
    for (int o = 16; o; o >>= 1) c32 += __shfl_xor_sync(0xffffffffu, c32, o);
    c32 = (0.5f * c32 + __uint_as_float(rb2 << 16)) * (1.0f / 32.0f);
    uint32_t bq[4];
    bq[2] = hfma2_bf16(lds16(vec), half2, nzero2);
    bq[3] = hfma2_bf16(lds16(vec + 16), half2, nzero2);
    if (lane & 3) bq[2] = bq[3] = 0;
    uint32_t wac[16], wd[16], wbc[16];
    {
      const int mi = lane >> 3, rr = lane & 7;
      const uint32_t a0 = sb + (8 * (mi >> 1) + rr) * 128 + (((2 * w + (mi & 1)) ^ rr) << 4);
#pragma unroll
      for (int ks = 0; ks < 4; ks++) {
        uint32_t A[4], Bm[4], C[4], Dm[4];
        ldsm_x4_t(a0 + ks * 2048 + w1_at(0), A[0], A[1], A[2], A[3]);
        ldsm_x4_t(a0 + ks * 2048 + w1_at(1), Bm[0], Bm[1], Bm[2], Bm[3]);
        ldsm_x4_t(a0 + ks * 2048 + w1_at(2), C[0], C[1], C[2], C[3]);
        ldsm_x4_t(a0 + ks * 2048 + w1_at(3), Dm[0], Dm[1], Dm[2], Dm[3]);
#pragma unroll
        for (int e = 0; e < 4; e++) {
          wac[4 * ks + e] = hfma2_bf16(A[e], half2, hfma2_bf16(C[e], half2, nzero2));
          wbc[4 * ks + e] = hfma2_bf16(Bm[e], half2, hfma2_bf16(C[e], nhalf2, nzero2));
          wd[4 * ks + e] = hfma2_bf16(Dm[e], half2, nzero2);
        }
      }
    }
    asm volatile("fence.proxy.async.shared::cta;" ::: "memory");
    asm volatile("bar.sync 5, %0;" :: "n"(NCW * 128) : "memory");

    const uint32_t ln = __shfl_sync(0xffffffffu, lane, lane);
    const uint32_t q0 = __shfl_sync(0xffffffffu, (lane & 3) ? 0u : 0xffffffffu, lane);
    const uint32_t meta = __shfl_sync(0xffffffffu, 0x88dddd88u + (grid >> 20), lane);
    const uint32_t zr = grid >> 20;
    const uint32_t sel = keep<K_SEL>(((ring + R_SEL) & 0x3FFFF) >> 4);
    const uint32_t ost = __shfl_sync(0xffffffffu, w * 2048 + lane * 16, lane);
    const uint32_t first = keep<K_FIRST>(ring);
    const uint32_t last = keep<K_LAST>(first + (NSLOT - 1) * SLOT_BYTES);
    uint32_t sa = first, phase = 0;
    uint32_t we[16];
    auto make_weff = [&](uint32_t ta) {
      uint32_t t[8];
      ta += (ln & 24) << 1;
      ldsm_x4(ta, t[0], t[1], t[2], t[3]);
      ldsm_x4(ta + 64, t[4], t[5], t[6], t[7]);
#pragma unroll
      for (int i = 0; i < 16; i++) we[i] = hfma2_bf16(t[i >> 1], wd[i], wac[i]);
    };
    auto make_bq = [&](const float (&bz)[4]) {
#pragma unroll
      for (int e = 0; e < 2; e++) {
        const uint32_t v = __float_as_uint(bz[2 * e]) & q0;
        const float hi = __uint_as_float(v & 0xffff0000u);
        bq[e] = pack_bf16(__uint_as_float(v) - hi, hi);
      }
    };
    if (active) {
      {
        float bz[4];
        uint64_t d0 = (uint64_t)DESC_ROWS << 32 | (ring + R_TGT0) >> 4;
        mma_fence();
        cbias<0>(bz, wbc, d0);
        make_weff(ring + R_TGT0);
        mma_wait<0>(bz);
        make_bq(bz);
      }
      STAMP(1);
      uint32_t raw = 0, cur = ring, hdr = 0;
#pragma unroll 1
      for (uint32_t pass = WARM ? zr : 1; pass < 2; pass++) {
      if (pass) {
      if (!LC) { mbar_wait(ring + S_FULL, 0); raw = lds32(ring + S_HDR); }
      uint32_t full = 0;
      while (true) {
        hdr = __shfl_sync(0xffffffffu, raw, 0);
        cur = sa;
        auto chunk = [&](auto groups) {
          constexpr int N8 = decltype(groups)::value, NA = N8 < KV || NX < 5 ? NX : 5, NY = N8 - NA, S1 = N8 < KV || NX < 5 ? SA : 2;
          constexpr int KT = (N8 + 1) / 2, E2 = KT - (N8 < KV ? KL : 3), E1 = E2 - (N8 < KV ? KM : 0), E0 = K0 && N8 < KV && K0 < E1 ? K0 : E1;
          constexpr int MF = N8 < KV ? ME : 0;
          float x[4 * NA], y[4 * NY], bz[4], o[16];
          uint32_t a[4 * E0], a1[E1 > E0 ? 4 * (E1 - E0) : 4], a2[E2 > E1 ? 4 * (E2 - E1) : 4], a3[4 * (KT - E2)];
          auto M = [&](int i0, int i1) {
#pragma unroll
            for (int i = i0; i < i1; i++) {
              uint32_t p = i < NA ? mix(x, i, w2a, w2b, c32) : i < N8 ? mix(y, i - NA, w2a, w2b, c32) : 0;
              if (N8 == 16) {
                uint32_t m = 0x3f803f80u;
                asm volatile("{\n.reg .pred p;\nsetp.ne.u32 p, %1, 0;\n@p ld.shared.u32 %0, [%2];\n}\n"
                             : "+r"(m) : "r"(hdr & H_GENERAL), "r"(cur + S_MASK + i * 16 + (ln & 3) * 4) : "memory");
                p = hfma2_bf16(p, m, 0x80008000u);
              }
              if (i < 2 * E0) a[2 * i] = a[2 * i + 1] = p;
              else if (i < 2 * E1) a1[2 * i - 4 * E0] = a1[2 * i - 4 * E0 + 1] = p;
              else if (i < 2 * E2) a2[2 * i - 4 * E1] = a2[2 * i - 4 * E1 + 1] = p;
              else a3[2 * i - 4 * E2] = a3[2 * i - 4 * E2 + 1] = p;
            }
          };
          int done = 0;
          auto T = [&](int upto) {
            upto = upto < 4 * NY ? upto : 4 * NY;
#pragma unroll
            for (int i = done; i < upto; i++) asm volatile("tanh.approx.f32 %0, %0;" : "+f"(y[i ^ 2]));
            done = upto > done ? upto : done;
          };
          auto pin4 = [&](uint32_t r0, uint32_t r1, uint32_t r2, uint32_t r3) {
            asm volatile("{\n.reg .pred p;\nsetp.ne.u32 p, %4, 0;\n@p st.shared.v4.u32 [%4], {%0,%1,%2,%3};\n}\n"
                         :: "r"(r0), "r"(r1), "r"(r2), "r"(r3), "r"(zr) : "memory");
          };
          uint64_t d1 = (uint64_t)(DESC_ROWS + (cur >> 24)) << 32 | ((cur >> 4) - DOFF);
          const uint32_t par = phase;
          phase ^= sa == last;
          sa = sa == last ? first : sa + SLOT_BYTES;
          mma_fence();
          sel_clr(x, bq, sel, 0);
          sel_clr(y, bq, sel, NY == NA ? zr : 0);
          if (EA) mbar_wait_unless(full, cur + S_FULL, par);
          else mbar_wait(cur + S_FULL, par);
          LOGT(0);
          DURT(sub);
          mma_fence();
          c1_acc<DOFF>(x, we, d1);
          if (SPLIT) {
            cbias<DOFF + S_TGT / 16>(bz, wbc, d1);
            mma_wait<1>(x);
            auto TX = [&](int i0, int i1) {
#pragma unroll
              for (int i = i0; i < i1; i++) asm volatile("tanh.approx.f32 %0, %0;" : "+f"(x[i ^ 2]));
            };
            auto PX = [&](int i0, int i1) {
#pragma unroll
              for (int i = i0; i < i1; i += 4) pin4(__float_as_uint(x[i]), __float_as_uint(x[i + 1]), __float_as_uint(x[i + 2]), __float_as_uint(x[i + 3]));
            };
            if (EARLY) {
              TX(0, 4 * S1 - EARLY);
              const uint32_t ok = mbar_test(cur + S_REST, par);
              TX(4 * S1 - EARLY, 4 * S1);
              M(0, MF);
              mbar_wait_unless(ok, cur + S_REST, par);
            } else {
              TX(0, 4 * S1);
              mbar_wait(cur + S_REST, par);
            }
            LOGT(2);
            mma_fence();
            c1_acc<DOFF + 64 * NA>(y, we, d1);
            TX(4 * S1, 4 * (S1 + SB));
            if (__builtin_expect(zr != 0, 0)) {
              __nanosleep(zr);
#pragma unroll
              for (int i = 4 * (S1 + SB); i < 4 * NA; i++) asm volatile("mov.b32 %0, %1;" : "=f"(x[i]) : "r"(ln));
            }
            if (BQE) { mma_wait<1>(bz); make_bq(bz); }
            TX(4 * (S1 + SB), 4 * NA);
          } else {
            c1_acc<DOFF + 64 * NA>(y, we, d1);
            mma_wait<1>(x);
            cbias<DOFF + S_TGT / 16>(bz, wbc, d1);
            tanh_groups(x, 0, NA);
          }
          constexpr bool GE = G0 && 2 * E0 <= NA && N8 < KV;
          constexpr int MX = N8 >= KV ? NA - 1 : GE ? 2 * E0 : NA - 1 < 2 * E0 ? NA - 1 : 2 * E0;
          M(MF, MX);
          asm volatile("{\n.reg .b32 lo, hi;\nmov.b64 {lo, hi}, %0;\nadd.u32 hi, hi, %1;\nmov.b64 %0, {lo, hi};\n}\n" : "+l"(d1) : "n"(DESC_HALVES - DESC_ROWS));
          auto after = [&](uint32_t g) {
            asm volatile("{\n.reg .b32 lo, hi, z;\n.reg .pred p;\nand.b32 z, %1, %2;\nsetp.ne.u32 p, z, 0;\nvote.sync.ballot.b32 z, p, 0xffffffff;\n"
                         "mov.b64 {lo, hi}, %0;\nadd.u32 " GATE_HALF ", z;\nmov.b64 %0, {lo, hi};\n}\n" : "+l"(d1) : "r"(g), "r"(zr));
          };
          auto any = [&](auto& v, int n) { return v[n - 2] | v[n - 4] | (n > 4 ? v[n - 6] : 0) | (n > 4 && GW4 ? v[n - 8] : 0); };
          if (GE) {
            c2_first<DOFF>(o, a, d1, meta);
            mma_wait<1>(y);
            if (WP == 0) make_weff(cur + S_TGT);
          } else {
            if (__builtin_expect(zr != 0, 0)) {
              __nanosleep(zr);
#pragma unroll
              for (int i = 2 * MF; i < 2 * MX; i += 2) sts32(zr + i, a[i]);
#pragma unroll
              for (int i = 4 * MX; i < 4 * NA; i++) sts32(zr + i, __float_as_uint(x[i]));
            }
            mma_wait<SPLIT ? 0 : 1>(y);
            T(4 * (2 * E0 - NA));
            if (WP == 0) make_weff(cur + S_TGT);
            M(MX, 2 * E0);
            if (GA & 1) after(any(a, 4 * E0));
            c2_first<DOFF>(o, a, d1, meta);
          }
          if (WP == 1) make_weff(cur + S_TGT);
          if constexpr (E1 > E0) {
            T(4 * (2 * E1 - NA));
            M(2 * E0, 2 * E1);
            if (GA & 2) after(any(a1, 4 * (E1 - E0)));
            c2_more<DOFF + 128 * E0>(o, a1, d1, meta);
          }
          if (WP == 2) make_weff(cur + S_TGT);
          if constexpr (E2 > E1) {
            T(4 * (2 * E2 - NA));
            M(2 * E1, 2 * E2);
            if (GA & 4) after(any(a2, 4 * (E2 - E1)));
            c2_more<DOFF + 128 * E1>(o, a2, d1, meta);
          }
          if (TP) {
            T(4 * (NY - TP));
            M(2 * E2, N8 - TP - 1);
            if (__builtin_expect(zr != 0, 0)) {
              __nanosleep(zr);
#pragma unroll
              for (int i = 0; i < 16; i++) sts32(zr + i, we[i]);
#pragma unroll
              for (int i = 2 * E2; i < N8 - TP - 1; i++) { sts32(zr + i, a3[2 * i - 4 * E2]); asm volatile("mov.b32 %0, %1;" : "=r"(a3[2 * i - 4 * E2 + 1]) : "r"(ln)); }
#pragma unroll
              for (int i = 4 * (NY - TP - 1); i < 4 * (NY - TP); i++) sts32(zr + i, __float_as_uint(y[i]));
#pragma unroll
              for (int i = 4 * (NY - TP); i < 4 * NY; i++) asm volatile("mov.b32 %0, %1;" : "=f"(y[i]) : "r"(ln));
            }
            T(4 * NY);
            M(N8 - TP - 1, 2 * KT);
          } else {
          T(4 * NY);
          M(2 * E2, 2 * KT);
          }
          c2_more<DOFF + 128 * E2>(o, a3, d1, meta);
          if (!(SPLIT && BQE)) {
          mma_wait<2 + (E1 > E0) + (E2 > E1)>(bz);
          make_bq(bz);
          }
          raw = lds32(sa + S_HDR);
          if (LC) raw = (raw >> 31) == phase ? 0 : raw;
          if (EA) full = mbar_test(sa + S_FULL, phase);
          mma_wait<0>(o);
#pragma unroll
          for (int j = 0; j < 4; j++)
            sts128(cur + S_OUT + j * 512 + ost,
                   make_uint4(__float_as_uint(o[4 * j]), __float_as_uint(o[4 * j + 1]), __float_as_uint(o[4 * j + 2]), __float_as_uint(o[4 * j + 3])));
          if (LC) {
            LOGT(1);
            __syncwarp();
            asm volatile("{\n.reg .pred p;\nsetp.eq.u32 p, %1, 0;\n@p mbarrier.arrive.shared::cta.b64 _, [%0];\n}\n"
                         :: "r"(cur + S_EMPTY), "r"(ln | (hdr & H_SELF)) : "memory");
          }
        };
        if (hdr & 0x2000) { chunk(Int<13>()); if (hdr & H_FINAL) break; }
        else if (hdr & (V11 ? 0x1000 : 0x1fff)) { chunk(Int<12>()); if (hdr & H_FINAL) break; }
        else if (hdr & 0x4000) { chunk(Int<14>()); if (hdr & H_FINAL) break; }
        else if (V15 && (hdr & 0x8000)) { chunk(Int<15>()); if (hdr & H_FINAL) break; }
        else if (V11 && (hdr & 0xfff)) { chunk(Int<11>()); if (hdr & H_FINAL) break; }
        else if (hdr) { chunk(Int<16>()); if (hdr & H_FINAL) break; }
        else {
          uint32_t spins = 0;
          do {
            if (++spins > 0x1000000) __trap();
            __nanosleep(32);
            raw = lds32(sa + S_HDR);
          } while ((raw >> 31) == phase);
        }
        continue;
        LOGT(1);
        if (hdr & H_FINAL) break;
        __syncwarp();
        if (ln == 0) mbar_arrive(cur + S_EMPTY);
        for (uint32_t spins = 0; (raw >> 31) == phase; spins++) {
          if (spins > 0x1000000) __trap();
          __nanosleep(32);
          raw = lds32(sa + S_HDR);
        }
      }
      }
      asm volatile("bar.sync %0, 128;" :: "r"(2 + wg) : "memory");
      const uint32_t ra = cur + S_OUT + w * 512 + ln * 4;
      float v[16];
#pragma unroll
      for (int i = 0; i < 16; i++) v[i] = __uint_as_float(lds32(ra + (i >> 2) * 2048 + (i & 3) * 128));
      __nv_bfloat16* dst = out + (lds32(cur + S_ROW + (hdr >> 31) * 4) * kD + 8 * w + ((ln >> 1) & 6) + (ln & 1) + (ln & 2) * 16);
#pragma unroll
      for (int k = 1; k < 16; k *= 2)
#pragma unroll
        for (int i = 0; i < 16; i += 2 * k) v[i] += v[i + k];
      v[0] += __shfl_xor_sync(0xffffffffu, v[0], 16);
      asm volatile("{\n.reg .pred p;\nsetp.lt.u32 p, %2, %3;\n@p st.global.u16 [%0], %1;\n}\n"
                   :: "l"(dst), "h"(__bfloat16_as_ushort(__float2bfloat16(v[0]))), "r"(ln), "r"(hdr & H_SELF ? 16 : 0) : "memory");
      if (!LC && !(hdr & H_SELF) && ln == 0) mbar_arrive(cur + S_EMPTY);
      }
    }
    STAMP(4);
  } else {
    const int pw = warp - NCW * 4;
    const uint32_t ring = sb + pw * RING_BYTES;
    asm volatile("setmaxnreg.dec.sync.aligned.u32 %0;" :: "n"(PROD_REGS));
    if (pw < NCW) {
      int b = pw * grid + blockIdx.x, bn = b + bstep;
      uint4 mw = load_mask(mask, min(b, B - 1), min(lane, 24));
      if (lane == 0) {
#pragma unroll
        for (int i = 0; i < NSLOT; i++) {
          mbar_init(ring + i * SLOT_BYTES + S_FULL, 33);
          mbar_init(ring + i * SLOT_BYTES + S_REST, 33);
          mbar_arrive(ring + i * SLOT_BYTES + S_REST);
          mbar_init(ring + i * SLOT_BYTES + S_EMPTY, 4);
          sts32(ring + i * SLOT_BYTES + S_HDR, 0);
        }
        sts32(ring + R_STOP, b < B && pw < ACT ? 0 : ring);
      }
      sts32(sb + R_PACE + lane * 4, 0);
      asm volatile("bar.arrive 1, %0;" :: "n"(NCW * 160) : "memory");
      asm volatile("bar.arrive 6, 128;" ::: "memory");
      if (pw >= ACT) return;
      const uint32_t list = ring + R_LIST;
      uint32_t lt;
      asm("mov.u32 %0, %%lanemask_lt;" : "=r"(lt));
      const uint32_t ln = __shfl_sync(0xffffffffu, lane, lane);
      const uint32_t r4 = (ln >> 3) * 4, c16 = (ln & 7) * 16, l25 = min(ln, 24u);
      const uint32_t pick = ln < 25 ? 0xeca8 : 0x9999;
      uint32_t dst[4];
#pragma unroll
      for (int i = 0; i < 4; i++) dst[i] = ring + (r4 + i) * 128 + (c16 ^ (((r4 + i) & 7) << 4));
      uint64_t pol;
      asm("createpolicy.fractional.L2::evict_first.b64 %0, 1.0;" : "=l"(pol));
      uint32_t sa = ring, phase = 1;
      const uint32_t wrap = (uint32_t)(max(B - NSTATIC * bstep, 0) + bstep - 1);
      auto next_slot = [&]() {
        const bool wrapped = sa == ring + (NSLOT - 1) * SLOT_BYTES;
        const int step = wrapped ? -(NSLOT - 1) * SLOT_BYTES : SLOT_BYTES;
        sa += step;
        phase ^= wrapped;
#pragma unroll
        for (int i = 0; i < 4; i++) dst[i] += step;
      };
      uint32_t claimer = ln;
      uint32_t drawn, started = 0;
      auto draw = [&]() {
        drawn = B;
        asm volatile("{\n.reg .pred p;\nsetp.eq.u32 p, %3, 0;\n@p atom.global.inc.u32 %0, [%1], %2;\n}\n"
                     : "+r"(drawn) : "l"(counter), "r"(wrap), "r"(claimer) : "memory");
      };
      if (b >= B) draw();
      while (b < B) {
        const uint32_t e0 = nonzero_as_one(mw.x), e1 = nonzero_as_one(mw.y);
        const uint32_t e2 = nonzero_as_one(mw.z), e3 = nonzero_as_one(mw.w);
        const uint32_t nonbin = (e0 ^ mw.x) | (e1 ^ mw.y) | (e2 ^ mw.z) | (e3 ^ mw.w);
        const uint32_t sA = prmt(e0, e1, pick), sB = prmt(e2, e3, pick);
        const uint32_t pA = (sA & 0x01010101u) * 0x01010101u;
        const uint32_t pB = ((sB & 0x01010101u) + (pA >> 24)) * 0x01010101u;
        uint32_t pos = 0;
        int n = 0;
#pragma unroll
        for (int k = 0; k < 4; k++) {
          const uint32_t bal = ballot_bit(pB, 0x01000000u << k);
          pos += __popc(bal & lt) << k;
          n += __popc(bal) << k;
        }
        const uint32_t general = __any_sync(0xffffffffu, nonbin != 0);
        const uint32_t aA = (pA + pos * 0x01010101u) | ~sA, aB = (pB + pos * 0x01010101u) | ~sB;
#pragma unroll
        for (int i = 0; i < 8; i++) sts8(list - 1 + prmt(i < 4 ? aA : aB, 0, 0x4440 + (i & 3)), 8 * ln + i);
        __syncwarp();

        const uint64_t src = reinterpret_cast<uint64_t>(hist) + (uint64_t)b * (kL * kD * 2);
        const bool no_carry = (uint32_t)src <= 0xffffffffu - kL * kD * 2;
        auto begin_fill = [&](uint32_t h, uint32_t part, int nc, int bt, auto extra) {
          LOGT(0);
          mbar_wait(sa + S_EMPTY, phase);
          if (bt >= B) {
            h |= H_FINAL;
            if (!part) { h |= H_SELF; sts32(ring + R_STOP, sa + (phase ^ 1)); }
          }
          extra();
          sts32(sa + S_HDR, h | phase << 31);
          sts32(sa + S_ROW + phase * 4, b | part);
          asm volatile("{\n.reg .pred p;\nsetp.eq.u32 p, %1, 0;\n@p mbarrier.arrive.shared::cta.b64 _, [%0];\n}\n"
                       :: "r"(sa + S_FULL), "r"(ln) : "memory");
          asm volatile("{\n.reg .u32 f, c;\n.reg .s32 d;\n.reg .pred p;\n"
                       "mov.u32 c, %%globaltimer_lo;\n"
                       "red.shared.max.u32 [%1], c;\n"
                       "atom.shared.add.u32 f, [%1], %2;\n"
                       "shfl.sync.idx.b32 f, f, 0, 31, 0xffffffff;\n"
                       "mov.u32 %0, f;\n"
                       "SPIN:\n"
                       "mov.u32 c, %%globaltimer_lo;\n"
                       "sub.s32 d, c, f;\n"
                       "setp.gt.u32 p, d, %3;\n"
                       "@p bra.uni SPIN;\n}\n" : "=r"(started) : "r"(sb + R_PACE + ln * 4), "r"(nc * (bn >= slow_from ? pace_slow : pace) >> 4), "r"(~(pace * (CHUNK / 4))) : "memory");
          if (!(part & ROW_REST)) {
            mw = load_mask(mask, min(bn, B - 1), l25);
            draw();
          }
          LOGT(1);
          asm volatile("cp.async.ca.shared.global [%0], [%1], 4;"
                       :: "r"(sa + S_TGT + ln * 4), "l"(reinterpret_cast<const uint32_t*>(target) + ((uint32_t)min(bt, B - 1) * 32u + ln)) : "memory");
        };
        auto end_fill = [&](int nc) {
          cp_async_arrive_noinc(sa + (SPLIT ? S_REST : S_FULL));
          next_slot();
          LOGT(2);
        };
        if (__builtin_expect(no_carry && !general, 1)) {
          int nc = n <= CHUNK ? n : n <= 160 ? 64 : 96;
          uint32_t la = list + r4, part = n <= CHUNK ? 0 : ROW_MORE;
#pragma unroll 1
          while (true) {
            uint32_t idx[7];
#pragma unroll
            for (int t = 0; t < 7; t++) idx[t] = lds32(la + t * 16);
            begin_fill(1u << ((nc + 7) >> 3), part, nc, part == ROW_MORE ? b : bn, [](){});
            const int left = nc - r4;
            const uint32_t base = (uint32_t)src + c16;
            uint64_t a[4];
            a[0] = a[1] = a[2] = a[3] = (uint64_t)((uint32_t)(src >> 32) + (ln >> 5)) << 32;
            if (__builtin_expect(nc >= 64, 1)) {
              cp_group<0>(dst, a, idx[0], base, pol);
              cp_group<1>(dst, a, idx[1], base, pol);
              if (NX > 4) cp_group<2>(dst, a, idx[2], base, pol);
              if (NX > 6) cp_group<3>(dst, a, idx[3], base, pol);
              if (SPLIT) cp_async_arrive_noinc(sa + S_FULL);
              asm volatile("{\n.reg .u32 c;\n.reg .s32 d;\n.reg .pred p;\n"
                           "SPIN:\n"
                           "mov.u32 c, %%globaltimer_lo;\n"
                           "sub.s32 d, c, %0;\n"
                           "setp.lt.u32 p, d, %1;\n"
                           "@p bra.uni SPIN;\n}\n" :: "r"(started), "r"(bn >= slow_from ? spread : 0) : "memory");
              if (NX <= 4) cp_group<2>(dst, a, idx[2], base, pol);
              if (NX <= 6) cp_group<3>(dst, a, idx[3], base, pol);
              cp_group_z<4>(dst, a, idx[4], base, left, pol);
              cp_group_z<5>(dst, a, idx[5], base, left, pol);
              if (nc > 96) {
                cp_group_z<6>(dst, a, idx[6], base, left, pol);
                if (nc > 112) cp_group_z<7>(dst, a, lds32(la + 112), base, left, pol);
              }
            } else {
              cp_group_z<0>(dst, a, idx[0], base, left, pol);
              cp_group_z<1>(dst, a, idx[1], base, left, pol);
              cp_group_z<2>(dst, a, idx[2], base, left, pol);
              cp_group_z<3>(dst, a, idx[3], base, left, pol);
              if (SPLIT) cp_async_arrive_noinc(sa + S_FULL);
              cp_group_z<4>(dst, a, 0, base, left, pol);
              cp_group_z<5>(dst, a, 0, base, left, pol);
            }
            end_fill(nc);
            if (part != ROW_MORE) break;
            la += nc;
            nc = n - nc;
            part = ROW_REST;
          }
        } else {
          int r0 = 0;
#pragma unroll 1
          do {
            const int nc = min(n - r0, CHUNK);
            const bool more = r0 + CHUNK < n;
            begin_fill(general ? H_GENERAL : 1u << ((nc + 7) >> 3), (more ? ROW_MORE : 0u) | (r0 ? ROW_REST : 0u), nc, more ? b : bn, [&]() {
#pragma unroll 1
              for (int z = ln; general && z < CHUNK; z += 32) {
                uint32_t v = 0;
                if (z < nc) {
                  uint32_t row;
                  asm volatile("ld.shared.u8 %0, [%1];" : "=r"(row) : "r"(list + r0 + z) : "memory");
                  v = __bfloat16_as_ushort(mask[(size_t)b * kL + row]);
                }
                sts16(sa + S_MASK + z * 2, v);
              }
              __syncwarp();
            });
#pragma unroll 1
            for (int z = r4 >> 2; z < CHUNK; z += 4) {
              uint32_t row;
              asm volatile("ld.shared.u8 %0, [%1];" : "=r"(row) : "r"(list + r0 + z) : "memory");
              asm volatile("cp.async.cg.shared.global [%0], [%1], 16, %2;"
                           :: "r"(sa + z * 128 + (c16 ^ ((z & 7) << 4))), "l"(src + c16 + (z < nc ? row : 0) * 128),
                              "r"(z < nc ? 16 : 0) : "memory");
            }
            if (SPLIT) cp_async_arrive_noinc(sa + S_FULL);
            end_fill(nc);
            r0 += CHUNK;
          } while (r0 < n);
        }
        b = bn;
        bn = __shfl_sync(0xffffffffu, drawn, 0) + NSTATIC * bstep;
        if (bn >= B) claimer = 1;
      }
      STAMP(3);
      if (lds32(ring + R_STOP) == 0) sts32(ring + R_STOP, sa + (phase ^ 1));
      asm volatile("cp.async.wait_all;" ::: "memory");
      STAMP(4);
    } else {
      uint32_t due = clock();
      int s0 = NSTATIC * bstep + (PF_EARLY * grid + blockIdx.x) * PF_ROWS;
      auto prefetch = [&]() {
        const int cnt = min(PF_ROWS, B - s0);
        if (lane == 0) {
          prefetch_l2(mask + (size_t)s0 * kL, cnt * kL * 2);
          prefetch_l2(target + (size_t)s0 * kD, cnt * kD * 2);
        }
        s0 += grid * PF_ROWS;
      };
#pragma unroll 1
      for (int j = PF_EARLY; j < PF_FAST && s0 < B; j++) {
        while ((int)(due - (uint32_t)clock()) > 0) {}
        prefetch();
        due += PF_CYCLES;
      }
      due += (PF_FAST - 1) * PF_SLOW - (PF_FAST - PF_EARLY) * PF_CYCLES + (blockIdx.x & 255) * (PF_SLOW / 256);
      asm volatile("bar.sync 6, 128;" ::: "memory");
      const uint32_t ln = __shfl_sync(0xffffffffu, lane, lane);
      const uint32_t home = sb + min(ln, NCW - 1u) * RING_BYTES;
      uint32_t mine = ln < NCW ? home : 0;
      const uint32_t rd = __shfl_sync(0xffffffffu, S_OUT + (lane >> 3) * 512 + (lane & 7) * 16, lane);
      const uint32_t word = __shfl_sync(0xffffffffu, (lane & 4) * 4 + (lane >> 3) * 4 + (lane & 3), lane);
      uint32_t idle = 0, turn = 0;
      auto poll = [&]() {
        uint32_t ok;
        asm volatile("{\n.reg .pred p;\nsetp.ne.u32 p, %3, 0;\n@p mbarrier.test_wait.parity.shared::cta.b64 p, [%1], %2;\n"
                     "vote.sync.ballot.b32 %0, p, 0xffffffff;\n}\n"
                     : "=r"(ok) : "r"((mine & ~1u) + S_EMPTY), "r"(mine & 1), "r"(mine) : "memory");
        return ok;
      };
      uint32_t ready = 0;
#pragma unroll 1
      while (true) {
        if (ready) {
          const uint32_t behind = ready & ~turn;
          const uint32_t r = __ffs(behind ? behind : ready) - 1;
          turn = (2u << r) - 1;
          const uint32_t at = __shfl_sync(0xffffffffu, mine, r), sa = at & ~1u;
          const uint32_t row = lds32(sa + S_ROW + 4 - (at & 1) * 4);
          if (ln == r) mine = sa == home + (NSLOT - 1) * SLOT_BYTES ? (at - (NSLOT - 1) * SLOT_BYTES) ^ 1 : at + SLOT_BYTES;
          float v[4];
#pragma unroll
          for (int i = 0; i < 2; i++) {
            uint4 u[8];
#pragma unroll
            for (int k = 0; k < 8; k++)
              u[k] = lds128(sa + rd + i * 4096 + (k >> 2) * 2048 + (k & 3) * 128);
#define DIN_SUM8(m) (((__uint_as_float(u[0].m) + __uint_as_float(u[1].m)) + (__uint_as_float(u[2].m) + __uint_as_float(u[3].m))) + \
                     ((__uint_as_float(u[4].m) + __uint_as_float(u[5].m)) + (__uint_as_float(u[6].m) + __uint_as_float(u[7].m))))
            v[0] = i ? v[0] + DIN_SUM8(x) : DIN_SUM8(x);
            v[1] = i ? v[1] + DIN_SUM8(y) : DIN_SUM8(y);
            v[2] = i ? v[2] + DIN_SUM8(z) : DIN_SUM8(z);
            v[3] = i ? v[3] + DIN_SUM8(w) : DIN_SUM8(w);
          }
          ready = poll();
          asm volatile("{\n.reg .pred p;\nsetp.eq.u32 p, %1, 0;\n@p mbarrier.arrive.shared::cta.b64 _, [%0];\n}\n"
                       :: "r"(sa + S_REST), "r"(ln) : "memory");
          const bool hi = ln & 4;
          float e0 = (hi ? v[2] : v[0]) + __shfl_xor_sync(0xffffffffu, hi ? v[0] : v[2], 4);
          float e1 = (hi ? v[3] : v[1]) + __shfl_xor_sync(0xffffffffu, hi ? v[1] : v[3], 4);
          const uint32_t carry = sb + r * RING_BYTES + R_CARRY + ln * 8;
          asm volatile("{\n.reg .pred p, q;\n.reg .f32 a, b;\n.reg .u32 t;\nshr.u32 t, %3, 30;\nsetp.eq.u32 p, t, 1;\nsetp.eq.u32 q, t, 2;\n"
                       "@p ld.shared.v2.f32 {a, b}, [%2];\n@p add.f32 %0, %0, a;\n@p add.f32 %1, %1, b;\n@q st.shared.v2.f32 [%2], {%0, %1};\n}\n"
                       : "+f"(e0), "+f"(e1) : "r"(carry), "r"(row) : "memory");
          asm volatile("{\n.reg .pred p;\nsetp.ge.s32 p, %2, 0;\n@p st.global.u32 [%0], %1;\n}\n"
                       :: "l"(reinterpret_cast<uint32_t*>(out) + (row * 32u + word)), "r"(pack_bf16(e0, e1)), "r"(row) : "memory");
          idle = 0;
        } else {
          if (lds32(home + R_STOP) == mine) mine = 0;
          if (!__any_sync(0xffffffffu, mine)) break;
          if (++idle > 0x4000000) __trap();
          if (s0 < B && (int)(due - (uint32_t)clock()) <= 0) { prefetch(); due += PF_SLOW; }
          __nanosleep(RED_SLEEP);
          ready = poll();
        }
      }
      STAMP(4);
    }
  }
}

}

extern "C" void kernel_launch(void* const* d_in, const int* in_sizes, int n_in, void* d_out, int out_size) {
  const __nv_bfloat16* target = (const __nv_bfloat16*)d_in[0];
  const __nv_bfloat16* hist = (const __nv_bfloat16*)d_in[1];
  const __nv_bfloat16* mask = (const __nv_bfloat16*)d_in[2];
  const __nv_bfloat16* w1 = (const __nv_bfloat16*)d_in[3];
  const __nv_bfloat16* b1 = (const __nv_bfloat16*)d_in[4];
  const __nv_bfloat16* w2 = (const __nv_bfloat16*)d_in[5];
  const __nv_bfloat16* b2 = (const __nv_bfloat16*)d_in[6];
  const int B = in_sizes[0] / din::kD;
  if (B <= 0) return;
  static int sms = 0, pace = 0;
  static unsigned int* counter = nullptr;
  if (sms == 0) {
    int dev = 0, khz = 0, bits = 0;
    cudaGetDevice(&dev);
    cudaDeviceGetAttribute(&sms, cudaDevAttrMultiProcessorCount, dev);
    cudaDeviceGetAttribute(&khz, cudaDevAttrMemoryClockRate, dev);
    cudaDeviceGetAttribute(&bits, cudaDevAttrGlobalMemoryBusWidth, dev);
    if (khz > 0 && bits > 0) pace = (int)(16.0 * 128.0 * sms / (khz * 1e-6 * 2.0 * bits / 8.0));
    if (pace > 256) pace = 0;
    cudaGetSymbolAddress((void**)&counter, din::g_next);
    cudaFuncSetAttribute(din::din_kernel, cudaFuncAttributeMaxDynamicSharedMemorySize, din::SMEM_BYTES);
  }
  const long long early = (long long)(din::NSTATIC * NCW + PF_EARLY * PF_ROWS) * sms, line = 128LL * sms;
  long long pf_mask = (early * din::kL * 2 + line - 1) / line, pf_tgt = early * din::kD * 2 / line;
  if (pf_mask > (long long)B * din::kL * 2 / line) pf_mask = (long long)B * din::kL * 2 / line;
  if (pf_tgt > (long long)B * din::kD * 2 / line) pf_tgt = (long long)B * din::kD * 2 / line;
  din::din_kernel<<<sms, din::NTHREADS, din::SMEM_BYTES>>>(mask, target, B, sms, (uint32_t)pf_mask * 128, (uint32_t)pf_tgt * 128,
                                                          w1, hist, b1, w2, b2, (__nv_bfloat16*)d_out, counter, pace,
                                                          B - SLOW_ROUNDS * NCW * sms / 2, pace + (pace * SLOW_BY + 40) / 80,
                                                          pace * SPREAD / 16);
}
```

```cpp
#include <cuda_runtime.h>
#include <cuda_bf16.h>
#include <stdint.h>

namespace din {

constexpr int kL = 200, kD = 64;
#define NCW 3
#define NSLOT 3
constexpr int CHUNK = 128;
constexpr int NTHREADS = NCW * 128 + 128;
#define PREGS 56
#define CREGS 152
constexpr int PROD_REGS = PREGS, CONS_REGS = CREGS;
#define PF_ROWS 8
#define PF_FAST 10
#define PF_SLOW 2000
#define PF_CYCLES 280
#define RED_SLEEP 0
#define K_SEL 0
#define K_FIRST 0
#define K_LAST 0
#define K_LO 1
#define K_HI1 1
#define K_HI2 1
#define K_ADV 0
#define KL 2
#define KM 0
#define GA 1
#define GW4 1
#define SPLIT 1
#define SA 2
#define SB 1
#define EARLY 4
#define PIN2 1
#define SPREAD 80
#define SPREAD_UP 600
#define DOFF 0
#define BQE 0
#define TP 0
#define LC 1
#define EA 1
#define V11 0
#define V15 1
#define KV 16
#define WARM 0
#define G0 0
#define ME 0
#define PK 2
#define RC 8
#define RO 1
#define K0 3
#define WP 0
#define GATE_HALF "hi, hi"
#define SLOW_ROUNDS 12
#define SLOW_BY 9
#define PF_EARLY 3
constexpr int NSTATIC = 2;
constexpr int S_TGT = CHUNK * 128;
constexpr int S_HDR = S_TGT + 128;
constexpr int S_FULL = S_HDR + 8;
constexpr int S_EMPTY = S_HDR + 16;
constexpr int S_ROW = S_HDR + 24;
constexpr int S_REST = S_HDR + 32;
constexpr int S_MASK = S_TGT + 256;
constexpr int S_OUT = S_TGT + 1024;
constexpr int SLOT_BYTES = S_OUT + 8192;
constexpr int RING_BYTES_ = NSLOT * SLOT_BYTES;
constexpr int R_PACE = 2 * RING_BYTES_ + S_TGT + 768;
constexpr int R_STOP = S_HDR + 44;
constexpr int R_LIST = S_TGT + 512;
constexpr int R_VEC = S_TGT + 768;
constexpr int R_SEL = S_TGT + 896;
constexpr int R_CARRY = SLOT_BYTES + S_TGT + 512;
constexpr int R_TGT0 = (NSLOT - 1) * SLOT_BYTES + S_OUT;
constexpr int RING_BYTES = NSLOT * SLOT_BYTES;
constexpr int SMEM_BYTES = NCW * RING_BYTES + 1024;
__device__ constexpr int w1_at(int i) { return (i >> 1) * RING_BYTES + (i & 1) * SLOT_BYTES + S_OUT; }
#define LOGT(slot)
static_assert(SMEM_BYTES <= 232448, "shared memory");
constexpr uint32_t H_GENERAL = 1u << 17, H_FINAL = 1u << 18, H_SELF = 1u << 19;
constexpr uint32_t ROW_REST = 1u << 30, ROW_MORE = 1u << 31;

__device__ unsigned int g_next;

#define STAMP(k)

#define DURT(sign)
#define STR2(x) #x
#define STR(x) STR2(x)
constexpr int NX = 5;
__device__ __forceinline__ void sel_clr(float (&d)[20], const uint32_t (&a)[4], uint32_t lo, uint32_t hi) {
  asm volatile("{\n.reg .b64 db;\n.reg .b32 lo, hi;\n"
    "mov.b32 hi, %25;\n"
    "add.u32 lo, %24, 0;\nmov.b64 db, {lo, hi};\n"
    "wgmma.mma_async.sync.aligned.m64n40k16.f32.bf16.bf16 {%0, %1, %2, %3, %4, %5, %6, %7, %8, %9, %10, %11, %12, %13, %14, %15, %16, %17, %18, %19}, {%20, %21, %22, %23}, db, 0, 1, 1, 0;\n"
    "}\n"
    : "=f"(d[0]), "=f"(d[1]), "=f"(d[2]), "=f"(d[3]), "=f"(d[4]), "=f"(d[5]), "=f"(d[6]), "=f"(d[7]), "=f"(d[8]), "=f"(d[9]), "=f"(d[10]), "=f"(d[11]), "=f"(d[12]), "=f"(d[13]), "=f"(d[14]), "=f"(d[15]), "=f"(d[16]), "=f"(d[17]), "=f"(d[18]), "=f"(d[19])
    : "r"(a[0]), "r"(a[1]), "r"(a[2]), "r"(a[3]), "r"(lo), "r"(hi)
    : "memory");
}
__device__ __forceinline__ void sel_clr(float (&d)[24], const uint32_t (&a)[4], uint32_t lo, uint32_t hi) {
  asm volatile("{\n.reg .b64 db;\n.reg .b32 lo, hi;\n"
    "mov.b32 hi, %29;\n"
    "add.u32 lo, %28, 0;\nmov.b64 db, {lo, hi};\n"
    "wgmma.mma_async.sync.aligned.m64n48k16.f32.bf16.bf16 {%0, %1, %2, %3, %4, %5, %6, %7, %8, %9, %10, %11, %12, %13, %14, %15, %16, %17, %18, %19, %20, %21, %22, %23}, {%24, %25, %26, %27}, db, 0, 1, 1, 0;\n"
    "}\n"
    : "=f"(d[0]), "=f"(d[1]), "=f"(d[2]), "=f"(d[3]), "=f"(d[4]), "=f"(d[5]), "=f"(d[6]), "=f"(d[7]), "=f"(d[8]), "=f"(d[9]), "=f"(d[10]), "=f"(d[11]), "=f"(d[12]), "=f"(d[13]), "=f"(d[14]), "=f"(d[15]), "=f"(d[16]), "=f"(d[17]), "=f"(d[18]), "=f"(d[19]), "=f"(d[20]), "=f"(d[21]), "=f"(d[22]), "=f"(d[23])
    : "r"(a[0]), "r"(a[1]), "r"(a[2]), "r"(a[3]), "r"(lo), "r"(hi)
    : "memory");
}
__device__ __forceinline__ void sel_clr(float (&d)[28], const uint32_t (&a)[4], uint32_t lo, uint32_t hi) {
  asm volatile("{\n.reg .b64 db;\n.reg .b32 lo, hi;\n"
    "mov.b32 hi, %33;\n"
    "add.u32 lo, %32, 0;\nmov.b64 db, {lo, hi};\n"
    "wgmma.mma_async.sync.aligned.m64n56k16.f32.bf16.bf16 {%0, %1, %2, %3, %4, %5, %6, %7, %8, %9, %10, %11, %12, %13, %14, %15, %16, %17, %18, %19, %20, %21, %22, %23, %24, %25, %26, %27}, {%28, %29, %30, %31}, db, 0, 1, 1, 0;\n"
    "}\n"
    : "=f"(d[0]), "=f"(d[1]), "=f"(d[2]), "=f"(d[3]), "=f"(d[4]), "=f"(d[5]), "=f"(d[6]), "=f"(d[7]), "=f"(d[8]), "=f"(d[9]), "=f"(d[10]), "=f"(d[11]), "=f"(d[12]), "=f"(d[13]), "=f"(d[14]), "=f"(d[15]), "=f"(d[16]), "=f"(d[17]), "=f"(d[18]), "=f"(d[19]), "=f"(d[20]), "=f"(d[21]), "=f"(d[22]), "=f"(d[23]), "=f"(d[24]), "=f"(d[25]), "=f"(d[26]), "=f"(d[27])
    : "r"(a[0]), "r"(a[1]), "r"(a[2]), "r"(a[3]), "r"(lo), "r"(hi)
    : "memory");
}
__device__ __forceinline__ void sel_clr(float (&d)[32], const uint32_t (&a)[4], uint32_t lo, uint32_t hi) {
  asm volatile("{\n.reg .b64 db;\n.reg .b32 lo, hi;\n"
    "mov.b32 hi, %37;\n"
    "add.u32 lo, %36, 0;\nmov.b64 db, {lo, hi};\n"
    "wgmma.mma_async.sync.aligned.m64n64k16.f32.bf16.bf16 {%0, %1, %2, %3, %4, %5, %6, %7, %8, %9, %10, %11, %12, %13, %14, %15, %16, %17, %18, %19, %20, %21, %22, %23, %24, %25, %26, %27, %28, %29, %30, %31}, {%32, %33, %34, %35}, db, 0, 1, 1, 0;\n"
    "}\n"
    : "=f"(d[0]), "=f"(d[1]), "=f"(d[2]), "=f"(d[3]), "=f"(d[4]), "=f"(d[5]), "=f"(d[6]), "=f"(d[7]), "=f"(d[8]), "=f"(d[9]), "=f"(d[10]), "=f"(d[11]), "=f"(d[12]), "=f"(d[13]), "=f"(d[14]), "=f"(d[15]), "=f"(d[16]), "=f"(d[17]), "=f"(d[18]), "=f"(d[19]), "=f"(d[20]), "=f"(d[21]), "=f"(d[22]), "=f"(d[23]), "=f"(d[24]), "=f"(d[25]), "=f"(d[26]), "=f"(d[27]), "=f"(d[28]), "=f"(d[29]), "=f"(d[30]), "=f"(d[31])
    : "r"(a[0]), "r"(a[1]), "r"(a[2]), "r"(a[3]), "r"(lo), "r"(hi)
    : "memory");
}
__device__ __forceinline__ void sel_clr(float (&d)[36], const uint32_t (&a)[4], uint32_t lo, uint32_t hi) {
  asm volatile("{\n.reg .b64 db;\n.reg .b32 lo, hi;\n"
    "mov.b32 hi, %41;\n"
    "add.u32 lo, %40, 0;\nmov.b64 db, {lo, hi};\n"
    "wgmma.mma_async.sync.aligned.m64n72k16.f32.bf16.bf16 {%0, %1, %2, %3, %4, %5, %6, %7, %8, %9, %10, %11, %12, %13, %14, %15, %16, %17, %18, %19, %20, %21, %22, %23, %24, %25, %26, %27, %28, %29, %30, %31, %32, %33, %34, %35}, {%36, %37, %38, %39}, db, 0, 1, 1, 0;\n"
    "}\n"
    : "=f"(d[0]), "=f"(d[1]), "=f"(d[2]), "=f"(d[3]), "=f"(d[4]), "=f"(d[5]), "=f"(d[6]), "=f"(d[7]), "=f"(d[8]), "=f"(d[9]), "=f"(d[10]), "=f"(d[11]), "=f"(d[12]), "=f"(d[13]), "=f"(d[14]), "=f"(d[15]), "=f"(d[16]), "=f"(d[17]), "=f"(d[18]), "=f"(d[19]), "=f"(d[20]), "=f"(d[21]), "=f"(d[22]), "=f"(d[23]), "=f"(d[24]), "=f"(d[25]), "=f"(d[26]), "=f"(d[27]), "=f"(d[28]), "=f"(d[29]), "=f"(d[30]), "=f"(d[31]), "=f"(d[32]), "=f"(d[33]), "=f"(d[34]), "=f"(d[35])
    : "r"(a[0]), "r"(a[1]), "r"(a[2]), "r"(a[3]), "r"(lo), "r"(hi)
    : "memory");
}
__device__ __forceinline__ void sel_clr(float (&d)[40], const uint32_t (&a)[4], uint32_t lo, uint32_t hi) {
  asm volatile("{\n.reg .b64 db;\n.reg .b32 lo, hi;\n"
    "mov.b32 hi, %45;\n"
    "add.u32 lo, %44, 0;\nmov.b64 db, {lo, hi};\n"
    "wgmma.mma_async.sync.aligned.m64n80k16.f32.bf16.bf16 {%0, %1, %2, %3, %4, %5, %6, %7, %8, %9, %10, %11, %12, %13, %14, %15, %16, %17, %18, %19, %20, %21, %22, %23, %24, %25, %26, %27, %28, %29, %30, %31, %32, %33, %34, %35, %36, %37, %38, %39}, {%40, %41, %42, %43}, db, 0, 1, 1, 0;\n"
    "}\n"
    : "=f"(d[0]), "=f"(d[1]), "=f"(d[2]), "=f"(d[3]), "=f"(d[4]), "=f"(d[5]), "=f"(d[6]), "=f"(d[7]), "=f"(d[8]), "=f"(d[9]), "=f"(d[10]), "=f"(d[11]), "=f"(d[12]), "=f"(d[13]), "=f"(d[14]), "=f"(d[15]), "=f"(d[16]), "=f"(d[17]), "=f"(d[18]), "=f"(d[19]), "=f"(d[20]), "=f"(d[21]), "=f"(d[22]), "=f"(d[23]), "=f"(d[24]), "=f"(d[25]), "=f"(d[26]), "=f"(d[27]), "=f"(d[28]), "=f"(d[29]), "=f"(d[30]), "=f"(d[31]), "=f"(d[32]), "=f"(d[33]), "=f"(d[34]), "=f"(d[35]), "=f"(d[36]), "=f"(d[37]), "=f"(d[38]), "=f"(d[39])
    : "r"(a[0]), "r"(a[1]), "r"(a[2]), "r"(a[3]), "r"(lo), "r"(hi)
    : "memory");
}
__device__ __forceinline__ void sel_clr(float (&d)[44], const uint32_t (&a)[4], uint32_t lo, uint32_t hi) {
  asm volatile("{\n.reg .b64 db;\n.reg .b32 lo, hi;\n"
    "mov.b32 hi, %49;\n"
    "add.u32 lo, %48, 0;\nmov.b64 db, {lo, hi};\n"
    "wgmma.mma_async.sync.aligned.m64n88k16.f32.bf16.bf16 {%0, %1, %2, %3, %4, %5, %6, %7, %8, %9, %10, %11, %12, %13, %14, %15, %16, %17, %18, %19, %20, %21, %22, %23, %24, %25, %26, %27, %28, %29, %30, %31, %32, %33, %34, %35, %36, %37, %38, %39, %40, %41, %42, %43}, {%44, %45, %46, %47}, db, 0, 1, 1, 0;\n"
    "}\n"
    : "=f"(d[0]), "=f"(d[1]), "=f"(d[2]), "=f"(d[3]), "=f"(d[4]), "=f"(d[5]), "=f"(d[6]), "=f"(d[7]), "=f"(d[8]), "=f"(d[9]), "=f"(d[10]), "=f"(d[11]), "=f"(d[12]), "=f"(d[13]), "=f"(d[14]), "=f"(d[15]), "=f"(d[16]), "=f"(d[17]), "=f"(d[18]), "=f"(d[19]), "=f"(d[20]), "=f"(d[21]), "=f"(d[22]), "=f"(d[23]), "=f"(d[24]), "=f"(d[25]), "=f"(d[26]), "=f"(d[27]), "=f"(d[28]), "=f"(d[29]), "=f"(d[30]), "=f"(d[31]), "=f"(d[32]), "=f"(d[33]), "=f"(d[34]), "=f"(d[35]), "=f"(d[36]), "=f"(d[37]), "=f"(d[38]), "=f"(d[39]), "=f"(d[40]), "=f"(d[41]), "=f"(d[42]), "=f"(d[43])
    : "r"(a[0]), "r"(a[1]), "r"(a[2]), "r"(a[3]), "r"(lo), "r"(hi)
    : "memory");
}
template<int D> __device__ __forceinline__ void c1_acc(float (&d)[20], const uint32_t (&a)[16], uint64_t db) {
  asm volatile("{\n.reg .b64 db;\n"
    "add.s64 db, %36, %37 + 0;\n"
    "wgmma.mma_async.sync.aligned.m64n40k16.f32.bf16.bf16 {%0, %1, %2, %3, %4, %5, %6, %7, %8, %9, %10, %11, %12, %13, %14, %15, %16, %17, %18, %19}, {%20, %21, %22, %23}, db, 1, 1, 1, 0;\n"
    "add.s64 db, %36, %37 + 2;\n"
    "wgmma.mma_async.sync.aligned.m64n40k16.f32.bf16.bf16 {%0, %1, %2, %3, %4, %5, %6, %7, %8, %9, %10, %11, %12, %13, %14, %15, %16, %17, %18, %19}, {%24, %25, %26, %27}, db, 1, 1, 1, 0;\n"
    "add.s64 db, %36, %37 + 4;\n"
    "wgmma.mma_async.sync.aligned.m64n40k16.f32.bf16.bf16 {%0, %1, %2, %3, %4, %5, %6, %7, %8, %9, %10, %11, %12, %13, %14, %15, %16, %17, %18, %19}, {%28, %29, %30, %31}, db, 1, 1, 1, 0;\n"
    "add.s64 db, %36, %37 + 6;\n"
    "wgmma.mma_async.sync.aligned.m64n40k16.f32.bf16.bf16 {%0, %1, %2, %3, %4, %5, %6, %7, %8, %9, %10, %11, %12, %13, %14, %15, %16, %17, %18, %19}, {%32, %33, %34, %35}, db, 1, 1, 1, 0;\n"
    "wgmma.commit_group.sync.aligned;\n}\n"
    : "+f"(d[0]), "+f"(d[1]), "+f"(d[2]), "+f"(d[3]), "+f"(d[4]), "+f"(d[5]), "+f"(d[6]), "+f"(d[7]), "+f"(d[8]), "+f"(d[9]), "+f"(d[10]), "+f"(d[11]), "+f"(d[12]), "+f"(d[13]), "+f"(d[14]), "+f"(d[15]), "+f"(d[16]), "+f"(d[17]), "+f"(d[18]), "+f"(d[19])
    : "r"(a[0]), "r"(a[1]), "r"(a[2]), "r"(a[3]), "r"(a[4]), "r"(a[5]), "r"(a[6]), "r"(a[7]), "r"(a[8]), "r"(a[9]), "r"(a[10]), "r"(a[11]), "r"(a[12]), "r"(a[13]), "r"(a[14]), "r"(a[15]), "l"(db), "n"(D)
    : "memory");
}
template<int D> __device__ __forceinline__ void c1_acc(float (&d)[24], const uint32_t (&a)[16], uint64_t db) {
  asm volatile("{\n.reg .b64 db;\n"
    "add.s64 db, %40, %41 + 0;\n"
    "wgmma.mma_async.sync.aligned.m64n48k16.f32.bf16.bf16 {%0, %1, %2, %3, %4, %5, %6, %7, %8, %9, %10, %11, %12, %13, %14, %15, %16, %17, %18, %19, %20, %21, %22, %23}, {%24, %25, %26, %27}, db, 1, 1, 1, 0;\n"
    "add.s64 db, %40, %41 + 2;\n"
    "wgmma.mma_async.sync.aligned.m64n48k16.f32.bf16.bf16 {%0, %1, %2, %3, %4, %5, %6, %7, %8, %9, %10, %11, %12, %13, %14, %15, %16, %17, %18, %19, %20, %21, %22, %23}, {%28, %29, %30, %31}, db, 1, 1, 1, 0;\n"
    "add.s64 db, %40, %41 + 4;\n"
    "wgmma.mma_async.sync.aligned.m64n48k16.f32.bf16.bf16 {%0, %1, %2, %3, %4, %5, %6, %7, %8, %9, %10, %11, %12, %13, %14, %15, %16, %17, %18, %19, %20, %21, %22, %23}, {%32, %33, %34, %35}, db, 1, 1, 1, 0;\n"
    "add.s64 db, %40, %41 + 6;\n"
    "wgmma.mma_async.sync.aligned.m64n48k16.f32.bf16.bf16 {%0, %1, %2, %3, %4, %5, %6, %7, %8, %9, %10, %11, %12, %13, %14, %15, %16, %17, %18, %19, %20, %21, %22, %23}, {%36, %37, %38, %39}, db, 1, 1, 1, 0;\n"
    "wgmma.commit_group.sync.aligned;\n}\n"
    : "+f"(d[0]), "+f"(d[1]), "+f"(d[2]), "+f"(d[3]), "+f"(d[4]), "+f"(d[5]), "+f"(d[6]), "+f"(d[7]), "+f"(d[8]), "+f"(d[9]), "+f"(d[10]), "+f"(d[11]), "+f"(d[12]), "+f"(d[13]), "+f"(d[14]), "+f"(d[15]), "+f"(d[16]), "+f"(d[17]), "+f"(d[18]), "+f"(d[19]), "+f"(d[20]), "+f"(d[21]), "+f"(d[22]), "+f"(d[23])
    : "r"(a[0]), "r"(a[1]), "r"(a[2]), "r"(a[3]), "r"(a[4]), "r"(a[5]), "r"(a[6]), "r"(a[7]), "r"(a[8]), "r"(a[9]), "r"(a[10]), "r"(a[11]), "r"(a[12]), "r"(a[13]), "r"(a[14]), "r"(a[15]), "l"(db), "n"(D)
    : "memory");
}
template<int D> __device__ __forceinline__ void c1_acc(float (&d)[28], const uint32_t (&a)[16], uint64_t db) {
  asm volatile("{\n.reg .b64 db;\n"
    "add.s64 db, %44, %45 + 0;\n"
    "wgmma.mma_async.sync.aligned.m64n56k16.f32.bf16.bf16 {%0, %1, %2, %3, %4, %5, %6, %7, %8, %9, %10, %11, %12, %13, %14, %15, %16, %17, %18, %19, %20, %21, %22, %23, %24, %25, %26, %27}, {%28, %29, %30, %31}, db, 1, 1, 1, 0;\n"
    "add.s64 db, %44, %45 + 2;\n"
    "wgmma.mma_async.sync.aligned.m64n56k16.f32.bf16.bf16 {%0, %1, %2, %3, %4, %5, %6, %7, %8, %9, %10, %11, %12, %13, %14, %15, %16, %17, %18, %19, %20, %21, %22, %23, %24, %25, %26, %27}, {%32, %33, %34, %35}, db, 1, 1, 1, 0;\n"
    "add.s64 db, %44, %45 + 4;\n"
    "wgmma.mma_async.sync.aligned.m64n56k16.f32.bf16.bf16 {%0, %1, %2, %3, %4, %5, %6, %7, %8, %9, %10, %11, %12, %13, %14, %15, %16, %17, %18, %19, %20, %21, %22, %23, %24, %25, %26, %27}, {%36, %37, %38, %39}, db, 1, 1, 1, 0;\n"
    "add.s64 db, %44, %45 + 6;\n"
    "wgmma.mma_async.sync.aligned.m64n56k16.f32.bf16.bf16 {%0, %1, %2, %3, %4, %5, %6, %7, %8, %9, %10, %11, %12, %13, %14, %15, %16, %17, %18, %19, %20, %21, %22, %23, %24, %25, %26, %27}, {%40, %41, %42, %43}, db, 1, 1, 1, 0;\n"
    "wgmma.commit_group.sync.aligned;\n}\n"
    : "+f"(d[0]), "+f"(d[1]), "+f"(d[2]), "+f"(d[3]), "+f"(d[4]), "+f"(d[5]), "+f"(d[6]), "+f"(d[7]), "+f"(d[8]), "+f"(d[9]), "+f"(d[10]), "+f"(d[11]), "+f"(d[12]), "+f"(d[13]), "+f"(d[14]), "+f"(d[15]), "+f"(d[16]), "+f"(d[17]), "+f"(d[18]), "+f"(d[19]), "+f"(d[20]), "+f"(d[21]), "+f"(d[22]), "+f"(d[23]), "+f"(d[24]), "+f"(d[25]), "+f"(d[26]), "+f"(d[27])
    : "r"(a[0]), "r"(a[1]), "r"(a[2]), "r"(a[3]), "r"(a[4]), "r"(a[5]), "r"(a[6]), "r"(a[7]), "r"(a[8]), "r"(a[9]), "r"(a[10]), "r"(a[11]), "r"(a[12]), "r"(a[13]), "r"(a[14]), "r"(a[15]), "l"(db), "n"(D)
    : "memory");
}
template<int D> __device__ __forceinline__ void c1_acc(float (&d)[32], const uint32_t (&a)[16], uint64_t db) {
  asm volatile("{\n.reg .b64 db;\n"
    "add.s64 db, %48, %49 + 0;\n"
    "wgmma.mma_async.sync.aligned.m64n64k16.f32.bf16.bf16 {%0, %1, %2, %3, %4, %5, %6, %7, %8, %9, %10, %11, %12, %13, %14, %15, %16, %17, %18, %19, %20, %21, %22, %23, %24, %25, %26, %27, %28, %29, %30, %31}, {%32, %33, %34, %35}, db, 1, 1, 1, 0;\n"
    "add.s64 db, %48, %49 + 2;\n"
    "wgmma.mma_async.sync.aligned.m64n64k16.f32.bf16.bf16 {%0, %1, %2, %3, %4, %5, %6, %7, %8, %9, %10, %11, %12, %13, %14, %15, %16, %17, %18, %19, %20, %21, %22, %23, %24, %25, %26, %27, %28, %29, %30, %31}, {%36, %37, %38, %39}, db, 1, 1, 1, 0;\n"
    "add.s64 db, %48, %49 + 4;\n"
    "wgmma.mma_async.sync.aligned.m64n64k16.f32.bf16.bf16 {%0, %1, %2, %3, %4, %5, %6, %7, %8, %9, %10, %11, %12, %13, %14, %15, %16, %17, %18, %19, %20, %21, %22, %23, %24, %25, %26, %27, %28, %29, %30, %31}, {%40, %41, %42, %43}, db, 1, 1, 1, 0;\n"
    "add.s64 db, %48, %49 + 6;\n"
    "wgmma.mma_async.sync.aligned.m64n64k16.f32.bf16.bf16 {%0, %1, %2, %3, %4, %5, %6, %7, %8, %9, %10, %11, %12, %13, %14, %15, %16, %17, %18, %19, %20, %21, %22, %23, %24, %25, %26, %27, %28, %29, %30, %31}, {%44, %45, %46, %47}, db, 1, 1, 1, 0;\n"
    "wgmma.commit_group.sync.aligned;\n}\n"
    : "+f"(d[0]), "+f"(d[1]), "+f"(d[2]), "+f"(d[3]), "+f"(d[4]), "+f"(d[5]), "+f"(d[6]), "+f"(d[7]), "+f"(d[8]), "+f"(d[9]), "+f"(d[10]), "+f"(d[11]), "+f"(d[12]), "+f"(d[13]), "+f"(d[14]), "+f"(d[15]), "+f"(d[16]), "+f"(d[17]), "+f"(d[18]), "+f"(d[19]), "+f"(d[20]), "+f"(d[21]), "+f"(d[22]), "+f"(d[23]), "+f"(d[24]), "+f"(d[25]), "+f"(d[26]), "+f"(d[27]), "+f"(d[28]), "+f"(d[29]), "+f"(d[30]), "+f"(d[31])
    : "r"(a[0]), "r"(a[1]), "r"(a[2]), "r"(a[3]), "r"(a[4]), "r"(a[5]), "r"(a[6]), "r"(a[7]), "r"(a[8]), "r"(a[9]), "r"(a[10]), "r"(a[11]), "r"(a[12]), "r"(a[13]), "r"(a[14]), "r"(a[15]), "l"(db), "n"(D)
    : "memory");
}
template<int D> __device__ __forceinline__ void c1_acc(float (&d)[36], const uint32_t (&a)[16], uint64_t db) {
  asm volatile("{\n.reg .b64 db;\n"
    "add.s64 db, %52, %53 + 0;\n"
    "wgmma.mma_async.sync.aligned.m64n72k16.f32.bf16.bf16 {%0, %1, %2, %3, %4, %5, %6, %7, %8, %9, %10, %11, %12, %13, %14, %15, %16, %17, %18, %19, %20, %21, %22, %23, %24, %25, %26, %27, %28, %29, %30, %31, %32, %33, %34, %35}, {%36, %37, %38, %39}, db, 1, 1, 1, 0;\n"
    "add.s64 db, %52, %53 + 2;\n"
    "wgmma.mma_async.sync.aligned.m64n72k16.f32.bf16.bf16 {%0, %1, %2, %3, %4, %5, %6, %7, %8, %9, %10, %11, %12, %13, %14, %15, %16, %17, %18, %19, %20, %21, %22, %23, %24, %25, %26, %27, %28, %29, %30, %31, %32, %33, %34, %35}, {%40, %41, %42, %43}, db, 1, 1, 1, 0;\n"
    "add.s64 db, %52, %53 + 4;\n"
    "wgmma.mma_async.sync.aligned.m64n72k16.f32.bf16.bf16 {%0, %1, %2, %3, %4, %5, %6, %7, %8, %9, %10, %11, %12, %13, %14, %15, %16, %17, %18, %19, %20, %21, %22, %23, %24, %25, %26, %27, %28, %29, %30, %31, %32, %33, %34, %35}, {%44, %45, %46, %47}, db, 1, 1, 1, 0;\n"
    "add.s64 db, %52, %53 + 6;\n"
    "wgmma.mma_async.sync.aligned.m64n72k16.f32.bf16.bf16 {%0, %1, %2, %3, %4, %5, %6, %7, %8, %9, %10, %11, %12, %13, %14, %15, %16, %17, %18, %19, %20, %21, %22, %23, %24, %25, %26, %27, %28, %29, %30, %31, %32, %33, %34, %35}, {%48, %49, %50, %51}, db, 1, 1, 1, 0;\n"
    "wgmma.commit_group.sync.aligned;\n}\n"
    : "+f"(d[0]), "+f"(d[1]), "+f"(d[2]), "+f"(d[3]), "+f"(d[4]), "+f"(d[5]), "+f"(d[6]), "+f"(d[7]), "+f"(d[8]), "+f"(d[9]), "+f"(d[10]), "+f"(d[11]), "+f"(d[12]), "+f"(d[13]), "+f"(d[14]), "+f"(d[15]), "+f"(d[16]), "+f"(d[17]), "+f"(d[18]), "+f"(d[19]), "+f"(d[20]), "+f"(d[21]), "+f"(d[22]), "+f"(d[23]), "+f"(d[24]), "+f"(d[25]), "+f"(d[26]), "+f"(d[27]), "+f"(d[28]), "+f"(d[29]), "+f"(d[30]), "+f"(d[31]), "+f"(d[32]), "+f"(d[33]), "+f"(d[34]), "+f"(d[35])
    : "r"(a[0]), "r"(a[1]), "r"(a[2]), "r"(a[3]), "r"(a[4]), "r"(a[5]), "r"(a[6]), "r"(a[7]), "r"(a[8]), "r"(a[9]), "r"(a[10]), "r"(a[11]), "r"(a[12]), "r"(a[13]), "r"(a[14]), "r"(a[15]), "l"(db), "n"(D)
    : "memory");
}
template<int D> __device__ __forceinline__ void c1_acc(float (&d)[40], const uint32_t (&a)[16], uint64_t db) {
  asm volatile("{\n.reg .b64 db;\n"
    "add.s64 db, %56, %57 + 0;\n"
    "wgmma.mma_async.sync.aligned.m64n80k16.f32.bf16.bf16 {%0, %1, %2, %3, %4, %5, %6, %7, %8, %9, %10, %11, %12, %13, %14, %15, %16, %17, %18, %19, %20, %21, %22, %23, %24, %25, %26, %27, %28, %29, %30, %31, %32, %33, %34, %35, %36, %37, %38, %39}, {%40, %41, %42, %43}, db, 1, 1, 1, 0;\n"
    "add.s64 db, %56, %57 + 2;\n"
    "wgmma.mma_async.sync.aligned.m64n80k16.f32.bf16.bf16 {%0, %1, %2, %3, %4, %5, %6, %7, %8, %9, %10, %11, %12, %13, %14, %15, %16, %17, %18, %19, %20, %21, %22, %23, %24, %25, %26, %27, %28, %29, %30, %31, %32, %33, %34, %35, %36, %37, %38, %39}, {%44, %45, %46, %47}, db, 1, 1, 1, 0;\n"
    "add.s64 db, %56, %57 + 4;\n"
    "wgmma.mma_async.sync.aligned.m64n80k16.f32.bf16.bf16 {%0, %1, %2, %3, %4, %5, %6, %7, %8, %9, %10, %11, %12, %13, %14, %15, %16, %17, %18, %19, %20, %21, %22, %23, %24, %25, %26, %27, %28, %29, %30, %31, %32, %33, %34, %35, %36, %37, %38, %39}, {%48, %49, %50, %51}, db, 1, 1, 1, 0;\n"
    "add.s64 db, %56, %57 + 6;\n"
    "wgmma.mma_async.sync.aligned.m64n80k16.f32.bf16.bf16 {%0, %1, %2, %3, %4, %5, %6, %7, %8, %9, %10, %11, %12, %13, %14, %15, %16, %17, %18, %19, %20, %21, %22, %23, %24, %25, %26, %27, %28, %29, %30, %31, %32, %33, %34, %35, %36, %37, %38, %39}, {%52, %53, %54, %55}, db, 1, 1, 1, 0;\n"
    "wgmma.commit_group.sync.aligned;\n}\n"
    : "+f"(d[0]), "+f"(d[1]), "+f"(d[2]), "+f"(d[3]), "+f"(d[4]), "+f"(d[5]), "+f"(d[6]), "+f"(d[7]), "+f"(d[8]), "+f"(d[9]), "+f"(d[10]), "+f"(d[11]), "+f"(d[12]), "+f"(d[13]), "+f"(d[14]), "+f"(d[15]), "+f"(d[16]), "+f"(d[17]), "+f"(d[18]), "+f"(d[19]), "+f"(d[20]), "+f"(d[21]), "+f"(d[22]), "+f"(d[23]), "+f"(d[24]), "+f"(d[25]), "+f"(d[26]), "+f"(d[27]), "+f"(d[28]), "+f"(d[29]), "+f"(d[30]), "+f"(d[31]), "+f"(d[32]), "+f"(d[33]), "+f"(d[34]), "+f"(d[35]), "+f"(d[36]), "+f"(d[37]), "+f"(d[38]), "+f"(d[39])
    : "r"(a[0]), "r"(a[1]), "r"(a[2]), "r"(a[3]), "r"(a[4]), "r"(a[5]), "r"(a[6]), "r"(a[7]), "r"(a[8]), "r"(a[9]), "r"(a[10]), "r"(a[11]), "r"(a[12]), "r"(a[13]), "r"(a[14]), "r"(a[15]), "l"(db), "n"(D)
    : "memory");
}
template<int D> __device__ __forceinline__ void c1_acc(float (&d)[44], const uint32_t (&a)[16], uint64_t db) {
  asm volatile("{\n.reg .b64 db;\n"
    "add.s64 db, %60, %61 + 0;\n"
    "wgmma.mma_async.sync.aligned.m64n88k16.f32.bf16.bf16 {%0, %1, %2, %3, %4, %5, %6, %7, %8, %9, %10, %11, %12, %13, %14, %15, %16, %17, %18, %19, %20, %21, %22, %23, %24, %25, %26, %27, %28, %29, %30, %31, %32, %33, %34, %35, %36, %37, %38, %39, %40, %41, %42, %43}, {%44, %45, %46, %47}, db, 1, 1, 1, 0;\n"
    "add.s64 db, %60, %61 + 2;\n"
    "wgmma.mma_async.sync.aligned.m64n88k16.f32.bf16.bf16 {%0, %1, %2, %3, %4, %5, %6, %7, %8, %9, %10, %11, %12, %13, %14, %15, %16, %17, %18, %19, %20, %21, %22, %23, %24, %25, %26, %27, %28, %29, %30, %31, %32, %33, %34, %35, %36, %37, %38, %39, %40, %41, %42, %43}, {%48, %49, %50, %51}, db, 1, 1, 1, 0;\n"
    "add.s64 db, %60, %61 + 4;\n"
    "wgmma.mma_async.sync.aligned.m64n88k16.f32.bf16.bf16 {%0, %1, %2, %3, %4, %5, %6, %7, %8, %9, %10, %11, %12, %13, %14, %15, %16, %17, %18, %19, %20, %21, %22, %23, %24, %25, %26, %27, %28, %29, %30, %31, %32, %33, %34, %35, %36, %37, %38, %39, %40, %41, %42, %43}, {%52, %53, %54, %55}, db, 1, 1, 1, 0;\n"
    "add.s64 db, %60, %61 + 6;\n"
    "wgmma.mma_async.sync.aligned.m64n88k16.f32.bf16.bf16 {%0, %1, %2, %3, %4, %5, %6, %7, %8, %9, %10, %11, %12, %13, %14, %15, %16, %17, %18, %19, %20, %21, %22, %23, %24, %25, %26, %27, %28, %29, %30, %31, %32, %33, %34, %35, %36, %37, %38, %39, %40, %41, %42, %43}, {%56, %57, %58, %59}, db, 1, 1, 1, 0;\n"
    "wgmma.commit_group.sync.aligned;\n}\n"
    : "+f"(d[0]), "+f"(d[1]), "+f"(d[2]), "+f"(d[3]), "+f"(d[4]), "+f"(d[5]), "+f"(d[6]), "+f"(d[7]), "+f"(d[8]), "+f"(d[9]), "+f"(d[10]), "+f"(d[11]), "+f"(d[12]), "+f"(d[13]), "+f"(d[14]), "+f"(d[15]), "+f"(d[16]), "+f"(d[17]), "+f"(d[18]), "+f"(d[19]), "+f"(d[20]), "+f"(d[21]), "+f"(d[22]), "+f"(d[23]), "+f"(d[24]), "+f"(d[25]), "+f"(d[26]), "+f"(d[27]), "+f"(d[28]), "+f"(d[29]), "+f"(d[30]), "+f"(d[31]), "+f"(d[32]), "+f"(d[33]), "+f"(d[34]), "+f"(d[35]), "+f"(d[36]), "+f"(d[37]), "+f"(d[38]), "+f"(d[39]), "+f"(d[40]), "+f"(d[41]), "+f"(d[42]), "+f"(d[43])
    : "r"(a[0]), "r"(a[1]), "r"(a[2]), "r"(a[3]), "r"(a[4]), "r"(a[5]), "r"(a[6]), "r"(a[7]), "r"(a[8]), "r"(a[9]), "r"(a[10]), "r"(a[11]), "r"(a[12]), "r"(a[13]), "r"(a[14]), "r"(a[15]), "l"(db), "n"(D)
    : "memory");
}
template<int D> __device__ __forceinline__ void cbias(float (&d)[4], const uint32_t (&a)[16], uint64_t db) {
  asm volatile("{\n.reg .b64 db;\n"
    "add.s64 db, %20, %21 + 0;\n"
    "wgmma.mma_async.sync.aligned.m64n8k16.f32.bf16.bf16 {%0, %1, %2, %3}, {%4, %5, %6, %7}, db, 0, 1, 1, 0;\n"
    "add.s64 db, %20, %21 + 2;\n"
    "wgmma.mma_async.sync.aligned.m64n8k16.f32.bf16.bf16 {%0, %1, %2, %3}, {%8, %9, %10, %11}, db, 1, 1, 1, 0;\n"
    "add.s64 db, %20, %21 + 4;\n"
    "wgmma.mma_async.sync.aligned.m64n8k16.f32.bf16.bf16 {%0, %1, %2, %3}, {%12, %13, %14, %15}, db, 1, 1, 1, 0;\n"
    "add.s64 db, %20, %21 + 6;\n"
    "wgmma.mma_async.sync.aligned.m64n8k16.f32.bf16.bf16 {%0, %1, %2, %3}, {%16, %17, %18, %19}, db, 1, 1, 1, 0;\n"
    "wgmma.commit_group.sync.aligned;\n}\n"
    : "=f"(d[0]), "=f"(d[1]), "=f"(d[2]), "=f"(d[3])
    : "r"(a[0]), "r"(a[1]), "r"(a[2]), "r"(a[3]), "r"(a[4]), "r"(a[5]), "r"(a[6]), "r"(a[7]), "r"(a[8]), "r"(a[9]), "r"(a[10]), "r"(a[11]), "r"(a[12]), "r"(a[13]), "r"(a[14]), "r"(a[15]), "l"(db), "n"(D)
    : "memory");
}
template<int D> __device__ __forceinline__ void c2_first(float (&d)[16], const uint32_t (&a)[4], uint64_t db, uint32_t meta) {
  asm volatile("{\n.reg .b64 db;\n"
    "wgmma.fence.sync.aligned;\n"
    "add.s64 db, %20, %21 + 0;\n"
    "wgmma.mma_async.sp.sync.aligned.m64n32k32.f32.bf16.bf16 {%0, %1, %2, %3, %4, %5, %6, %7, %8, %9, %10, %11, %12, %13, %14, %15}, {%16, %17, %18, %19}, db, %22, 0, 0, 1, 1, 1;\n"
    "wgmma.commit_group.sync.aligned;\n}\n"
    : "=f"(d[0]), "=f"(d[1]), "=f"(d[2]), "=f"(d[3]), "=f"(d[4]), "=f"(d[5]), "=f"(d[6]), "=f"(d[7]), "=f"(d[8]), "=f"(d[9]), "=f"(d[10]), "=f"(d[11]), "=f"(d[12]), "=f"(d[13]), "=f"(d[14]), "=f"(d[15])
    : "r"(a[0]), "r"(a[1]), "r"(a[2]), "r"(a[3]), "l"(db), "n"(D), "r"(meta)
    : "memory");
}
template<int D> __device__ __forceinline__ void c2_more(float (&d)[16], const uint32_t (&a)[4], uint64_t db, uint32_t meta) {
  asm volatile("{\n.reg .b64 db;\n"
    "wgmma.fence.sync.aligned;\n"
    "add.s64 db, %20, %21 + 0;\n"
    "wgmma.mma_async.sp.sync.aligned.m64n32k32.f32.bf16.bf16 {%0, %1, %2, %3, %4, %5, %6, %7, %8, %9, %10, %11, %12, %13, %14, %15}, {%16, %17, %18, %19}, db, %22, 0, 1, 1, 1, 1;\n"
    "wgmma.commit_group.sync.aligned;\n}\n"
    : "+f"(d[0]), "+f"(d[1]), "+f"(d[2]), "+f"(d[3]), "+f"(d[4]), "+f"(d[5]), "+f"(d[6]), "+f"(d[7]), "+f"(d[8]), "+f"(d[9]), "+f"(d[10]), "+f"(d[11]), "+f"(d[12]), "+f"(d[13]), "+f"(d[14]), "+f"(d[15])
    : "r"(a[0]), "r"(a[1]), "r"(a[2]), "r"(a[3]), "l"(db), "n"(D), "r"(meta)
    : "memory");
}
template<int D> __device__ __forceinline__ void c2_first(float (&d)[16], const uint32_t (&a)[8], uint64_t db, uint32_t meta) {
  asm volatile("{\n.reg .b64 db;\n"
    "wgmma.fence.sync.aligned;\n"
    "add.s64 db, %24, %25 + 0;\n"
    "wgmma.mma_async.sp.sync.aligned.m64n32k32.f32.bf16.bf16 {%0, %1, %2, %3, %4, %5, %6, %7, %8, %9, %10, %11, %12, %13, %14, %15}, {%16, %17, %18, %19}, db, %26, 0, 0, 1, 1, 1;\n"
    "add.s64 db, %24, %25 + 128;\n"
    "wgmma.mma_async.sp.sync.aligned.m64n32k32.f32.bf16.bf16 {%0, %1, %2, %3, %4, %5, %6, %7, %8, %9, %10, %11, %12, %13, %14, %15}, {%20, %21, %22, %23}, db, %26, 0, 1, 1, 1, 1;\n"
    "wgmma.commit_group.sync.aligned;\n}\n"
    : "=f"(d[0]), "=f"(d[1]), "=f"(d[2]), "=f"(d[3]), "=f"(d[4]), "=f"(d[5]), "=f"(d[6]), "=f"(d[7]), "=f"(d[8]), "=f"(d[9]), "=f"(d[10]), "=f"(d[11]), "=f"(d[12]), "=f"(d[13]), "=f"(d[14]), "=f"(d[15])
    : "r"(a[0]), "r"(a[1]), "r"(a[2]), "r"(a[3]), "r"(a[4]), "r"(a[5]), "r"(a[6]), "r"(a[7]), "l"(db), "n"(D), "r"(meta)
    : "memory");
}
template<int D> __device__ __forceinline__ void c2_more(float (&d)[16], const uint32_t (&a)[8], uint64_t db, uint32_t meta) {
  asm volatile("{\n.reg .b64 db;\n"
    "wgmma.fence.sync.aligned;\n"
    "add.s64 db, %24, %25 + 0;\n"
    "wgmma.mma_async.sp.sync.aligned.m64n32k32.f32.bf16.bf16 {%0, %1, %2, %3, %4, %5, %6, %7, %8, %9, %10, %11, %12, %13, %14, %15}, {%16, %17, %18, %19}, db, %26, 0, 1, 1, 1, 1;\n"
    "add.s64 db, %24, %25 + 128;\n"
    "wgmma.mma_async.sp.sync.aligned.m64n32k32.f32.bf16.bf16 {%0, %1, %2, %3, %4, %5, %6, %7, %8, %9, %10, %11, %12, %13, %14, %15}, {%20, %21, %22, %23}, db, %26, 0, 1, 1, 1, 1;\n"
    "wgmma.commit_group.sync.aligned;\n}\n"
    : "+f"(d[0]), "+f"(d[1]), "+f"(d[2]), "+f"(d[3]), "+f"(d[4]), "+f"(d[5]), "+f"(d[6]), "+f"(d[7]), "+f"(d[8]), "+f"(d[9]), "+f"(d[10]), "+f"(d[11]), "+f"(d[12]), "+f"(d[13]), "+f"(d[14]), "+f"(d[15])
    : "r"(a[0]), "r"(a[1]), "r"(a[2]), "r"(a[3]), "r"(a[4]), "r"(a[5]), "r"(a[6]), "r"(a[7]), "l"(db), "n"(D), "r"(meta)
    : "memory");
}
template<int D> __device__ __forceinline__ void c2_first(float (&d)[16], const uint32_t (&a)[12], uint64_t db, uint32_t meta) {
  asm volatile("{\n.reg .b64 db;\n"
    "wgmma.fence.sync.aligned;\n"
    "add.s64 db, %28, %29 + 0;\n"
    "wgmma.mma_async.sp.sync.aligned.m64n32k32.f32.bf16.bf16 {%0, %1, %2, %3, %4, %5, %6, %7, %8, %9, %10, %11, %12, %13, %14, %15}, {%16, %17, %18, %19}, db, %30, 0, 0, 1, 1, 1;\n"
    "add.s64 db, %28, %29 + 128;\n"
    "wgmma.mma_async.sp.sync.aligned.m64n32k32.f32.bf16.bf16 {%0, %1, %2, %3, %4, %5, %6, %7, %8, %9, %10, %11, %12, %13, %14, %15}, {%20, %21, %22, %23}, db, %30, 0, 1, 1, 1, 1;\n"
    "add.s64 db, %28, %29 + 256;\n"
    "wgmma.mma_async.sp.sync.aligned.m64n32k32.f32.bf16.bf16 {%0, %1, %2, %3, %4, %5, %6, %7, %8, %9, %10, %11, %12, %13, %14, %15}, {%24, %25, %26, %27}, db, %30, 0, 1, 1, 1, 1;\n"
    "wgmma.commit_group.sync.aligned;\n}\n"
    : "=f"(d[0]), "=f"(d[1]), "=f"(d[2]), "=f"(d[3]), "=f"(d[4]), "=f"(d[5]), "=f"(d[6]), "=f"(d[7]), "=f"(d[8]), "=f"(d[9]), "=f"(d[10]), "=f"(d[11]), "=f"(d[12]), "=f"(d[13]), "=f"(d[14]), "=f"(d[15])
    : "r"(a[0]), "r"(a[1]), "r"(a[2]), "r"(a[3]), "r"(a[4]), "r"(a[5]), "r"(a[6]), "r"(a[7]), "r"(a[8]), "r"(a[9]), "r"(a[10]), "r"(a[11]), "l"(db), "n"(D), "r"(meta)
    : "memory");
}
template<int D> __device__ __forceinline__ void c2_more(float (&d)[16], const uint32_t (&a)[12], uint64_t db, uint32_t meta) {
  asm volatile("{\n.reg .b64 db;\n"
    "wgmma.fence.sync.aligned;\n"
    "add.s64 db, %28, %29 + 0;\n"
    "wgmma.mma_async.sp.sync.aligned.m64n32k32.f32.bf16.bf16 {%0, %1, %2, %3, %4, %5, %6, %7, %8, %9, %10, %11, %12, %13, %14, %15}, {%16, %17, %18, %19}, db, %30, 0, 1, 1, 1, 1;\n"
    "add.s64 db, %28, %29 + 128;\n"
    "wgmma.mma_async.sp.sync.aligned.m64n32k32.f32.bf16.bf16 {%0, %1, %2, %3, %4, %5, %6, %7, %8, %9, %10, %11, %12, %13, %14, %15}, {%20, %21, %22, %23}, db, %30, 0, 1, 1, 1, 1;\n"
    "add.s64 db, %28, %29 + 256;\n"
    "wgmma.mma_async.sp.sync.aligned.m64n32k32.f32.bf16.bf16 {%0, %1, %2, %3, %4, %5, %6, %7, %8, %9, %10, %11, %12, %13, %14, %15}, {%24, %25, %26, %27}, db, %30, 0, 1, 1, 1, 1;\n"
    "wgmma.commit_group.sync.aligned;\n}\n"
    : "+f"(d[0]), "+f"(d[1]), "+f"(d[2]), "+f"(d[3]), "+f"(d[4]), "+f"(d[5]), "+f"(d[6]), "+f"(d[7]), "+f"(d[8]), "+f"(d[9]), "+f"(d[10]), "+f"(d[11]), "+f"(d[12]), "+f"(d[13]), "+f"(d[14]), "+f"(d[15])
    : "r"(a[0]), "r"(a[1]), "r"(a[2]), "r"(a[3]), "r"(a[4]), "r"(a[5]), "r"(a[6]), "r"(a[7]), "r"(a[8]), "r"(a[9]), "r"(a[10]), "r"(a[11]), "l"(db), "n"(D), "r"(meta)
    : "memory");
}
template<int D> __device__ __forceinline__ void c2_first(float (&d)[16], const uint32_t (&a)[16], uint64_t db, uint32_t meta) {
  asm volatile("{\n.reg .b64 db;\n"
    "wgmma.fence.sync.aligned;\n"
    "add.s64 db, %32, %33 + 0;\n"
    "wgmma.mma_async.sp.sync.aligned.m64n32k32.f32.bf16.bf16 {%0, %1, %2, %3, %4, %5, %6, %7, %8, %9, %10, %11, %12, %13, %14, %15}, {%16, %17, %18, %19}, db, %34, 0, 0, 1, 1, 1;\n"
    "add.s64 db, %32, %33 + 128;\n"
    "wgmma.mma_async.sp.sync.aligned.m64n32k32.f32.bf16.bf16 {%0, %1, %2, %3, %4, %5, %6, %7, %8, %9, %10, %11, %12, %13, %14, %15}, {%20, %21, %22, %23}, db, %34, 0, 1, 1, 1, 1;\n"
    "add.s64 db, %32, %33 + 256;\n"
    "wgmma.mma_async.sp.sync.aligned.m64n32k32.f32.bf16.bf16 {%0, %1, %2, %3, %4, %5, %6, %7, %8, %9, %10, %11, %12, %13, %14, %15}, {%24, %25, %26, %27}, db, %34, 0, 1, 1, 1, 1;\n"
    "add.s64 db, %32, %33 + 384;\n"
    "wgmma.mma_async.sp.sync.aligned.m64n32k32.f32.bf16.bf16 {%0, %1, %2, %3, %4, %5, %6, %7, %8, %9, %10, %11, %12, %13, %14, %15}, {%28, %29, %30, %31}, db, %34, 0, 1, 1, 1, 1;\n"
    "wgmma.commit_group.sync.aligned;\n}\n"
    : "=f"(d[0]), "=f"(d[1]), "=f"(d[2]), "=f"(d[3]), "=f"(d[4]), "=f"(d[5]), "=f"(d[6]), "=f"(d[7]), "=f"(d[8]), "=f"(d[9]), "=f"(d[10]), "=f"(d[11]), "=f"(d[12]), "=f"(d[13]), "=f"(d[14]), "=f"(d[15])
    : "r"(a[0]), "r"(a[1]), "r"(a[2]), "r"(a[3]), "r"(a[4]), "r"(a[5]), "r"(a[6]), "r"(a[7]), "r"(a[8]), "r"(a[9]), "r"(a[10]), "r"(a[11]), "r"(a[12]), "r"(a[13]), "r"(a[14]), "r"(a[15]), "l"(db), "n"(D), "r"(meta)
    : "memory");
}
template<int D> __device__ __forceinline__ void c2_more(float (&d)[16], const uint32_t (&a)[16], uint64_t db, uint32_t meta) {
  asm volatile("{\n.reg .b64 db;\n"
    "wgmma.fence.sync.aligned;\n"
    "add.s64 db, %32, %33 + 0;\n"
    "wgmma.mma_async.sp.sync.aligned.m64n32k32.f32.bf16.bf16 {%0, %1, %2, %3, %4, %5, %6, %7, %8, %9, %10, %11, %12, %13, %14, %15}, {%16, %17, %18, %19}, db, %34, 0, 1, 1, 1, 1;\n"
    "add.s64 db, %32, %33 + 128;\n"
    "wgmma.mma_async.sp.sync.aligned.m64n32k32.f32.bf16.bf16 {%0, %1, %2, %3, %4, %5, %6, %7, %8, %9, %10, %11, %12, %13, %14, %15}, {%20, %21, %22, %23}, db, %34, 0, 1, 1, 1, 1;\n"
    "add.s64 db, %32, %33 + 256;\n"
    "wgmma.mma_async.sp.sync.aligned.m64n32k32.f32.bf16.bf16 {%0, %1, %2, %3, %4, %5, %6, %7, %8, %9, %10, %11, %12, %13, %14, %15}, {%24, %25, %26, %27}, db, %34, 0, 1, 1, 1, 1;\n"
    "add.s64 db, %32, %33 + 384;\n"
    "wgmma.mma_async.sp.sync.aligned.m64n32k32.f32.bf16.bf16 {%0, %1, %2, %3, %4, %5, %6, %7, %8, %9, %10, %11, %12, %13, %14, %15}, {%28, %29, %30, %31}, db, %34, 0, 1, 1, 1, 1;\n"
    "wgmma.commit_group.sync.aligned;\n}\n"
    : "+f"(d[0]), "+f"(d[1]), "+f"(d[2]), "+f"(d[3]), "+f"(d[4]), "+f"(d[5]), "+f"(d[6]), "+f"(d[7]), "+f"(d[8]), "+f"(d[9]), "+f"(d[10]), "+f"(d[11]), "+f"(d[12]), "+f"(d[13]), "+f"(d[14]), "+f"(d[15])
    : "r"(a[0]), "r"(a[1]), "r"(a[2]), "r"(a[3]), "r"(a[4]), "r"(a[5]), "r"(a[6]), "r"(a[7]), "r"(a[8]), "r"(a[9]), "r"(a[10]), "r"(a[11]), "r"(a[12]), "r"(a[13]), "r"(a[14]), "r"(a[15]), "l"(db), "n"(D), "r"(meta)
    : "memory");
}
template<int D> __device__ __forceinline__ void c2_first(float (&d)[16], const uint32_t (&a)[20], uint64_t db, uint32_t meta) {
  asm volatile("{\n.reg .b64 db;\n"
    "wgmma.fence.sync.aligned;\n"
    "add.s64 db, %36, %37 + 0;\n"
    "wgmma.mma_async.sp.sync.aligned.m64n32k32.f32.bf16.bf16 {%0, %1, %2, %3, %4, %5, %6, %7, %8, %9, %10, %11, %12, %13, %14, %15}, {%16, %17, %18, %19}, db, %38, 0, 0, 1, 1, 1;\n"
    "add.s64 db, %36, %37 + 128;\n"
    "wgmma.mma_async.sp.sync.aligned.m64n32k32.f32.bf16.bf16 {%0, %1, %2, %3, %4, %5, %6, %7, %8, %9, %10, %11, %12, %13, %14, %15}, {%20, %21, %22, %23}, db, %38, 0, 1, 1, 1, 1;\n"
    "add.s64 db, %36, %37 + 256;\n"
    "wgmma.mma_async.sp.sync.aligned.m64n32k32.f32.bf16.bf16 {%0, %1, %2, %3, %4, %5, %6, %7, %8, %9, %10, %11, %12, %13, %14, %15}, {%24, %25, %26, %27}, db, %38, 0, 1, 1, 1, 1;\n"
    "add.s64 db, %36, %37 + 384;\n"
    "wgmma.mma_async.sp.sync.aligned.m64n32k32.f32.bf16.bf16 {%0, %1, %2, %3, %4, %5, %6, %7, %8, %9, %10, %11, %12, %13, %14, %15}, {%28, %29, %30, %31}, db, %38, 0, 1, 1, 1, 1;\n"
    "add.s64 db, %36, %37 + 512;\n"
    "wgmma.mma_async.sp.sync.aligned.m64n32k32.f32.bf16.bf16 {%0, %1, %2, %3, %4, %5, %6, %7, %8, %9, %10, %11, %12, %13, %14, %15}, {%32, %33, %34, %35}, db, %38, 0, 1, 1, 1, 1;\n"
    "wgmma.commit_group.sync.aligned;\n}\n"
    : "=f"(d[0]), "=f"(d[1]), "=f"(d[2]), "=f"(d[3]), "=f"(d[4]), "=f"(d[5]), "=f"(d[6]), "=f"(d[7]), "=f"(d[8]), "=f"(d[9]), "=f"(d[10]), "=f"(d[11]), "=f"(d[12]), "=f"(d[13]), "=f"(d[14]), "=f"(d[15])
    : "r"(a[0]), "r"(a[1]), "r"(a[2]), "r"(a[3]), "r"(a[4]), "r"(a[5]), "r"(a[6]), "r"(a[7]), "r"(a[8]), "r"(a[9]), "r"(a[10]), "r"(a[11]), "r"(a[12]), "r"(a[13]), "r"(a[14]), "r"(a[15]), "r"(a[16]), "r"(a[17]), "r"(a[18]), "r"(a[19]), "l"(db), "n"(D), "r"(meta)
    : "memory");
}
template<int D> __device__ __forceinline__ void c2_more(float (&d)[16], const uint32_t (&a)[20], uint64_t db, uint32_t meta) {
  asm volatile("{\n.reg .b64 db;\n"
    "wgmma.fence.sync.aligned;\n"
    "add.s64 db, %36, %37 + 0;\n"
    "wgmma.mma_async.sp.sync.aligned.m64n32k32.f32.bf16.bf16 {%0, %1, %2, %3, %4, %5, %6, %7, %8, %9, %10, %11, %12, %13, %14, %15}, {%16, %17, %18, %19}, db, %38, 0, 1, 1, 1, 1;\n"
    "add.s64 db, %36, %37 + 128;\n"
    "wgmma.mma_async.sp.sync.aligned.m64n32k32.f32.bf16.bf16 {%0, %1, %2, %3, %4, %5, %6, %7, %8, %9, %10, %11, %12, %13, %14, %15}, {%20, %21, %22, %23}, db, %38, 0, 1, 1, 1, 1;\n"
    "add.s64 db, %36, %37 + 256;\n"
    "wgmma.mma_async.sp.sync.aligned.m64n32k32.f32.bf16.bf16 {%0, %1, %2, %3, %4, %5, %6, %7, %8, %9, %10, %11, %12, %13, %14, %15}, {%24, %25, %26, %27}, db, %38, 0, 1, 1, 1, 1;\n"
    "add.s64 db, %36, %37 + 384;\n"
    "wgmma.mma_async.sp.sync.aligned.m64n32k32.f32.bf16.bf16 {%0, %1, %2, %3, %4, %5, %6, %7, %8, %9, %10, %11, %12, %13, %14, %15}, {%28, %29, %30, %31}, db, %38, 0, 1, 1, 1, 1;\n"
    "add.s64 db, %36, %37 + 512;\n"
    "wgmma.mma_async.sp.sync.aligned.m64n32k32.f32.bf16.bf16 {%0, %1, %2, %3, %4, %5, %6, %7, %8, %9, %10, %11, %12, %13, %14, %15}, {%32, %33, %34, %35}, db, %38, 0, 1, 1, 1, 1;\n"
    "wgmma.commit_group.sync.aligned;\n}\n"
    : "+f"(d[0]), "+f"(d[1]), "+f"(d[2]), "+f"(d[3]), "+f"(d[4]), "+f"(d[5]), "+f"(d[6]), "+f"(d[7]), "+f"(d[8]), "+f"(d[9]), "+f"(d[10]), "+f"(d[11]), "+f"(d[12]), "+f"(d[13]), "+f"(d[14]), "+f"(d[15])
    : "r"(a[0]), "r"(a[1]), "r"(a[2]), "r"(a[3]), "r"(a[4]), "r"(a[5]), "r"(a[6]), "r"(a[7]), "r"(a[8]), "r"(a[9]), "r"(a[10]), "r"(a[11]), "r"(a[12]), "r"(a[13]), "r"(a[14]), "r"(a[15]), "r"(a[16]), "r"(a[17]), "r"(a[18]), "r"(a[19]), "l"(db), "n"(D), "r"(meta)
    : "memory");
}
template<int D> __device__ __forceinline__ void c2_first(float (&d)[16], const uint32_t (&a)[24], uint64_t db, uint32_t meta) {
  asm volatile("{\n.reg .b64 db;\n"
    "wgmma.fence.sync.aligned;\n"
    "add.s64 db, %40, %41 + 0;\n"
    "wgmma.mma_async.sp.sync.aligned.m64n32k32.f32.bf16.bf16 {%0, %1, %2, %3, %4, %5, %6, %7, %8, %9, %10, %11, %12, %13, %14, %15}, {%16, %17, %18, %19}, db, %42, 0, 0, 1, 1, 1;\n"
    "add.s64 db, %40, %41 + 128;\n"
    "wgmma.mma_async.sp.sync.aligned.m64n32k32.f32.bf16.bf16 {%0, %1, %2, %3, %4, %5, %6, %7, %8, %9, %10, %11, %12, %13, %14, %15}, {%20, %21, %22, %23}, db, %42, 0, 1, 1, 1, 1;\n"
    "add.s64 db, %40, %41 + 256;\n"
    "wgmma.mma_async.sp.sync.aligned.m64n32k32.f32.bf16.bf16 {%0, %1, %2, %3, %4, %5, %6, %7, %8, %9, %10, %11, %12, %13, %14, %15}, {%24, %25, %26, %27}, db, %42, 0, 1, 1, 1, 1;\n"
    "add.s64 db, %40, %41 + 384;\n"
    "wgmma.mma_async.sp.sync.aligned.m64n32k32.f32.bf16.bf16 {%0, %1, %2, %3, %4, %5, %6, %7, %8, %9, %10, %11, %12, %13, %14, %15}, {%28, %29, %30, %31}, db, %42, 0, 1, 1, 1, 1;\n"
    "add.s64 db, %40, %41 + 512;\n"
    "wgmma.mma_async.sp.sync.aligned.m64n32k32.f32.bf16.bf16 {%0, %1, %2, %3, %4, %5, %6, %7, %8, %9, %10, %11, %12, %13, %14, %15}, {%32, %33, %34, %35}, db, %42, 0, 1, 1, 1, 1;\n"
    "add.s64 db, %40, %41 + 640;\n"
    "wgmma.mma_async.sp.sync.aligned.m64n32k32.f32.bf16.bf16 {%0, %1, %2, %3, %4, %5, %6, %7, %8, %9, %10, %11, %12, %13, %14, %15}, {%36, %37, %38, %39}, db, %42, 0, 1, 1, 1, 1;\n"
    "wgmma.commit_group.sync.aligned;\n}\n"
    : "=f"(d[0]), "=f"(d[1]), "=f"(d[2]), "=f"(d[3]), "=f"(d[4]), "=f"(d[5]), "=f"(d[6]), "=f"(d[7]), "=f"(d[8]), "=f"(d[9]), "=f"(d[10]), "=f"(d[11]), "=f"(d[12]), "=f"(d[13]), "=f"(d[14]), "=f"(d[15])
    : "r"(a[0]), "r"(a[1]), "r"(a[2]), "r"(a[3]), "r"(a[4]), "r"(a[5]), "r"(a[6]), "r"(a[7]), "r"(a[8]), "r"(a[9]), "r"(a[10]), "r"(a[11]), "r"(a[12]), "r"(a[13]), "r"(a[14]), "r"(a[15]), "r"(a[16]), "r"(a[17]), "r"(a[18]), "r"(a[19]), "r"(a[20]), "r"(a[21]), "r"(a[22]), "r"(a[23]), "l"(db), "n"(D), "r"(meta)
    : "memory");
}
template<int D> __device__ __forceinline__ void c2_more(float (&d)[16], const uint32_t (&a)[24], uint64_t db, uint32_t meta) {
  asm volatile("{\n.reg .b64 db;\n"
    "wgmma.fence.sync.aligned;\n"
    "add.s64 db, %40, %41 + 0;\n"
    "wgmma.mma_async.sp.sync.aligned.m64n32k32.f32.bf16.bf16 {%0, %1, %2, %3, %4, %5, %6, %7, %8, %9, %10, %11, %12, %13, %14, %15}, {%16, %17, %18, %19}, db, %42, 0, 1, 1, 1, 1;\n"
    "add.s64 db, %40, %41 + 128;\n"
    "wgmma.mma_async.sp.sync.aligned.m64n32k32.f32.bf16.bf16 {%0, %1, %2, %3, %4, %5, %6, %7, %8, %9, %10, %11, %12, %13, %14, %15}, {%20, %21, %22, %23}, db, %42, 0, 1, 1, 1, 1;\n"
    "add.s64 db, %40, %41 + 256;\n"
    "wgmma.mma_async.sp.sync.aligned.m64n32k32.f32.bf16.bf16 {%0, %1, %2, %3, %4, %5, %6, %7, %8, %9, %10, %11, %12, %13, %14, %15}, {%24, %25, %26, %27}, db, %42, 0, 1, 1, 1, 1;\n"
    "add.s64 db, %40, %41 + 384;\n"
    "wgmma.mma_async.sp.sync.aligned.m64n32k32.f32.bf16.bf16 {%0, %1, %2, %3, %4, %5, %6, %7, %8, %9, %10, %11, %12, %13, %14, %15}, {%28, %29, %30, %31}, db, %42, 0, 1, 1, 1, 1;\n"
    "add.s64 db, %40, %41 + 512;\n"
    "wgmma.mma_async.sp.sync.aligned.m64n32k32.f32.bf16.bf16 {%0, %1, %2, %3, %4, %5, %6, %7, %8, %9, %10, %11, %12, %13, %14, %15}, {%32, %33, %34, %35}, db, %42, 0, 1, 1, 1, 1;\n"
    "add.s64 db, %40, %41 + 640;\n"
    "wgmma.mma_async.sp.sync.aligned.m64n32k32.f32.bf16.bf16 {%0, %1, %2, %3, %4, %5, %6, %7, %8, %9, %10, %11, %12, %13, %14, %15}, {%36, %37, %38, %39}, db, %42, 0, 1, 1, 1, 1;\n"
    "wgmma.commit_group.sync.aligned;\n}\n"
    : "+f"(d[0]), "+f"(d[1]), "+f"(d[2]), "+f"(d[3]), "+f"(d[4]), "+f"(d[5]), "+f"(d[6]), "+f"(d[7]), "+f"(d[8]), "+f"(d[9]), "+f"(d[10]), "+f"(d[11]), "+f"(d[12]), "+f"(d[13]), "+f"(d[14]), "+f"(d[15])
    : "r"(a[0]), "r"(a[1]), "r"(a[2]), "r"(a[3]), "r"(a[4]), "r"(a[5]), "r"(a[6]), "r"(a[7]), "r"(a[8]), "r"(a[9]), "r"(a[10]), "r"(a[11]), "r"(a[12]), "r"(a[13]), "r"(a[14]), "r"(a[15]), "r"(a[16]), "r"(a[17]), "r"(a[18]), "r"(a[19]), "r"(a[20]), "r"(a[21]), "r"(a[22]), "r"(a[23]), "l"(db), "n"(D), "r"(meta)
    : "memory");
}
template<int D> __device__ __forceinline__ void c2_first(float (&d)[16], const uint32_t (&a)[28], uint64_t db, uint32_t meta) {
  asm volatile("{\n.reg .b64 db;\n"
    "wgmma.fence.sync.aligned;\n"
    "add.s64 db, %44, %45 + 0;\n"
    "wgmma.mma_async.sp.sync.aligned.m64n32k32.f32.bf16.bf16 {%0, %1, %2, %3, %4, %5, %6, %7, %8, %9, %10, %11, %12, %13, %14, %15}, {%16, %17, %18, %19}, db, %46, 0, 0, 1, 1, 1;\n"
    "add.s64 db, %44, %45 + 128;\n"
    "wgmma.mma_async.sp.sync.aligned.m64n32k32.f32.bf16.bf16 {%0, %1, %2, %3, %4, %5, %6, %7, %8, %9, %10, %11, %12, %13, %14, %15}, {%20, %21, %22, %23}, db, %46, 0, 1, 1, 1, 1;\n"
    "add.s64 db, %44, %45 + 256;\n"
    "wgmma.mma_async.sp.sync.aligned.m64n32k32.f32.bf16.bf16 {%0, %1, %2, %3, %4, %5, %6, %7, %8, %9, %10, %11, %12, %13, %14, %15}, {%24, %25, %26, %27}, db, %46, 0, 1, 1, 1, 1;\n"
    "add.s64 db, %44, %45 + 384;\n"
    "wgmma.mma_async.sp.sync.aligned.m64n32k32.f32.bf16.bf16 {%0, %1, %2, %3, %4, %5, %6, %7, %8, %9, %10, %11, %12, %13, %14, %15}, {%28, %29, %30, %31}, db, %46, 0, 1, 1, 1, 1;\n"
    "add.s64 db, %44, %45 + 512;\n"
    "wgmma.mma_async.sp.sync.aligned.m64n32k32.f32.bf16.bf16 {%0, %1, %2, %3, %4, %5, %6, %7, %8, %9, %10, %11, %12, %13, %14, %15}, {%32, %33, %34, %35}, db, %46, 0, 1, 1, 1, 1;\n"
    "add.s64 db, %44, %45 + 640;\n"
    "wgmma.mma_async.sp.sync.aligned.m64n32k32.f32.bf16.bf16 {%0, %1, %2, %3, %4, %5, %6, %7, %8, %9, %10, %11, %12, %13, %14, %15}, {%36, %37, %38, %39}, db, %46, 0, 1, 1, 1, 1;\n"
    "add.s64 db, %44, %45 + 768;\n"
    "wgmma.mma_async.sp.sync.aligned.m64n32k32.f32.bf16.bf16 {%0, %1, %2, %3, %4, %5, %6, %7, %8, %9, %10, %11, %12, %13, %14, %15}, {%40, %41, %42, %43}, db, %46, 0, 1, 1, 1, 1;\n"
    "wgmma.commit_group.sync.aligned;\n}\n"
    : "=f"(d[0]), "=f"(d[1]), "=f"(d[2]), "=f"(d[3]), "=f"(d[4]), "=f"(d[5]), "=f"(d[6]), "=f"(d[7]), "=f"(d[8]), "=f"(d[9]), "=f"(d[10]), "=f"(d[11]), "=f"(d[12]), "=f"(d[13]), "=f"(d[14]), "=f"(d[15])
    : "r"(a[0]), "r"(a[1]), "r"(a[2]), "r"(a[3]), "r"(a[4]), "r"(a[5]), "r"(a[6]), "r"(a[7]), "r"(a[8]), "r"(a[9]), "r"(a[10]), "r"(a[11]), "r"(a[12]), "r"(a[13]), "r"(a[14]), "r"(a[15]), "r"(a[16]), "r"(a[17]), "r"(a[18]), "r"(a[19]), "r"(a[20]), "r"(a[21]), "r"(a[22]), "r"(a[23]), "r"(a[24]), "r"(a[25]), "r"(a[26]), "r"(a[27]), "l"(db), "n"(D), "r"(meta)
    : "memory");
}
template<int D> __device__ __forceinline__ void c2_more(float (&d)[16], const uint32_t (&a)[28], uint64_t db, uint32_t meta) {
  asm volatile("{\n.reg .b64 db;\n"
    "wgmma.fence.sync.aligned;\n"
    "add.s64 db, %44, %45 + 0;\n"
    "wgmma.mma_async.sp.sync.aligned.m64n32k32.f32.bf16.bf16 {%0, %1, %2, %3, %4, %5, %6, %7, %8, %9, %10, %11, %12, %13, %14, %15}, {%16, %17, %18, %19}, db, %46, 0, 1, 1, 1, 1;\n"
    "add.s64 db, %44, %45 + 128;\n"
    "wgmma.mma_async.sp.sync.aligned.m64n32k32.f32.bf16.bf16 {%0, %1, %2, %3, %4, %5, %6, %7, %8, %9, %10, %11, %12, %13, %14, %15}, {%20, %21, %22, %23}, db, %46, 0, 1, 1, 1, 1;\n"
    "add.s64 db, %44, %45 + 256;\n"
    "wgmma.mma_async.sp.sync.aligned.m64n32k32.f32.bf16.bf16 {%0, %1, %2, %3, %4, %5, %6, %7, %8, %9, %10, %11, %12, %13, %14, %15}, {%24, %25, %26, %27}, db, %46, 0, 1, 1, 1, 1;\n"
    "add.s64 db, %44, %45 + 384;\n"
    "wgmma.mma_async.sp.sync.aligned.m64n32k32.f32.bf16.bf16 {%0, %1, %2, %3, %4, %5, %6, %7, %8, %9, %10, %11, %12, %13, %14, %15}, {%28, %29, %30, %31}, db, %46, 0, 1, 1, 1, 1;\n"
    "add.s64 db, %44, %45 + 512;\n"
    "wgmma.mma_async.sp.sync.aligned.m64n32k32.f32.bf16.bf16 {%0, %1, %2, %3, %4, %5, %6, %7, %8, %9, %10, %11, %12, %13, %14, %15}, {%32, %33, %34, %35}, db, %46, 0, 1, 1, 1, 1;\n"
    "add.s64 db, %44, %45 + 640;\n"
    "wgmma.mma_async.sp.sync.aligned.m64n32k32.f32.bf16.bf16 {%0, %1, %2, %3, %4, %5, %6, %7, %8, %9, %10, %11, %12, %13, %14, %15}, {%36, %37, %38, %39}, db, %46, 0, 1, 1, 1, 1;\n"
    "add.s64 db, %44, %45 + 768;\n"
    "wgmma.mma_async.sp.sync.aligned.m64n32k32.f32.bf16.bf16 {%0, %1, %2, %3, %4, %5, %6, %7, %8, %9, %10, %11, %12, %13, %14, %15}, {%40, %41, %42, %43}, db, %46, 0, 1, 1, 1, 1;\n"
    "wgmma.commit_group.sync.aligned;\n}\n"
    : "+f"(d[0]), "+f"(d[1]), "+f"(d[2]), "+f"(d[3]), "+f"(d[4]), "+f"(d[5]), "+f"(d[6]), "+f"(d[7]), "+f"(d[8]), "+f"(d[9]), "+f"(d[10]), "+f"(d[11]), "+f"(d[12]), "+f"(d[13]), "+f"(d[14]), "+f"(d[15])
    : "r"(a[0]), "r"(a[1]), "r"(a[2]), "r"(a[3]), "r"(a[4]), "r"(a[5]), "r"(a[6]), "r"(a[7]), "r"(a[8]), "r"(a[9]), "r"(a[10]), "r"(a[11]), "r"(a[12]), "r"(a[13]), "r"(a[14]), "r"(a[15]), "r"(a[16]), "r"(a[17]), "r"(a[18]), "r"(a[19]), "r"(a[20]), "r"(a[21]), "r"(a[22]), "r"(a[23]), "r"(a[24]), "r"(a[25]), "r"(a[26]), "r"(a[27]), "l"(db), "n"(D), "r"(meta)
    : "memory");
}
template<int N> __device__ __forceinline__ void mma_wait(float (&d)[4]) {
  asm volatile("wgmma.wait_group.sync.aligned %4;"
    : "+f"(d[0]), "+f"(d[1]), "+f"(d[2]), "+f"(d[3])
    : "n"(N) : "memory");
}
template<int N> __device__ __forceinline__ void mma_wait(float (&d)[16]) {
  asm volatile("wgmma.wait_group.sync.aligned %16;"
    : "+f"(d[0]), "+f"(d[1]), "+f"(d[2]), "+f"(d[3]), "+f"(d[4]), "+f"(d[5]), "+f"(d[6]), "+f"(d[7]), "+f"(d[8]), "+f"(d[9]), "+f"(d[10]), "+f"(d[11]), "+f"(d[12]), "+f"(d[13]), "+f"(d[14]), "+f"(d[15])
    : "n"(N) : "memory");
}
template<int N> __device__ __forceinline__ void mma_wait(float (&d)[20]) {
  asm volatile("wgmma.wait_group.sync.aligned %20;"
    : "+f"(d[0]), "+f"(d[1]), "+f"(d[2]), "+f"(d[3]), "+f"(d[4]), "+f"(d[5]), "+f"(d[6]), "+f"(d[7]), "+f"(d[8]), "+f"(d[9]), "+f"(d[10]), "+f"(d[11]), "+f"(d[12]), "+f"(d[13]), "+f"(d[14]), "+f"(d[15]), "+f"(d[16]), "+f"(d[17]), "+f"(d[18]), "+f"(d[19])
    : "n"(N) : "memory");
}
template<int N> __device__ __forceinline__ void mma_wait(float (&d)[24]) {
  asm volatile("wgmma.wait_group.sync.aligned %24;"
    : "+f"(d[0]), "+f"(d[1]), "+f"(d[2]), "+f"(d[3]), "+f"(d[4]), "+f"(d[5]), "+f"(d[6]), "+f"(d[7]), "+f"(d[8]), "+f"(d[9]), "+f"(d[10]), "+f"(d[11]), "+f"(d[12]), "+f"(d[13]), "+f"(d[14]), "+f"(d[15]), "+f"(d[16]), "+f"(d[17]), "+f"(d[18]), "+f"(d[19]), "+f"(d[20]), "+f"(d[21]), "+f"(d[22]), "+f"(d[23])
    : "n"(N) : "memory");
}
template<int N> __device__ __forceinline__ void mma_wait(float (&d)[28]) {
  asm volatile("wgmma.wait_group.sync.aligned %28;"
    : "+f"(d[0]), "+f"(d[1]), "+f"(d[2]), "+f"(d[3]), "+f"(d[4]), "+f"(d[5]), "+f"(d[6]), "+f"(d[7]), "+f"(d[8]), "+f"(d[9]), "+f"(d[10]), "+f"(d[11]), "+f"(d[12]), "+f"(d[13]), "+f"(d[14]), "+f"(d[15]), "+f"(d[16]), "+f"(d[17]), "+f"(d[18]), "+f"(d[19]), "+f"(d[20]), "+f"(d[21]), "+f"(d[22]), "+f"(d[23]), "+f"(d[24]), "+f"(d[25]), "+f"(d[26]), "+f"(d[27])
    : "n"(N) : "memory");
}
template<int N> __device__ __forceinline__ void mma_wait(float (&d)[32]) {
  asm volatile("wgmma.wait_group.sync.aligned %32;"
    : "+f"(d[0]), "+f"(d[1]), "+f"(d[2]), "+f"(d[3]), "+f"(d[4]), "+f"(d[5]), "+f"(d[6]), "+f"(d[7]), "+f"(d[8]), "+f"(d[9]), "+f"(d[10]), "+f"(d[11]), "+f"(d[12]), "+f"(d[13]), "+f"(d[14]), "+f"(d[15]), "+f"(d[16]), "+f"(d[17]), "+f"(d[18]), "+f"(d[19]), "+f"(d[20]), "+f"(d[21]), "+f"(d[22]), "+f"(d[23]), "+f"(d[24]), "+f"(d[25]), "+f"(d[26]), "+f"(d[27]), "+f"(d[28]), "+f"(d[29]), "+f"(d[30]), "+f"(d[31])
    : "n"(N) : "memory");
}
template<int N> __device__ __forceinline__ void mma_wait(float (&d)[36]) {
  asm volatile("wgmma.wait_group.sync.aligned %36;"
    : "+f"(d[0]), "+f"(d[1]), "+f"(d[2]), "+f"(d[3]), "+f"(d[4]), "+f"(d[5]), "+f"(d[6]), "+f"(d[7]), "+f"(d[8]), "+f"(d[9]), "+f"(d[10]), "+f"(d[11]), "+f"(d[12]), "+f"(d[13]), "+f"(d[14]), "+f"(d[15]), "+f"(d[16]), "+f"(d[17]), "+f"(d[18]), "+f"(d[19]), "+f"(d[20]), "+f"(d[21]), "+f"(d[22]), "+f"(d[23]), "+f"(d[24]), "+f"(d[25]), "+f"(d[26]), "+f"(d[27]), "+f"(d[28]), "+f"(d[29]), "+f"(d[30]), "+f"(d[31]), "+f"(d[32]), "+f"(d[33]), "+f"(d[34]), "+f"(d[35])
    : "n"(N) : "memory");
}
template<int N> __device__ __forceinline__ void mma_wait(float (&d)[40]) {
  asm volatile("wgmma.wait_group.sync.aligned %40;"
    : "+f"(d[0]), "+f"(d[1]), "+f"(d[2]), "+f"(d[3]), "+f"(d[4]), "+f"(d[5]), "+f"(d[6]), "+f"(d[7]), "+f"(d[8]), "+f"(d[9]), "+f"(d[10]), "+f"(d[11]), "+f"(d[12]), "+f"(d[13]), "+f"(d[14]), "+f"(d[15]), "+f"(d[16]), "+f"(d[17]), "+f"(d[18]), "+f"(d[19]), "+f"(d[20]), "+f"(d[21]), "+f"(d[22]), "+f"(d[23]), "+f"(d[24]), "+f"(d[25]), "+f"(d[26]), "+f"(d[27]), "+f"(d[28]), "+f"(d[29]), "+f"(d[30]), "+f"(d[31]), "+f"(d[32]), "+f"(d[33]), "+f"(d[34]), "+f"(d[35]), "+f"(d[36]), "+f"(d[37]), "+f"(d[38]), "+f"(d[39])
    : "n"(N) : "memory");
}
template<int N> __device__ __forceinline__ void mma_wait(float (&d)[44]) {
  asm volatile("wgmma.wait_group.sync.aligned %44;"
    : "+f"(d[0]), "+f"(d[1]), "+f"(d[2]), "+f"(d[3]), "+f"(d[4]), "+f"(d[5]), "+f"(d[6]), "+f"(d[7]), "+f"(d[8]), "+f"(d[9]), "+f"(d[10]), "+f"(d[11]), "+f"(d[12]), "+f"(d[13]), "+f"(d[14]), "+f"(d[15]), "+f"(d[16]), "+f"(d[17]), "+f"(d[18]), "+f"(d[19]), "+f"(d[20]), "+f"(d[21]), "+f"(d[22]), "+f"(d[23]), "+f"(d[24]), "+f"(d[25]), "+f"(d[26]), "+f"(d[27]), "+f"(d[28]), "+f"(d[29]), "+f"(d[30]), "+f"(d[31]), "+f"(d[32]), "+f"(d[33]), "+f"(d[34]), "+f"(d[35]), "+f"(d[36]), "+f"(d[37]), "+f"(d[38]), "+f"(d[39]), "+f"(d[40]), "+f"(d[41]), "+f"(d[42]), "+f"(d[43])
    : "n"(N) : "memory");
}
__device__ __forceinline__ void mma_fence() { asm volatile("wgmma.fence.sync.aligned;" ::: "memory"); }

__device__ __forceinline__ uint32_t smem_u32(const void* p) { return (uint32_t)__cvta_generic_to_shared(p); }

__device__ __forceinline__ void mbar_init(uint32_t bar, uint32_t cnt) {
  asm volatile("mbarrier.init.shared::cta.b64 [%0], %1;" :: "r"(bar), "r"(cnt) : "memory");
}
__device__ __forceinline__ void mbar_arrive(uint32_t bar) {
  asm volatile("mbarrier.arrive.shared::cta.b64 _, [%0];" :: "r"(bar) : "memory");
}
__device__ __forceinline__ void mbar_wait(uint32_t bar, uint32_t parity) {
  asm volatile("{\n.reg .pred p;\n.reg .u32 n;\n"
               "mov.u32 n, 0;\n"
               "WAIT_LOOP:\n"
               "mbarrier.try_wait.parity.shared::cta.b64 p, [%0], %1;\n"
               "@p bra.uni WAIT_DONE;\n"
               "add.u32 n, n, 1;\n"
               "setp.lt.u32 p, n, 0x1000000;\n"
               "@p bra.uni WAIT_LOOP;\n"
               "trap;\n"
               "WAIT_DONE:\n}\n"
               :: "r"(bar), "r"(parity) : "memory");
}
__device__ __forceinline__ void mbar_wait_unless(uint32_t ok, uint32_t bar, uint32_t parity) {
  asm volatile("{\n.reg .pred p;\n.reg .u32 n;\n"
               "setp.ne.u32 p, %2, 0;\n"
               "@p bra.uni WAIT_DONE;\n"
               "mov.u32 n, 0;\n"
               "WAIT_LOOP:\n"
               "mbarrier.try_wait.parity.shared::cta.b64 p, [%0], %1;\n"
               "@p bra.uni WAIT_DONE;\n"
               "add.u32 n, n, 1;\n"
               "setp.lt.u32 p, n, 0x1000000;\n"
               "@p bra.uni WAIT_LOOP;\n"
               "trap;\n"
               "WAIT_DONE:\n}\n"
               :: "r"(bar), "r"(parity), "r"(ok) : "memory");
}
__device__ __forceinline__ uint32_t mbar_test(uint32_t bar, uint32_t parity) {
  uint32_t ok;
  asm volatile("{\n.reg .pred p;\nmbarrier.test_wait.parity.shared::cta.b64 p, [%1], %2;\nselp.u32 %0, 1, 0, p;\n}\n"
               : "=r"(ok) : "r"(bar), "r"(parity) : "memory");
  return ok;
}
__device__ __forceinline__ void cp_async16(uint32_t dst, const void* src) {
  asm volatile("cp.async.cg.shared.global [%0], [%1], 16;" :: "r"(dst), "l"(src) : "memory");
}
#define DIN_ADDR4                                                                        \
  "mov.b64 {x, y}, %0;\ndp4a.u32.u32 x, %8, 0x80, %11;\nmov.b64 %0, {x, y};\n"           \
  "mov.b64 {x, y}, %1;\ndp4a.u32.u32 x, %8, 0x8000, %11;\nmov.b64 %1, {x, y};\n"         \
  "mov.b64 {x, y}, %2;\ndp4a.u32.u32 x, %8, 0x800000, %11;\nmov.b64 %2, {x, y};\n"       \
  "mov.b64 {x, y}, %3;\ndp4a.u32.u32 x, %8, 0x80000000, %11;\nmov.b64 %3, {x, y};\n"
template<int T>
__device__ __forceinline__ void cp_group(const uint32_t (&dst)[4], uint64_t (&a)[4], uint32_t rows4, uint32_t base, uint64_t pol) {
  asm volatile("{\n.reg .u32 x, y;\n" DIN_ADDR4
               "cp.async.cg.shared.global.L2::cache_hint [%4 + %10], [%0], 16, %9;\n"
               "cp.async.cg.shared.global.L2::cache_hint [%5 + %10], [%1], 16, %9;\n"
               "cp.async.cg.shared.global.L2::cache_hint [%6 + %10], [%2], 16, %9;\n"
               "cp.async.cg.shared.global.L2::cache_hint [%7 + %10], [%3], 16, %9;\n}\n"
               : "+l"(a[0]), "+l"(a[1]), "+l"(a[2]), "+l"(a[3])
               : "r"(dst[0]), "r"(dst[1]), "r"(dst[2]), "r"(dst[3]), "r"(rows4), "l"(pol), "n"(T * 2048), "r"(base) : "memory");
}
template<int T>
__device__ __forceinline__ void cp_group_z(const uint32_t (&dst)[4], uint64_t (&a)[4], uint32_t rows4, uint32_t base, int left, uint64_t pol) {
  asm volatile("{\n.reg .u32 x, y;\n.reg .pred p0, p1, p2, p3;\n" DIN_ADDR4
               "setp.le.s32 p0, %12, %13;\nsetp.le.s32 p1, %12, %13 + 1;\nsetp.le.s32 p2, %12, %13 + 2;\nsetp.le.s32 p3, %12, %13 + 3;\n"
               "cp.async.cg.shared.global.L2::cache_hint [%4 + %10], [%0], 16, p0, %9;\n"
               "cp.async.cg.shared.global.L2::cache_hint [%5 + %10], [%1], 16, p1, %9;\n"
               "cp.async.cg.shared.global.L2::cache_hint [%6 + %10], [%2], 16, p2, %9;\n"
               "cp.async.cg.shared.global.L2::cache_hint [%7 + %10], [%3], 16, p3, %9;\n}\n"
               : "+l"(a[0]), "+l"(a[1]), "+l"(a[2]), "+l"(a[3])
               : "r"(dst[0]), "r"(dst[1]), "r"(dst[2]), "r"(dst[3]), "r"(rows4), "l"(pol), "n"(T * 2048), "r"(base),
                 "r"(left), "n"(T * 16) : "memory");
}
__device__ __forceinline__ uint32_t prmt(uint32_t a, uint32_t b, uint32_t sel) {
  uint32_t d;
  asm("prmt.b32 %0, %1, %2, %3;" : "=r"(d) : "r"(a), "r"(b), "r"(sel));
  return d;
}
__device__ __forceinline__ uint32_t ballot_bit(uint32_t x, uint32_t bit) {
  uint32_t d;
  asm volatile("{\n.reg .pred p;\n.reg .u32 t;\nand.b32 t, %1, %2;\nsetp.ne.u32 p, t, 0;\nvote.sync.ballot.b32 %0, p, 0xffffffff;\n}\n"
               : "=r"(d) : "r"(x), "r"(bit));
  return d;
}
__device__ __forceinline__ uint4 load_mask(const void* mask, uint32_t b, uint32_t i) {
  uint4 m;
  asm volatile("ld.global.nc.L1::no_allocate.v4.u32 {%0,%1,%2,%3}, [%4];"
               : "=r"(m.x), "=r"(m.y), "=r"(m.z), "=r"(m.w) : "l"(reinterpret_cast<const uint4*>(mask) + (b * 25u + i)));
  return m;
}
__device__ __forceinline__ uint32_t nonzero_as_one(uint32_t x) {
  uint32_t d;
  asm("set.neu.bf16x2.bf16x2 %0, %1, %2;" : "=r"(d) : "r"(x), "r"(0u));
  return d;
}
__device__ __forceinline__ void cp_async_arrive_noinc(uint32_t bar) {
  asm volatile("cp.async.mbarrier.arrive.noinc.shared::cta.b64 [%0];" :: "r"(bar) : "memory");
}
__device__ __forceinline__ void ldsm_x4(uint32_t addr, uint32_t& r0, uint32_t& r1, uint32_t& r2, uint32_t& r3) {
  asm volatile("ldmatrix.sync.aligned.m8n8.x4.shared.b16 {%0,%1,%2,%3}, [%4];"
               : "=r"(r0), "=r"(r1), "=r"(r2), "=r"(r3) : "r"(addr) : "memory");
}
__device__ __forceinline__ void ldsm_x4_t(uint32_t addr, uint32_t& r0, uint32_t& r1, uint32_t& r2, uint32_t& r3) {
  asm volatile("ldmatrix.sync.aligned.m8n8.x4.trans.shared.b16 {%0,%1,%2,%3}, [%4];"
               : "=r"(r0), "=r"(r1), "=r"(r2), "=r"(r3) : "r"(addr) : "memory");
}
__device__ __forceinline__ void stsm_x4(uint32_t addr, uint32_t r0, uint32_t r1, uint32_t r2, uint32_t r3) {
  asm volatile("stmatrix.sync.aligned.m8n8.x4.shared.b16 [%0], {%1,%2,%3,%4};"
               :: "r"(addr), "r"(r0), "r"(r1), "r"(r2), "r"(r3) : "memory");
}
__device__ __forceinline__ void stsm_x2(uint32_t addr, uint32_t r0, uint32_t r1) {
  asm volatile("stmatrix.sync.aligned.m8n8.x2.shared.b16 [%0], {%1,%2};"
               :: "r"(addr), "r"(r0), "r"(r1) : "memory");
}
__device__ __forceinline__ void mma_bf16(float (&c)[4], const uint32_t (&a)[4], uint32_t b) {
  asm("mma.sync.aligned.m16n8k16.row.col.f32.bf16.bf16.f32 {%0,%1,%2,%3}, {%4,%5,%6,%7}, {%8,%8}, {%0,%1,%2,%3};"
      : "+f"(c[0]), "+f"(c[1]), "+f"(c[2]), "+f"(c[3]) : "r"(a[0]), "r"(a[1]), "r"(a[2]), "r"(a[3]), "r"(b));
}
__device__ __forceinline__ uint32_t hfma2_bf16(uint32_t a, uint32_t b, uint32_t c) {
  uint32_t d;
  asm volatile("fma.rn.bf16x2 %0, %1, %2, %3;" : "=r"(d) : "r"(a), "r"(b), "r"(c));
  return d;
}
__device__ __forceinline__ uint32_t pack_bf16(float lo, float hi) {
  uint32_t d;
  asm("cvt.rn.bf16x2.f32 %0, %1, %2;" : "=r"(d) : "f"(hi), "f"(lo));
  return d;
}
__device__ __forceinline__ uint32_t lds32(uint32_t a) {
  uint32_t v; asm volatile("ld.shared.u32 %0, [%1];" : "=r"(v) : "r"(a) : "memory"); return v;
}
__device__ __forceinline__ uint32_t lds16(uint32_t a) {
  uint32_t v; asm volatile("ld.shared.u16 %0, [%1];" : "=r"(v) : "r"(a) : "memory"); return v;
}
__device__ __forceinline__ void sts32(uint32_t a, uint32_t v) {
  asm volatile("st.shared.u32 [%0], %1;" :: "r"(a), "r"(v) : "memory");
}
__device__ __forceinline__ void sts16(uint32_t a, uint32_t v) {
  asm volatile("st.shared.u16 [%0], %1;" :: "r"(a), "h"((unsigned short)v) : "memory");
}
__device__ __forceinline__ void sts8(uint32_t a, uint32_t v) {
  asm volatile("st.shared.u8 [%0], %1;" :: "r"(a), "r"(v) : "memory");
}
constexpr uint32_t DESC_ROWS = 0x40000040u, DESC_HALVES = 0x80000020u;
__device__ __forceinline__ uint32_t desc_lo(uint32_t addr) { return ((addr & 0x3FFFF) >> 4) | (1u << 16); }

__device__ __forceinline__ uint4 lds128(uint32_t a) {
  uint4 v;
  asm volatile("ld.shared.v4.u32 {%0,%1,%2,%3}, [%4];" : "=r"(v.x), "=r"(v.y), "=r"(v.z), "=r"(v.w) : "r"(a) : "memory");
  return v;
}
__device__ __forceinline__ void sts128(uint32_t a, uint4 v) {
  asm volatile("st.shared.v4.u32 [%0], {%1,%2,%3,%4};" :: "r"(a), "r"(v.x), "r"(v.y), "r"(v.z), "r"(v.w) : "memory");
}
__device__ __forceinline__ void prefetch_l2(const void* p, uint32_t bytes) {
  asm volatile("cp.async.bulk.prefetch.L2.global [%0], %1;" :: "l"(p), "r"(bytes) : "memory");
}

template<int ND>
__device__ __forceinline__ void tanh_groups(float (&d)[ND], int i0, int i1) {
#pragma unroll
  for (int i = 4 * i0; i < 4 * i1; i++) asm volatile("tanh.approx.f32 %0, %0;" : "+f"(d[i ^ 2]));
}
template<int ND>
__device__ __forceinline__ uint32_t mix(const float (&d)[ND], int i, float w2a, float w2b, float c32) {
  uint32_t p;
  asm volatile("{\n.reg .f32 x, y;\nfma.rn.f32 x, %3, %6, %7;\nfma.rn.f32 y, %4, %6, %7;\n"
               "fma.rn.f32 x, %1, %5, x;\nfma.rn.f32 y, %2, %5, y;\ncvt.rn.bf16x2.f32 %0, y, x;\n}\n"
               : "=r"(p) : "f"(d[4 * i]), "f"(d[4 * i + 1]), "f"(d[4 * i + 2]), "f"(d[4 * i + 3]), "f"(w2a), "f"(w2b), "f"(c32));
  return p;
}
template<int K> __device__ __forceinline__ uint32_t keep(uint32_t x) { return K ? __shfl_sync(0xffffffffu, x, 0) : x; }
template<int V> struct Int { static constexpr int value = V; };

__global__ void __launch_bounds__(NTHREADS, 1)
din_kernel(const __nv_bfloat16* __restrict__ mask, const __nv_bfloat16* __restrict__ target, int B, int grid,
           uint32_t pf_mask, uint32_t pf_tgt, const __nv_bfloat16* __restrict__ w1, const __nv_bfloat16* __restrict__ hist,
           const __nv_bfloat16* __restrict__ b1, const __nv_bfloat16* __restrict__ w2,
           const __nv_bfloat16* __restrict__ b2, __nv_bfloat16* __restrict__ out, unsigned int* counter, int pace,
           int slow_from, int pace_slow, int spread) {
  {
    const char* pm = reinterpret_cast<const char*>(mask) + (size_t)blockIdx.x * pf_mask;
    const char* pt = reinterpret_cast<const char*>(target) + (size_t)blockIdx.x * pf_tgt;
    const uint32_t o = threadIdx.x * 128;
    asm volatile("{\n.reg .pred p;\nsetp.lt.u32 p, %1, %2;\n@p prefetch.global.L2 [%0];\n}\n" :: "l"(pm + o), "r"(o), "r"(pf_mask));
    asm volatile("{\n.reg .pred p;\nsetp.lt.u32 p, %1, %2;\n@p prefetch.global.L2 [%0];\n}\n" :: "l"(pt + o), "r"(o), "r"(pf_tgt));
  }
  extern __shared__ unsigned char smem_raw[];
  const uint32_t sb = (smem_u32(smem_raw) + 1023u) & ~1023u;
  const int tid = threadIdx.x, lane = tid & 31;
  const int warp = __shfl_sync(0xffffffffu, tid >> 5, 0);
#define ACT NCW
  const int bstep = ACT * grid;

  STAMP(0);
  if (warp < NCW * 4) {
    const int wg = warp >> 2, w = warp & 3;
    const int g = lane >> 2;
    const uint32_t ring = sb + wg * RING_BYTES;
    const bool active = wg * grid + (int)blockIdx.x < B && wg < ACT;
    {
      const int t = tid & 127;
      const uint32_t dst = sb + ((t ^ ((t >> 3) & 7)) << 4);
      const char* src = reinterpret_cast<const char*>(w1) + t * 16;
#pragma unroll
      for (int i = 0; i < 4; i++) cp_async16(dst + w1_at(i) + wg * 2048, src + i * 8192 + wg * 2048);
      cp_async16(dst + w1_at(0) + (wg >> 1) * RING_BYTES + (wg & 1) * SLOT_BYTES + 6144, src + wg * 8192 + 6144);
      if (wg == 0) cp_async16(dst + w1_at(3) + 6144, src + 3 * 8192 + 6144);
      if (lane < 8) {
        if (w == 0 && active) cp_async16(ring + R_TGT0 + lane * 16, target + (size_t)(wg * grid + blockIdx.x) * kD + lane * 8);
        if (w == 1 && wg < 2) cp_async16(ring + R_VEC + lane * 16, (wg ? w2 : b1) + lane * 8);
      }
    }
    if (w == 2) sts32(ring + R_SEL + lane * 4, 0x3f803f80u);
    uint32_t rb2;
    asm volatile("ld.global.nc.u16 %0, [%1];" : "=r"(rb2) : "l"(b2));
    asm volatile("setmaxnreg.inc.sync.aligned.u32 %0;" :: "n"(CONS_REGS));
    asm volatile("cp.async.wait_all;" ::: "memory");
    STAMP(5);
    asm volatile("bar.sync 1, %0;" :: "n"(NCW * 160) : "memory");
    const uint32_t half2 = 0x3f003f00u, nhalf2 = 0xbf00bf00u, nzero2 = 0x80008000u;
    const uint32_t vec = sb + R_VEC + (16 * w + g) * 2;
    const float w2a = 0.5f * __uint_as_float(lds16(vec + RING_BYTES) << 16);
    const float w2b = 0.5f * __uint_as_float(lds16(vec + RING_BYTES + 16) << 16);
    const uint32_t rw2 = lds32(sb + RING_BYTES + R_VEC + lane * 4);
    float c32 = __uint_as_float(rw2 << 16) + __uint_as_float(rw2 & 0xffff0000u);
#pragma unroll
    for (int o = 16; o; o >>= 1) c32 += __shfl_xor_sync(0xffffffffu, c32, o);
    c32 = (0.5f * c32 + __uint_as_float(rb2 << 16)) * (1.0f / 32.0f);
    uint32_t bq[4];
    bq[2] = hfma2_bf16(lds16(vec), half2, nzero2);
    bq[3] = hfma2_bf16(lds16(vec + 16), half2, nzero2);
    if (lane & 3) bq[2] = bq[3] = 0;
    uint32_t wac[16], wd[16], wbc[16];
    {
      const int mi = lane >> 3, rr = lane & 7;
      const uint32_t a0 = sb + (8 * (mi >> 1) + rr) * 128 + (((2 * w + (mi & 1)) ^ rr) << 4);
#pragma unroll
      for (int ks = 0; ks < 4; ks++) {
        uint32_t A[4], Bm[4], C[4], Dm[4];
        ldsm_x4_t(a0 + ks * 2048 + w1_at(0), A[0], A[1], A[2], A[3]);
        ldsm_x4_t(a0 + ks * 2048 + w1_at(1), Bm[0], Bm[1], Bm[2], Bm[3]);
        ldsm_x4_t(a0 + ks * 2048 + w1_at(2), C[0], C[1], C[2], C[3]);
        ldsm_x4_t(a0 + ks * 2048 + w1_at(3), Dm[0], Dm[1], Dm[2], Dm[3]);
#pragma unroll
        for (int e = 0; e < 4; e++) {
          wac[4 * ks + e] = hfma2_bf16(A[e], half2, hfma2_bf16(C[e], half2, nzero2));
          wbc[4 * ks + e] = hfma2_bf16(Bm[e], half2, hfma2_bf16(C[e], nhalf2, nzero2));
          wd[4 * ks + e] = hfma2_bf16(Dm[e], half2, nzero2);
        }
      }
    }
    asm volatile("fence.proxy.async.shared::cta;" ::: "memory");
    asm volatile("bar.sync 5, %0;" :: "n"(NCW * 128) : "memory");

    const uint32_t ln = __shfl_sync(0xffffffffu, lane, lane);
    const uint32_t q0 = __shfl_sync(0xffffffffu, (lane & 3) ? 0u : 0xffffffffu, lane);
    const uint32_t meta = __shfl_sync(0xffffffffu, 0x88dddd88u + (grid >> 20), lane);
    const uint32_t zr = grid >> 20;
    const uint32_t sel = keep<K_SEL>(((ring + R_SEL) & 0x3FFFF) >> 4);
    const uint32_t ost = __shfl_sync(0xffffffffu, PK == 2 ? w * 1024 + lane * 16 : PK ? w * 1024 + (lane ^ (w & 1) * 2) * 16 : w * 2048 + lane * 16, lane);
    const uint32_t first = keep<K_FIRST>(ring);
    const uint32_t last = keep<K_LAST>(first + (NSLOT - 1) * SLOT_BYTES);
    uint32_t sa = first, phase = 0;
    uint32_t we[16];
    auto make_weff = [&](uint32_t ta) {
      uint32_t t[8];
      ta += (ln & 24) << 1;
      ldsm_x4(ta, t[0], t[1], t[2], t[3]);
      ldsm_x4(ta + 64, t[4], t[5], t[6], t[7]);
#pragma unroll
      for (int i = 0; i < 16; i++) we[i] = hfma2_bf16(t[i >> 1], wd[i], wac[i]);
    };
    auto make_bq = [&](const float (&bz)[4]) {
#pragma unroll
      for (int e = 0; e < 2; e++) {
        const uint32_t v = __float_as_uint(bz[2 * e]) & q0;
        const float hi = __uint_as_float(v & 0xffff0000u);
        bq[e] = pack_bf16(__uint_as_float(v) - hi, hi);
      }
    };
    if (active) {
      {
        float bz[4];
        uint64_t d0 = (uint64_t)DESC_ROWS << 32 | (ring + R_TGT0) >> 4;
        mma_fence();
        cbias<0>(bz, wbc, d0);
        make_weff(ring + R_TGT0);
        mma_wait<0>(bz);
        make_bq(bz);
      }
      STAMP(1);
      uint32_t raw = 0, cur = ring, hdr = 0;
#pragma unroll 1
      for (uint32_t pass = WARM ? zr : 1; pass < 2; pass++) {
      if (pass) {
      if (!LC) { mbar_wait(ring + S_FULL, 0); raw = lds32(ring + S_HDR); }
      uint32_t full = 0;
      while (true) {
        hdr = __shfl_sync(0xffffffffu, raw, 0);
        cur = sa;
        auto chunk = [&](auto groups) {
          constexpr int N8 = decltype(groups)::value, NA = N8 < KV || NX < 5 ? NX : 5, NY = N8 - NA, S1 = N8 < KV || NX < 5 ? SA : 2;
          constexpr int KT = (N8 + 1) / 2, E2 = KT - (N8 < KV ? KL : 3), E1 = E2 - (N8 < KV ? KM : 0), E0 = K0 && N8 < KV && K0 < E1 ? K0 : E1;
          constexpr int MF = N8 < KV ? ME : 0;
          float x[4 * NA], y[4 * NY], bz[4], o[16];
          uint32_t a[4 * E0], a1[E1 > E0 ? 4 * (E1 - E0) : 4], a2[E2 > E1 ? 4 * (E2 - E1) : 4], a3[4 * (KT - E2)];
          auto M = [&](int i0, int i1) {
#pragma unroll
            for (int i = i0; i < i1; i++) {
              uint32_t p = i < NA ? mix(x, i, w2a, w2b, c32) : i < N8 ? mix(y, i - NA, w2a, w2b, c32) : 0;
              if (N8 == 16) {
                uint32_t m = 0x3f803f80u;
                asm volatile("{\n.reg .pred p;\nsetp.ne.u32 p, %1, 0;\n@p ld.shared.u32 %0, [%2];\n}\n"
                             : "+r"(m) : "r"(hdr & H_GENERAL), "r"(cur + S_MASK + i * 16 + (ln & 3) * 4) : "memory");
                p = hfma2_bf16(p, m, 0x80008000u);
              }
              if (i < 2 * E0) a[2 * i] = a[2 * i + 1] = p;
              else if (i < 2 * E1) a1[2 * i - 4 * E0] = a1[2 * i - 4 * E0 + 1] = p;
              else if (i < 2 * E2) a2[2 * i - 4 * E1] = a2[2 * i - 4 * E1 + 1] = p;
              else a3[2 * i - 4 * E2] = a3[2 * i - 4 * E2 + 1] = p;
            }
          };
          int done = 0;
          auto T = [&](int upto) {
            upto = upto < 4 * NY ? upto : 4 * NY;
#pragma unroll
            for (int i = done; i < upto; i++) asm volatile("tanh.approx.f32 %0, %0;" : "+f"(y[i ^ 2]));
            done = upto > done ? upto : done;
          };
          auto pin4 = [&](uint32_t r0, uint32_t r1, uint32_t r2, uint32_t r3) {
            asm volatile("{\n.reg .pred p;\nsetp.ne.u32 p, %4, 0;\n@p st.shared.v4.u32 [%4], {%0,%1,%2,%3};\n}\n"
                         :: "r"(r0), "r"(r1), "r"(r2), "r"(r3), "r"(zr) : "memory");
          };
          uint64_t d1 = (uint64_t)(DESC_ROWS + (cur >> 24)) << 32 | ((cur >> 4) - DOFF);
          const uint32_t par = phase;
          phase ^= sa == last;
          sa = sa == last ? first : sa + SLOT_BYTES;
          mma_fence();
          sel_clr(x, bq, sel, 0);
          sel_clr(y, bq, sel, NY == NA ? zr : 0);
          if (EA) mbar_wait_unless(full, cur + S_FULL, par);
          else mbar_wait(cur + S_FULL, par);
          LOGT(0);
          DURT(sub);
          mma_fence();
          c1_acc<DOFF>(x, we, d1);
          if (SPLIT) {
            cbias<DOFF + S_TGT / 16>(bz, wbc, d1);
            mma_wait<1>(x);
            auto TX = [&](int i0, int i1) {
#pragma unroll
              for (int i = i0; i < i1; i++) asm volatile("tanh.approx.f32 %0, %0;" : "+f"(x[i ^ 2]));
            };
            auto PX = [&](int i0, int i1) {
#pragma unroll
              for (int i = i0; i < i1; i += 4) pin4(__float_as_uint(x[i]), __float_as_uint(x[i + 1]), __float_as_uint(x[i + 2]), __float_as_uint(x[i + 3]));
            };
            if (EARLY) {
              TX(0, 4 * S1 - EARLY);
              const uint32_t ok = mbar_test(cur + S_REST, par);
              TX(4 * S1 - EARLY, 4 * S1);
              M(0, MF);
              mbar_wait_unless(ok, cur + S_REST, par);
            } else {
              TX(0, 4 * S1);
              mbar_wait(cur + S_REST, par);
            }
            LOGT(2);
            mma_fence();
            c1_acc<DOFF + 64 * NA>(y, we, d1);
            TX(4 * S1, 4 * (S1 + SB));
            if (__builtin_expect(zr != 0, 0)) {
              __nanosleep(zr);
#pragma unroll
              for (int i = 4 * (S1 + SB); i < 4 * NA; i++) asm volatile("mov.b32 %0, %1;" : "=f"(x[i]) : "r"(ln));
            }
            if (BQE) { mma_wait<1>(bz); make_bq(bz); }
            TX(4 * (S1 + SB), 4 * NA);
          } else {
            c1_acc<DOFF + 64 * NA>(y, we, d1);
            mma_wait<1>(x);
            cbias<DOFF + S_TGT / 16>(bz, wbc, d1);
            tanh_groups(x, 0, NA);
          }
          constexpr bool GE = G0 && 2 * E0 <= NA && N8 < KV;
          constexpr int MX = N8 >= KV ? NA - 1 : GE ? 2 * E0 : NA - 1 < 2 * E0 ? NA - 1 : 2 * E0;
          M(MF, MX);
          asm volatile("{\n.reg .b32 lo, hi;\nmov.b64 {lo, hi}, %0;\nadd.u32 hi, hi, %1;\nmov.b64 %0, {lo, hi};\n}\n" : "+l"(d1) : "n"(DESC_HALVES - DESC_ROWS));
          auto after = [&](uint32_t g) {
            asm volatile("{\n.reg .b32 lo, hi, z;\n.reg .pred p;\nand.b32 z, %1, %2;\nsetp.ne.u32 p, z, 0;\nvote.sync.ballot.b32 z, p, 0xffffffff;\n"
                         "mov.b64 {lo, hi}, %0;\nadd.u32 " GATE_HALF ", z;\nmov.b64 %0, {lo, hi};\n}\n" : "+l"(d1) : "r"(g), "r"(zr));
          };
          auto any = [&](auto& v, int n) { return v[n - 2] | v[n - 4] | (n > 4 ? v[n - 6] : 0) | (n > 4 && GW4 ? v[n - 8] : 0); };
          if (GE) {
            c2_first<DOFF>(o, a, d1, meta);
            mma_wait<1>(y);
            if (WP == 0) make_weff(cur + S_TGT);
          } else {
            if (__builtin_expect(zr != 0, 0)) {
              __nanosleep(zr);
#pragma unroll
              for (int i = 2 * MF; i < 2 * MX; i += 2) sts32(zr + i, a[i]);
#pragma unroll
              for (int i = 4 * MX; i < 4 * NA; i++) sts32(zr + i, __float_as_uint(x[i]));
            }
            mma_wait<SPLIT ? 0 : 1>(y);
            T(4 * (2 * E0 - NA));
            if (WP == 0) make_weff(cur + S_TGT);
            M(MX, 2 * E0);
            if (GA & 1) after(any(a, 4 * E0));
            c2_first<DOFF>(o, a, d1, meta);
          }
          if (WP == 1) make_weff(cur + S_TGT);
          if constexpr (E1 > E0) {
            T(4 * (2 * E1 - NA));
            M(2 * E0, 2 * E1);
            if (GA & 2) after(any(a1, 4 * (E1 - E0)));
            c2_more<DOFF + 128 * E0>(o, a1, d1, meta);
          }
          if (WP == 2) make_weff(cur + S_TGT);
          if constexpr (E2 > E1) {
            T(4 * (2 * E2 - NA));
            M(2 * E1, 2 * E2);
            if (GA & 4) after(any(a2, 4 * (E2 - E1)));
            c2_more<DOFF + 128 * E1>(o, a2, d1, meta);
          }
          if (TP) {
            T(4 * (NY - TP));
            M(2 * E2, N8 - TP - 1);
            if (__builtin_expect(zr != 0, 0)) {
              __nanosleep(zr);
#pragma unroll
              for (int i = 0; i < 16; i++) sts32(zr + i, we[i]);
#pragma unroll
              for (int i = 2 * E2; i < N8 - TP - 1; i++) { sts32(zr + i, a3[2 * i - 4 * E2]); asm volatile("mov.b32 %0, %1;" : "=r"(a3[2 * i - 4 * E2 + 1]) : "r"(ln)); }
#pragma unroll
              for (int i = 4 * (NY - TP - 1); i < 4 * (NY - TP); i++) sts32(zr + i, __float_as_uint(y[i]));
#pragma unroll
              for (int i = 4 * (NY - TP); i < 4 * NY; i++) asm volatile("mov.b32 %0, %1;" : "=f"(y[i]) : "r"(ln));
            }
            T(4 * NY);
            M(N8 - TP - 1, 2 * KT);
          } else {
          T(4 * NY);
          M(2 * E2, 2 * KT);
          }
          c2_more<DOFF + 128 * E2>(o, a3, d1, meta);
          if (!(SPLIT && BQE)) {
          mma_wait<2 + (E1 > E0) + (E2 > E1)>(bz);
          make_bq(bz);
          }
          raw = lds32(sa + S_HDR);
          if (LC) raw = (raw >> 31) == phase ? 0 : raw;
          if (EA) full = mbar_test(sa + S_FULL, phase);
          mma_wait<0>(o);
#pragma unroll
          for (int j = 0; j < 2; j++)
            stsm_x4(cur + S_OUT + j * 512 + ost, pack_bf16(o[8 * j], o[8 * j + 2]), pack_bf16(o[8 * j + 1], o[8 * j + 3]),
                    pack_bf16(o[8 * j + 4], o[8 * j + 6]), pack_bf16(o[8 * j + 5], o[8 * j + 7]));
          if (LC) {
            LOGT(1);
            __syncwarp();
            asm volatile("{\n.reg .pred p;\nsetp.eq.u32 p, %1, 0;\n@p mbarrier.arrive.shared::cta.b64 _, [%0];\n}\n"
                         :: "r"(cur + S_EMPTY), "r"(ln | (hdr & H_SELF)) : "memory");
          }
        };
        if (hdr & 0x2000) { chunk(Int<13>()); if (hdr & H_FINAL) break; }
        else if (hdr & (V11 ? 0x1000 : 0x1fff)) { chunk(Int<12>()); if (hdr & H_FINAL) break; }
        else if (hdr & 0x4000) { chunk(Int<14>()); if (hdr & H_FINAL) break; }
        else if (V15 && (hdr & 0x8000)) { chunk(Int<15>()); if (hdr & H_FINAL) break; }
        else if (V11 && (hdr & 0xfff)) { chunk(Int<11>()); if (hdr & H_FINAL) break; }
        else if (hdr) { chunk(Int<16>()); if (hdr & H_FINAL) break; }
        else {
          uint32_t spins = 0;
          do {
            if (++spins > 0x1000000) __trap();
            __nanosleep(32);
            raw = lds32(sa + S_HDR);
          } while ((raw >> 31) == phase);
        }
        continue;
        LOGT(1);
        if (hdr & H_FINAL) break;
        __syncwarp();
        if (ln == 0) mbar_arrive(cur + S_EMPTY);
        for (uint32_t spins = 0; (raw >> 31) == phase; spins++) {
          if (spins > 0x1000000) __trap();
          __nanosleep(32);
          raw = lds32(sa + S_HDR);
        }
      }
      }
      asm volatile("bar.sync %0, 128;" :: "r"(2 + wg) : "memory");
      const uint32_t ra = cur + S_OUT + w * 256 + (ln >> 4) * 1024 + (ln & 15) * 16;
      uint32_t f0[4], f1[4];
      ldsm_x4_t(ra, f0[0], f0[1], f0[2], f0[3]);
      ldsm_x4_t(ra + 2048, f1[0], f1[1], f1[2], f1[3]);
      uint32_t* dst = reinterpret_cast<uint32_t*>(out) + (lds32(cur + S_ROW + (hdr >> 31) * 4) * 32u + 4 * w + (ln & 4) * 4 + (ln >> 3));
      float c0[4] = {0.f, 0.f, 0.f, 0.f}, c1[4] = {0.f, 0.f, 0.f, 0.f};
      mma_bf16(c0, f0, 0x3f803f80u);
      mma_bf16(c1, f1, 0x3f803f80u);
      asm volatile("{\n.reg .pred p;\nsetp.lt.u32 p, %2, %3;\n@p st.global.u32 [%0], %1;\n}\n"
                   :: "l"(dst), "r"(pack_bf16(c0[0] + c1[0], c0[2] + c1[2])), "r"(ln & 3), "r"(hdr & H_SELF ? 1 : 0) : "memory");
      if (!LC && !(hdr & H_SELF) && ln == 0) mbar_arrive(cur + S_EMPTY);
      }
    }
    STAMP(4);
  } else {
    const int pw = warp - NCW * 4;
    const uint32_t ring = sb + pw * RING_BYTES;
    asm volatile("setmaxnreg.dec.sync.aligned.u32 %0;" :: "n"(PROD_REGS));
    if (pw < NCW) {
      int b = pw * grid + blockIdx.x, bn = b + bstep;
      uint4 mw = load_mask(mask, min(b, B - 1), min(lane, 24));
      if (lane == 0) {
#pragma unroll
        for (int i = 0; i < NSLOT; i++) {
          mbar_init(ring + i * SLOT_BYTES + S_FULL, 33);
          mbar_init(ring + i * SLOT_BYTES + S_REST, 33);
          mbar_arrive(ring + i * SLOT_BYTES + S_REST);
          mbar_init(ring + i * SLOT_BYTES + S_EMPTY, 4);
          sts32(ring + i * SLOT_BYTES + S_HDR, 0);
        }
        sts32(ring + R_STOP, b < B && pw < ACT ? 0 : ring);
      }
      sts32(sb + R_PACE + lane * 4, 0);
      asm volatile("bar.arrive 1, %0;" :: "n"(NCW * 160) : "memory");
      asm volatile("bar.arrive 6, 128;" ::: "memory");
      if (pw >= ACT) return;
      const uint32_t list = ring + R_LIST;
      uint32_t lt;
      asm("mov.u32 %0, %%lanemask_lt;" : "=r"(lt));
      const uint32_t ln = __shfl_sync(0xffffffffu, lane, lane);
      const uint32_t r4 = (ln >> 3) * 4, c16 = (ln & 7) * 16, l25 = min(ln, 24u);
      const uint32_t pick = ln < 25 ? 0xeca8 : 0x9999;
      uint32_t dst[4];
#pragma unroll
      for (int i = 0; i < 4; i++) dst[i] = ring + (r4 + i) * 128 + (c16 ^ (((r4 + i) & 7) << 4));
      uint64_t pol;
      asm("createpolicy.fractional.L2::evict_first.b64 %0, 1.0;" : "=l"(pol));
      uint32_t sa = ring, phase = 1;
      const uint32_t wrap = (uint32_t)(max(B - NSTATIC * bstep, 0) + bstep - 1);
      auto next_slot = [&]() {
        const bool wrapped = sa == ring + (NSLOT - 1) * SLOT_BYTES;
        const int step = wrapped ? -(NSLOT - 1) * SLOT_BYTES : SLOT_BYTES;
        sa += step;
        phase ^= wrapped;
#pragma unroll
        for (int i = 0; i < 4; i++) dst[i] += step;
      };
      uint32_t claimer = ln;
      uint32_t drawn, started = 0;
      auto draw = [&]() {
        drawn = B;
        asm volatile("{\n.reg .pred p;\nsetp.eq.u32 p, %3, 0;\n@p atom.global.inc.u32 %0, [%1], %2;\n}\n"
                     : "+r"(drawn) : "l"(counter), "r"(wrap), "r"(claimer) : "memory");
      };
      if (b >= B) draw();
      while (b < B) {
        const uint32_t e0 = nonzero_as_one(mw.x), e1 = nonzero_as_one(mw.y);
        const uint32_t e2 = nonzero_as_one(mw.z), e3 = nonzero_as_one(mw.w);
        const uint32_t nonbin = (e0 ^ mw.x) | (e1 ^ mw.y) | (e2 ^ mw.z) | (e3 ^ mw.w);
        const uint32_t sA = prmt(e0, e1, pick), sB = prmt(e2, e3, pick);
        const uint32_t pA = (sA & 0x01010101u) * 0x01010101u;
        const uint32_t pB = ((sB & 0x01010101u) + (pA >> 24)) * 0x01010101u;
        uint32_t pos = 0;
        int n = 0;
#pragma unroll
        for (int k = 0; k < 4; k++) {
          const uint32_t bal = ballot_bit(pB, 0x01000000u << k);
          pos += __popc(bal & lt) << k;
          n += __popc(bal) << k;
        }
        const uint32_t general = __any_sync(0xffffffffu, nonbin != 0);
        const uint32_t aA = (pA + pos * 0x01010101u) | ~sA, aB = (pB + pos * 0x01010101u) | ~sB;
#pragma unroll
        for (int i = 0; i < 8; i++) sts8(list - 1 + prmt(i < 4 ? aA : aB, 0, 0x4440 + (i & 3)), 8 * ln + i);
        __syncwarp();

        const uint64_t src = reinterpret_cast<uint64_t>(hist) + (uint64_t)b * (kL * kD * 2);
        const bool no_carry = (uint32_t)src <= 0xffffffffu - kL * kD * 2;
        auto begin_fill = [&](uint32_t h, uint32_t part, int nc, int bt, auto extra) {
          LOGT(0);
          mbar_wait(sa + S_EMPTY, phase);
          if (bt >= B) {
            h |= H_FINAL;
            if (!part) { h |= H_SELF; sts32(ring + R_STOP, sa + (phase ^ 1)); }
          }
          extra();
          sts32(sa + S_HDR, h | phase << 31);
          sts32(sa + S_ROW + phase * 4, b | part);
          asm volatile("{\n.reg .pred p;\nsetp.eq.u32 p, %1, 0;\n@p mbarrier.arrive.shared::cta.b64 _, [%0];\n}\n"
                       :: "r"(sa + S_FULL), "r"(ln) : "memory");
          asm volatile("{\n.reg .u32 f, c;\n.reg .s32 d;\n.reg .pred p;\n"
                       "mov.u32 c, %%globaltimer_lo;\n"
                       "red.shared.max.u32 [%1], c;\n"
                       "atom.shared.add.u32 f, [%1], %2;\n"
                       "shfl.sync.idx.b32 f, f, 0, 31, 0xffffffff;\n"
                       "mov.u32 %0, f;\n"
                       "SPIN:\n"
                       "mov.u32 c, %%globaltimer_lo;\n"
                       "sub.s32 d, c, f;\n"
                       "setp.gt.u32 p, d, %3;\n"
                       "@p bra.uni SPIN;\n}\n" : "=r"(started) : "r"(sb + R_PACE + ln * 4), "r"(nc * (bn >= slow_from ? pace_slow : pace) >> 4), "r"(~(pace * (CHUNK / 4))) : "memory");
          if (!(part & ROW_REST)) {
            mw = load_mask(mask, min(bn, B - 1), l25);
            draw();
          }
          LOGT(1);
          asm volatile("cp.async.ca.shared.global [%0], [%1], 4;"
                       :: "r"(sa + S_TGT + ln * 4), "l"(reinterpret_cast<const uint32_t*>(target) + ((uint32_t)min(bt, B - 1) * 32u + ln)) : "memory");
        };
        auto end_fill = [&](int nc) {
          cp_async_arrive_noinc(sa + (SPLIT ? S_REST : S_FULL));
          next_slot();
          LOGT(2);
        };
        if (__builtin_expect(no_carry && !general, 1)) {
          int nc = n <= CHUNK ? n : n <= 160 ? 64 : 96;
          uint32_t la = list + r4, part = n <= CHUNK ? 0 : ROW_MORE;
#pragma unroll 1
          while (true) {
            uint32_t idx[7];
#pragma unroll
            for (int t = 0; t < 7; t++) idx[t] = lds32(la + t * 16);
            begin_fill(1u << ((nc + 7) >> 3), part, nc, part == ROW_MORE ? b : bn, [](){});
            const int left = nc - r4;
            const uint32_t base = (uint32_t)src + c16;
            uint64_t a[4];
            a[0] = a[1] = a[2] = a[3] = (uint64_t)((uint32_t)(src >> 32) + (ln >> 5)) << 32;
            if (__builtin_expect(nc >= 64, 1)) {
              cp_group<0>(dst, a, idx[0], base, pol);
              cp_group<1>(dst, a, idx[1], base, pol);
              if (NX > 4) cp_group<2>(dst, a, idx[2], base, pol);
              if (NX > 6) cp_group<3>(dst, a, idx[3], base, pol);
              if (SPLIT) cp_async_arrive_noinc(sa + S_FULL);
              asm volatile("{\n.reg .u32 c;\n.reg .s32 d;\n.reg .pred p;\n"
                           "SPIN:\n"
                           "mov.u32 c, %%globaltimer_lo;\n"
                           "sub.s32 d, c, %0;\n"
                           "setp.lt.u32 p, d, %1;\n"
                           "@p bra.uni SPIN;\n}\n" :: "r"(started), "r"(bn >= slow_from ? spread : 0) : "memory");
              if (NX <= 4) cp_group<2>(dst, a, idx[2], base, pol);
              if (NX <= 6) cp_group<3>(dst, a, idx[3], base, pol);
              cp_group_z<4>(dst, a, idx[4], base, left, pol);
              cp_group_z<5>(dst, a, idx[5], base, left, pol);
              if (nc > 96) {
                cp_group_z<6>(dst, a, idx[6], base, left, pol);
                if (nc > 112) cp_group_z<7>(dst, a, lds32(la + 112), base, left, pol);
              }
            } else {
              cp_group_z<0>(dst, a, idx[0], base, left, pol);
              cp_group_z<1>(dst, a, idx[1], base, left, pol);
              cp_group_z<2>(dst, a, idx[2], base, left, pol);
              cp_group_z<3>(dst, a, idx[3], base, left, pol);
              if (SPLIT) cp_async_arrive_noinc(sa + S_FULL);
              cp_group_z<4>(dst, a, 0, base, left, pol);
              cp_group_z<5>(dst, a, 0, base, left, pol);
            }
            end_fill(nc);
            if (part != ROW_MORE) break;
            la += nc;
            nc = n - nc;
            part = ROW_REST;
          }
        } else {
          int r0 = 0;
#pragma unroll 1
          do {
            const int nc = min(n - r0, CHUNK);
            const bool more = r0 + CHUNK < n;
            begin_fill(general ? H_GENERAL : 1u << ((nc + 7) >> 3), (more ? ROW_MORE : 0u) | (r0 ? ROW_REST : 0u), nc, more ? b : bn, [&]() {
#pragma unroll 1
              for (int z = ln; general && z < CHUNK; z += 32) {
                uint32_t v = 0;
                if (z < nc) {
                  uint32_t row;
                  asm volatile("ld.shared.u8 %0, [%1];" : "=r"(row) : "r"(list + r0 + z) : "memory");
                  v = __bfloat16_as_ushort(mask[(size_t)b * kL + row]);
                }
                sts16(sa + S_MASK + z * 2, v);
              }
              __syncwarp();
            });
#pragma unroll 1
            for (int z = r4 >> 2; z < CHUNK; z += 4) {
              uint32_t row;
              asm volatile("ld.shared.u8 %0, [%1];" : "=r"(row) : "r"(list + r0 + z) : "memory");
              asm volatile("cp.async.cg.shared.global [%0], [%1], 16, %2;"
                           :: "r"(sa + z * 128 + (c16 ^ ((z & 7) << 4))), "l"(src + c16 + (z < nc ? row : 0) * 128),
                              "r"(z < nc ? 16 : 0) : "memory");
            }
            if (SPLIT) cp_async_arrive_noinc(sa + S_FULL);
            end_fill(nc);
            r0 += CHUNK;
          } while (r0 < n);
        }
        b = bn;
        bn = __shfl_sync(0xffffffffu, drawn, 0) + NSTATIC * bstep;
        if (bn >= B) claimer = 1;
      }
      STAMP(3);
      if (lds32(ring + R_STOP) == 0) sts32(ring + R_STOP, sa + (phase ^ 1));
      asm volatile("cp.async.wait_all;" ::: "memory");
      STAMP(4);
    } else {
      uint32_t due = clock();
      int s0 = NSTATIC * bstep + (PF_EARLY * grid + blockIdx.x) * PF_ROWS;
      auto prefetch = [&]() {
        const int cnt = min(PF_ROWS, B - s0);
        if (lane == 0) {
          prefetch_l2(mask + (size_t)s0 * kL, cnt * kL * 2);
          prefetch_l2(target + (size_t)s0 * kD, cnt * kD * 2);
        }
        s0 += grid * PF_ROWS;
      };
#pragma unroll 1
      for (int j = PF_EARLY; j < PF_FAST && s0 < B; j++) {
        while ((int)(due - (uint32_t)clock()) > 0) {}
        prefetch();
        due += PF_CYCLES;
      }
      due += (PF_FAST - 1) * PF_SLOW - (PF_FAST - PF_EARLY) * PF_CYCLES + (blockIdx.x & 255) * (PF_SLOW / 256);
      asm volatile("bar.sync 6, 128;" ::: "memory");
      const uint32_t ln = __shfl_sync(0xffffffffu, lane, lane);
      const uint32_t home = sb + min(ln, NCW - 1u) * RING_BYTES;
      uint32_t mine = ln < NCW ? home : 0;
      const uint32_t rd = __shfl_sync(0xffffffffu, S_OUT + (lane >> 4) * 1024 + (lane & 15) * 16, lane);
      const uint32_t word = __shfl_sync(0xffffffffu, (lane & 4) * 4 + (lane & 3) * 4 + (lane >> 3), lane);
      uint32_t idle = 0, r = 0, at;
      auto poll = [&]() {
        uint32_t ready;
        asm volatile("{\n.reg .pred p;\nsetp.ne.u32 p, %3, 0;\n@p mbarrier.test_wait.parity.shared::cta.b64 p, [%1], %2;\n"
                     "vote.sync.ballot.b32 %0, p, 0xffffffff;\n}\n"
                     : "=r"(ready) : "r"((mine & ~1u) + S_EMPTY), "r"(mine & 1), "r"(mine) : "memory");
        static_assert(NCW == 3, "");
        const uint32_t pick = ((r == 0 ? 0x5a53u : r == 1 ? 0xaa13u : 0x1213u) >> (2 * ready)) & 3;
        at = __shfl_sync(0xffffffffu, mine, pick);
        r = ready ? pick : r;
      };
      poll();
#pragma unroll 1
      while (true) {
        if (at) {
          const uint32_t sa = at & ~1u, carry = sb + r * RING_BYTES + R_CARRY + ln * 8;
          uint32_t f[8][4];
#pragma unroll
          for (int i = 0; i < 8; i++) ldsm_x4_t(sa + rd + (i >> 2) * 2048 + (i & 3) * 256, f[i][0], f[i][1], f[i][2], f[i][3]);
          const uint32_t row = lds32(sa + S_ROW + 4 - (at & 1) * 4);
          if (ln == r) mine = sa == home + (NSLOT - 1) * SLOT_BYTES ? (at - (NSLOT - 1) * SLOT_BYTES) ^ 1 : at + SLOT_BYTES;
          float c[8][4];
#pragma unroll
          for (int i = 0; i < 8; i++) {
            c[i][0] = c[i][1] = c[i][2] = c[i][3] = 0.f;
            mma_bf16(c[i], f[i], 0x3f803f80u);
          }
          poll();
          asm volatile("{\n.reg .pred p;\nsetp.eq.u32 p, %1, 0;\n@p mbarrier.arrive.shared::cta.b64 _, [%0];\n}\n"
                       :: "r"(sa + S_REST), "r"(ln) : "memory");
          float e[2];
#pragma unroll
          for (int k = 0; k < 2; k++) {
            const float u0 = ln & 1 ? c[1][2 * k] : c[0][2 * k], u1 = ln & 1 ? c[3][2 * k] : c[2][2 * k];
            const float u2 = ln & 1 ? c[5][2 * k] : c[4][2 * k], u3 = ln & 1 ? c[7][2 * k] : c[6][2 * k];
            e[k] = ln & 2 ? u1 + u3 : u0 + u2;
          }
          asm volatile("{\n.reg .pred p, q;\n.reg .f32 a, b;\n.reg .u32 t;\nshr.u32 t, %3, 30;\nsetp.eq.u32 p, t, 1;\nsetp.eq.u32 q, t, 2;\n"
                       "@p ld.shared.v2.f32 {a, b}, [%2];\n@p add.f32 %0, %0, a;\n@p add.f32 %1, %1, b;\n@q st.shared.v2.f32 [%2], {%0, %1};\n}\n"
                       : "+f"(e[0]), "+f"(e[1]) : "r"(carry), "r"(row) : "memory");
          asm volatile("{\n.reg .pred p;\nsetp.ge.s32 p, %2, 0;\n@p st.global.u32 [%0], %1;\n}\n"
                       :: "l"(reinterpret_cast<uint32_t*>(out) + (row * 32u + word)), "r"(pack_bf16(e[0], e[1])), "r"(row) : "memory");
        } else {
          const uint32_t stop = lds32(home + R_STOP);
          poll();
          if (stop == mine) mine = 0;
          if (!__any_sync(0xffffffffu, mine)) break;
          if (s0 < B) {
            if ((int)(due - (uint32_t)clock()) <= 0) { prefetch(); due += PF_SLOW; }
          } else if (++idle > 0x10000000) __trap();
          if (RED_SLEEP) __nanosleep(RED_SLEEP);
        }
      }
      STAMP(4);
    }
  }
}

}

extern "C" void kernel_launch(void* const* d_in, const int* in_sizes, int n_in, void* d_out, int out_size) {
  const __nv_bfloat16* target = (const __nv_bfloat16*)d_in[0];
  const __nv_bfloat16* hist = (const __nv_bfloat16*)d_in[1];
  const __nv_bfloat16* mask = (const __nv_bfloat16*)d_in[2];
  const __nv_bfloat16* w1 = (const __nv_bfloat16*)d_in[3];
  const __nv_bfloat16* b1 = (const __nv_bfloat16*)d_in[4];
  const __nv_bfloat16* w2 = (const __nv_bfloat16*)d_in[5];
  const __nv_bfloat16* b2 = (const __nv_bfloat16*)d_in[6];
  const int B = in_sizes[0] / din::kD;
  if (B <= 0) return;
  static int sms = 0, pace = 0;
  static unsigned int* counter = nullptr;
  if (sms == 0) {
    int dev = 0, khz = 0, bits = 0;
    cudaGetDevice(&dev);
    cudaDeviceGetAttribute(&sms, cudaDevAttrMultiProcessorCount, dev);
    cudaDeviceGetAttribute(&khz, cudaDevAttrMemoryClockRate, dev);
    cudaDeviceGetAttribute(&bits, cudaDevAttrGlobalMemoryBusWidth, dev);
    if (khz > 0 && bits > 0) pace = (int)(16.0 * 128.0 * sms / (khz * 1e-6 * 2.0 * bits / 8.0));
    if (pace > 256) pace = 0;
    cudaGetSymbolAddress((void**)&counter, din::g_next);
    cudaFuncSetAttribute(din::din_kernel, cudaFuncAttributeMaxDynamicSharedMemorySize, din::SMEM_BYTES);
  }
  const long long early = (long long)(din::NSTATIC * NCW + PF_EARLY * PF_ROWS) * sms, line = 128LL * sms;
  long long pf_mask = (early * din::kL * 2 + line - 1) / line, pf_tgt = early * din::kD * 2 / line;
  if (pf_mask > (long long)B * din::kL * 2 / line) pf_mask = (long long)B * din::kL * 2 / line;
  if (pf_tgt > (long long)B * din::kD * 2 / line) pf_tgt = (long long)B * din::kD * 2 / line;
  din::din_kernel<<<sms, din::NTHREADS, din::SMEM_BYTES>>>(mask, target, B, sms, (uint32_t)pf_mask * 128, (uint32_t)pf_tgt * 128,
                                                          w1, hist, b1, w2, b2, (__nv_bfloat16*)d_out, counter, pace,
                                                          B - SLOW_ROUNDS * NCW * sms / 2, pace + (pace * SLOW_BY + 40) / 80,
                                                          pace * SPREAD / 16);
}
```

```cpp
#include <cuda_runtime.h>
#include <cuda_bf16.h>
#include <stdint.h>

namespace din {

constexpr int kL = 200, kD = 64;
#define NCW 3
#define NSLOT 3
constexpr int CHUNK = 128;
constexpr int NTHREADS = NCW * 128 + 128;
#define PREGS 56
#define CREGS 152
constexpr int PROD_REGS = PREGS, CONS_REGS = CREGS;
#define PF_ROWS 8
#define PF_FAST 10
#define PF_SLOW 2000
#define PF_CYCLES 280
#define RED_SLEEP 0
#define KL 2
#define KL14 2
#define K0 3
#define SA 2
#define SB 1
#define TP 3
#define FIN 0
#define SPREAD 72
#define SLOW_ROUNDS 12
#define SLOW_BY 9
#define PF_EARLY 3
constexpr int NSTATIC = 2;
constexpr int S_TGT = CHUNK * 128;
constexpr int S_HDR = S_TGT + 128;
constexpr int S_FULL = S_HDR + 8;
constexpr int S_EMPTY = S_HDR + 16;
constexpr int S_ROW = S_HDR + 24;
constexpr int S_REST = S_HDR + 32;
constexpr int S_MASK = S_TGT + 256;
constexpr int S_OUT = S_TGT + 1024;
constexpr int SLOT_BYTES = S_OUT + 8192;
constexpr int RING_BYTES_ = NSLOT * SLOT_BYTES;
constexpr int R_PACE = 2 * RING_BYTES_ + S_TGT + 768;
constexpr int R_STOP = S_HDR + 44;
constexpr int R_LIST = S_TGT + 512;
constexpr int R_VEC = S_TGT + 768;
constexpr int R_SEL = S_TGT + 896;
constexpr int R_CARRY = SLOT_BYTES + S_TGT + 512;
constexpr int R_TGT0 = (NSLOT - 1) * SLOT_BYTES + S_OUT;
constexpr int RING_BYTES = NSLOT * SLOT_BYTES;
constexpr int SMEM_BYTES = NCW * RING_BYTES + 1024;
__device__ constexpr int w1_at(int i) { return (i >> 1) * RING_BYTES + (i & 1) * SLOT_BYTES + S_OUT; }
#define LOGT(slot)
static_assert(SMEM_BYTES <= 232448, "shared memory");
constexpr uint32_t H_12 = 2, H_13 = 4, H_14 = 8, H_15 = 16, H_16 = 1u << 16;
constexpr uint32_t H_GENERAL = 1u << 17, H_FINAL = 1u << 18, H_SELF = 1u << 19;
constexpr uint32_t ROW_REST = 1u << 30, ROW_MORE = 1u << 31;

__device__ unsigned int g_next;

#define STAMP(k)

#define STR2(x) #x
#define STR(x) STR2(x)
constexpr int NA = 5;
__device__ __forceinline__ void bias_in(float (&d)[20], const uint32_t (&a)[4], uint32_t lo) {
  asm volatile("{\n.reg .b64 db;\n"
    "cvt.u64.u32 db, %24;\n"
    "wgmma.mma_async.sync.aligned.m64n40k16.f32.bf16.bf16 {%0, %1, %2, %3, %4, %5, %6, %7, %8, %9, %10, %11, %12, %13, %14, %15, %16, %17, %18, %19}, {%20, %21, %22, %23}, db, 0, 1, 1, 0;\n}\n"
    : "=f"(d[0]), "=f"(d[1]), "=f"(d[2]), "=f"(d[3]), "=f"(d[4]), "=f"(d[5]), "=f"(d[6]), "=f"(d[7]), "=f"(d[8]), "=f"(d[9]), "=f"(d[10]), "=f"(d[11]), "=f"(d[12]), "=f"(d[13]), "=f"(d[14]), "=f"(d[15]), "=f"(d[16]), "=f"(d[17]), "=f"(d[18]), "=f"(d[19])
    : "r"(a[0]), "r"(a[1]), "r"(a[2]), "r"(a[3]), "r"(lo)
    : "memory");
}
__device__ __forceinline__ void bias_in(float (&d)[28], const uint32_t (&a)[4], uint32_t lo) {
  asm volatile("{\n.reg .b64 db;\n"
    "cvt.u64.u32 db, %32;\n"
    "wgmma.mma_async.sync.aligned.m64n56k16.f32.bf16.bf16 {%0, %1, %2, %3, %4, %5, %6, %7, %8, %9, %10, %11, %12, %13, %14, %15, %16, %17, %18, %19, %20, %21, %22, %23, %24, %25, %26, %27}, {%28, %29, %30, %31}, db, 0, 1, 1, 0;\n}\n"
    : "=f"(d[0]), "=f"(d[1]), "=f"(d[2]), "=f"(d[3]), "=f"(d[4]), "=f"(d[5]), "=f"(d[6]), "=f"(d[7]), "=f"(d[8]), "=f"(d[9]), "=f"(d[10]), "=f"(d[11]), "=f"(d[12]), "=f"(d[13]), "=f"(d[14]), "=f"(d[15]), "=f"(d[16]), "=f"(d[17]), "=f"(d[18]), "=f"(d[19]), "=f"(d[20]), "=f"(d[21]), "=f"(d[22]), "=f"(d[23]), "=f"(d[24]), "=f"(d[25]), "=f"(d[26]), "=f"(d[27])
    : "r"(a[0]), "r"(a[1]), "r"(a[2]), "r"(a[3]), "r"(lo)
    : "memory");
}
__device__ __forceinline__ void bias_in(float (&d)[32], const uint32_t (&a)[4], uint32_t lo) {
  asm volatile("{\n.reg .b64 db;\n"
    "cvt.u64.u32 db, %36;\n"
    "wgmma.mma_async.sync.aligned.m64n64k16.f32.bf16.bf16 {%0, %1, %2, %3, %4, %5, %6, %7, %8, %9, %10, %11, %12, %13, %14, %15, %16, %17, %18, %19, %20, %21, %22, %23, %24, %25, %26, %27, %28, %29, %30, %31}, {%32, %33, %34, %35}, db, 0, 1, 1, 0;\n}\n"
    : "=f"(d[0]), "=f"(d[1]), "=f"(d[2]), "=f"(d[3]), "=f"(d[4]), "=f"(d[5]), "=f"(d[6]), "=f"(d[7]), "=f"(d[8]), "=f"(d[9]), "=f"(d[10]), "=f"(d[11]), "=f"(d[12]), "=f"(d[13]), "=f"(d[14]), "=f"(d[15]), "=f"(d[16]), "=f"(d[17]), "=f"(d[18]), "=f"(d[19]), "=f"(d[20]), "=f"(d[21]), "=f"(d[22]), "=f"(d[23]), "=f"(d[24]), "=f"(d[25]), "=f"(d[26]), "=f"(d[27]), "=f"(d[28]), "=f"(d[29]), "=f"(d[30]), "=f"(d[31])
    : "r"(a[0]), "r"(a[1]), "r"(a[2]), "r"(a[3]), "r"(lo)
    : "memory");
}
__device__ __forceinline__ void bias_in(float (&d)[36], const uint32_t (&a)[4], uint32_t lo) {
  asm volatile("{\n.reg .b64 db;\n"
    "cvt.u64.u32 db, %40;\n"
    "wgmma.mma_async.sync.aligned.m64n72k16.f32.bf16.bf16 {%0, %1, %2, %3, %4, %5, %6, %7, %8, %9, %10, %11, %12, %13, %14, %15, %16, %17, %18, %19, %20, %21, %22, %23, %24, %25, %26, %27, %28, %29, %30, %31, %32, %33, %34, %35}, {%36, %37, %38, %39}, db, 0, 1, 1, 0;\n}\n"
    : "=f"(d[0]), "=f"(d[1]), "=f"(d[2]), "=f"(d[3]), "=f"(d[4]), "=f"(d[5]), "=f"(d[6]), "=f"(d[7]), "=f"(d[8]), "=f"(d[9]), "=f"(d[10]), "=f"(d[11]), "=f"(d[12]), "=f"(d[13]), "=f"(d[14]), "=f"(d[15]), "=f"(d[16]), "=f"(d[17]), "=f"(d[18]), "=f"(d[19]), "=f"(d[20]), "=f"(d[21]), "=f"(d[22]), "=f"(d[23]), "=f"(d[24]), "=f"(d[25]), "=f"(d[26]), "=f"(d[27]), "=f"(d[28]), "=f"(d[29]), "=f"(d[30]), "=f"(d[31]), "=f"(d[32]), "=f"(d[33]), "=f"(d[34]), "=f"(d[35])
    : "r"(a[0]), "r"(a[1]), "r"(a[2]), "r"(a[3]), "r"(lo)
    : "memory");
}
__device__ __forceinline__ void bias_in(float (&d)[40], const uint32_t (&a)[4], uint32_t lo) {
  asm volatile("{\n.reg .b64 db;\n"
    "cvt.u64.u32 db, %44;\n"
    "wgmma.mma_async.sync.aligned.m64n80k16.f32.bf16.bf16 {%0, %1, %2, %3, %4, %5, %6, %7, %8, %9, %10, %11, %12, %13, %14, %15, %16, %17, %18, %19, %20, %21, %22, %23, %24, %25, %26, %27, %28, %29, %30, %31, %32, %33, %34, %35, %36, %37, %38, %39}, {%40, %41, %42, %43}, db, 0, 1, 1, 0;\n}\n"
    : "=f"(d[0]), "=f"(d[1]), "=f"(d[2]), "=f"(d[3]), "=f"(d[4]), "=f"(d[5]), "=f"(d[6]), "=f"(d[7]), "=f"(d[8]), "=f"(d[9]), "=f"(d[10]), "=f"(d[11]), "=f"(d[12]), "=f"(d[13]), "=f"(d[14]), "=f"(d[15]), "=f"(d[16]), "=f"(d[17]), "=f"(d[18]), "=f"(d[19]), "=f"(d[20]), "=f"(d[21]), "=f"(d[22]), "=f"(d[23]), "=f"(d[24]), "=f"(d[25]), "=f"(d[26]), "=f"(d[27]), "=f"(d[28]), "=f"(d[29]), "=f"(d[30]), "=f"(d[31]), "=f"(d[32]), "=f"(d[33]), "=f"(d[34]), "=f"(d[35]), "=f"(d[36]), "=f"(d[37]), "=f"(d[38]), "=f"(d[39])
    : "r"(a[0]), "r"(a[1]), "r"(a[2]), "r"(a[3]), "r"(lo)
    : "memory");
}
__device__ __forceinline__ void bias_in(float (&d)[44], const uint32_t (&a)[4], uint32_t lo) {
  asm volatile("{\n.reg .b64 db;\n"
    "cvt.u64.u32 db, %48;\n"
    "wgmma.mma_async.sync.aligned.m64n88k16.f32.bf16.bf16 {%0, %1, %2, %3, %4, %5, %6, %7, %8, %9, %10, %11, %12, %13, %14, %15, %16, %17, %18, %19, %20, %21, %22, %23, %24, %25, %26, %27, %28, %29, %30, %31, %32, %33, %34, %35, %36, %37, %38, %39, %40, %41, %42, %43}, {%44, %45, %46, %47}, db, 0, 1, 1, 0;\n}\n"
    : "=f"(d[0]), "=f"(d[1]), "=f"(d[2]), "=f"(d[3]), "=f"(d[4]), "=f"(d[5]), "=f"(d[6]), "=f"(d[7]), "=f"(d[8]), "=f"(d[9]), "=f"(d[10]), "=f"(d[11]), "=f"(d[12]), "=f"(d[13]), "=f"(d[14]), "=f"(d[15]), "=f"(d[16]), "=f"(d[17]), "=f"(d[18]), "=f"(d[19]), "=f"(d[20]), "=f"(d[21]), "=f"(d[22]), "=f"(d[23]), "=f"(d[24]), "=f"(d[25]), "=f"(d[26]), "=f"(d[27]), "=f"(d[28]), "=f"(d[29]), "=f"(d[30]), "=f"(d[31]), "=f"(d[32]), "=f"(d[33]), "=f"(d[34]), "=f"(d[35]), "=f"(d[36]), "=f"(d[37]), "=f"(d[38]), "=f"(d[39]), "=f"(d[40]), "=f"(d[41]), "=f"(d[42]), "=f"(d[43])
    : "r"(a[0]), "r"(a[1]), "r"(a[2]), "r"(a[3]), "r"(lo)
    : "memory");
}
template<int D> __device__ __forceinline__ void gemm1(float (&d)[20], const uint32_t (&a)[16], uint64_t db) {
  asm volatile("{\n.reg .b64 db;\n"
    "add.s64 db, %36, %37 + 0;\n"
    "wgmma.mma_async.sync.aligned.m64n40k16.f32.bf16.bf16 {%0, %1, %2, %3, %4, %5, %6, %7, %8, %9, %10, %11, %12, %13, %14, %15, %16, %17, %18, %19}, {%20, %21, %22, %23}, db, 1, 1, 1, 0;\n"
    "add.s64 db, %36, %37 + 2;\n"
    "wgmma.mma_async.sync.aligned.m64n40k16.f32.bf16.bf16 {%0, %1, %2, %3, %4, %5, %6, %7, %8, %9, %10, %11, %12, %13, %14, %15, %16, %17, %18, %19}, {%24, %25, %26, %27}, db, 1, 1, 1, 0;\n"
    "add.s64 db, %36, %37 + 4;\n"
    "wgmma.mma_async.sync.aligned.m64n40k16.f32.bf16.bf16 {%0, %1, %2, %3, %4, %5, %6, %7, %8, %9, %10, %11, %12, %13, %14, %15, %16, %17, %18, %19}, {%28, %29, %30, %31}, db, 1, 1, 1, 0;\n"
    "add.s64 db, %36, %37 + 6;\n"
    "wgmma.mma_async.sync.aligned.m64n40k16.f32.bf16.bf16 {%0, %1, %2, %3, %4, %5, %6, %7, %8, %9, %10, %11, %12, %13, %14, %15, %16, %17, %18, %19}, {%32, %33, %34, %35}, db, 1, 1, 1, 0;\n"
    "wgmma.commit_group.sync.aligned;\n}\n"
    : "+f"(d[0]), "+f"(d[1]), "+f"(d[2]), "+f"(d[3]), "+f"(d[4]), "+f"(d[5]), "+f"(d[6]), "+f"(d[7]), "+f"(d[8]), "+f"(d[9]), "+f"(d[10]), "+f"(d[11]), "+f"(d[12]), "+f"(d[13]), "+f"(d[14]), "+f"(d[15]), "+f"(d[16]), "+f"(d[17]), "+f"(d[18]), "+f"(d[19])
    : "r"(a[0]), "r"(a[1]), "r"(a[2]), "r"(a[3]), "r"(a[4]), "r"(a[5]), "r"(a[6]), "r"(a[7]), "r"(a[8]), "r"(a[9]), "r"(a[10]), "r"(a[11]), "r"(a[12]), "r"(a[13]), "r"(a[14]), "r"(a[15]), "l"(db), "n"(D)
    : "memory");
}
template<int D> __device__ __forceinline__ void gemm1(float (&d)[28], const uint32_t (&a)[16], uint64_t db) {
  asm volatile("{\n.reg .b64 db;\n"
    "add.s64 db, %44, %45 + 0;\n"
    "wgmma.mma_async.sync.aligned.m64n56k16.f32.bf16.bf16 {%0, %1, %2, %3, %4, %5, %6, %7, %8, %9, %10, %11, %12, %13, %14, %15, %16, %17, %18, %19, %20, %21, %22, %23, %24, %25, %26, %27}, {%28, %29, %30, %31}, db, 1, 1, 1, 0;\n"
    "add.s64 db, %44, %45 + 2;\n"
    "wgmma.mma_async.sync.aligned.m64n56k16.f32.bf16.bf16 {%0, %1, %2, %3, %4, %5, %6, %7, %8, %9, %10, %11, %12, %13, %14, %15, %16, %17, %18, %19, %20, %21, %22, %23, %24, %25, %26, %27}, {%32, %33, %34, %35}, db, 1, 1, 1, 0;\n"
    "add.s64 db, %44, %45 + 4;\n"
    "wgmma.mma_async.sync.aligned.m64n56k16.f32.bf16.bf16 {%0, %1, %2, %3, %4, %5, %6, %7, %8, %9, %10, %11, %12, %13, %14, %15, %16, %17, %18, %19, %20, %21, %22, %23, %24, %25, %26, %27}, {%36, %37, %38, %39}, db, 1, 1, 1, 0;\n"
    "add.s64 db, %44, %45 + 6;\n"
    "wgmma.mma_async.sync.aligned.m64n56k16.f32.bf16.bf16 {%0, %1, %2, %3, %4, %5, %6, %7, %8, %9, %10, %11, %12, %13, %14, %15, %16, %17, %18, %19, %20, %21, %22, %23, %24, %25, %26, %27}, {%40, %41, %42, %43}, db, 1, 1, 1, 0;\n"
    "wgmma.commit_group.sync.aligned;\n}\n"
    : "+f"(d[0]), "+f"(d[1]), "+f"(d[2]), "+f"(d[3]), "+f"(d[4]), "+f"(d[5]), "+f"(d[6]), "+f"(d[7]), "+f"(d[8]), "+f"(d[9]), "+f"(d[10]), "+f"(d[11]), "+f"(d[12]), "+f"(d[13]), "+f"(d[14]), "+f"(d[15]), "+f"(d[16]), "+f"(d[17]), "+f"(d[18]), "+f"(d[19]), "+f"(d[20]), "+f"(d[21]), "+f"(d[22]), "+f"(d[23]), "+f"(d[24]), "+f"(d[25]), "+f"(d[26]), "+f"(d[27])
    : "r"(a[0]), "r"(a[1]), "r"(a[2]), "r"(a[3]), "r"(a[4]), "r"(a[5]), "r"(a[6]), "r"(a[7]), "r"(a[8]), "r"(a[9]), "r"(a[10]), "r"(a[11]), "r"(a[12]), "r"(a[13]), "r"(a[14]), "r"(a[15]), "l"(db), "n"(D)
    : "memory");
}
template<int D> __device__ __forceinline__ void gemm1(float (&d)[32], const uint32_t (&a)[16], uint64_t db) {
  asm volatile("{\n.reg .b64 db;\n"
    "add.s64 db, %48, %49 + 0;\n"
    "wgmma.mma_async.sync.aligned.m64n64k16.f32.bf16.bf16 {%0, %1, %2, %3, %4, %5, %6, %7, %8, %9, %10, %11, %12, %13, %14, %15, %16, %17, %18, %19, %20, %21, %22, %23, %24, %25, %26, %27, %28, %29, %30, %31}, {%32, %33, %34, %35}, db, 1, 1, 1, 0;\n"
    "add.s64 db, %48, %49 + 2;\n"
    "wgmma.mma_async.sync.aligned.m64n64k16.f32.bf16.bf16 {%0, %1, %2, %3, %4, %5, %6, %7, %8, %9, %10, %11, %12, %13, %14, %15, %16, %17, %18, %19, %20, %21, %22, %23, %24, %25, %26, %27, %28, %29, %30, %31}, {%36, %37, %38, %39}, db, 1, 1, 1, 0;\n"
    "add.s64 db, %48, %49 + 4;\n"
    "wgmma.mma_async.sync.aligned.m64n64k16.f32.bf16.bf16 {%0, %1, %2, %3, %4, %5, %6, %7, %8, %9, %10, %11, %12, %13, %14, %15, %16, %17, %18, %19, %20, %21, %22, %23, %24, %25, %26, %27, %28, %29, %30, %31}, {%40, %41, %42, %43}, db, 1, 1, 1, 0;\n"
    "add.s64 db, %48, %49 + 6;\n"
    "wgmma.mma_async.sync.aligned.m64n64k16.f32.bf16.bf16 {%0, %1, %2, %3, %4, %5, %6, %7, %8, %9, %10, %11, %12, %13, %14, %15, %16, %17, %18, %19, %20, %21, %22, %23, %24, %25, %26, %27, %28, %29, %30, %31}, {%44, %45, %46, %47}, db, 1, 1, 1, 0;\n"
    "wgmma.commit_group.sync.aligned;\n}\n"
    : "+f"(d[0]), "+f"(d[1]), "+f"(d[2]), "+f"(d[3]), "+f"(d[4]), "+f"(d[5]), "+f"(d[6]), "+f"(d[7]), "+f"(d[8]), "+f"(d[9]), "+f"(d[10]), "+f"(d[11]), "+f"(d[12]), "+f"(d[13]), "+f"(d[14]), "+f"(d[15]), "+f"(d[16]), "+f"(d[17]), "+f"(d[18]), "+f"(d[19]), "+f"(d[20]), "+f"(d[21]), "+f"(d[22]), "+f"(d[23]), "+f"(d[24]), "+f"(d[25]), "+f"(d[26]), "+f"(d[27]), "+f"(d[28]), "+f"(d[29]), "+f"(d[30]), "+f"(d[31])
    : "r"(a[0]), "r"(a[1]), "r"(a[2]), "r"(a[3]), "r"(a[4]), "r"(a[5]), "r"(a[6]), "r"(a[7]), "r"(a[8]), "r"(a[9]), "r"(a[10]), "r"(a[11]), "r"(a[12]), "r"(a[13]), "r"(a[14]), "r"(a[15]), "l"(db), "n"(D)
    : "memory");
}
template<int D> __device__ __forceinline__ void gemm1(float (&d)[36], const uint32_t (&a)[16], uint64_t db) {
  asm volatile("{\n.reg .b64 db;\n"
    "add.s64 db, %52, %53 + 0;\n"
    "wgmma.mma_async.sync.aligned.m64n72k16.f32.bf16.bf16 {%0, %1, %2, %3, %4, %5, %6, %7, %8, %9, %10, %11, %12, %13, %14, %15, %16, %17, %18, %19, %20, %21, %22, %23, %24, %25, %26, %27, %28, %29, %30, %31, %32, %33, %34, %35}, {%36, %37, %38, %39}, db, 1, 1, 1, 0;\n"
    "add.s64 db, %52, %53 + 2;\n"
    "wgmma.mma_async.sync.aligned.m64n72k16.f32.bf16.bf16 {%0, %1, %2, %3, %4, %5, %6, %7, %8, %9, %10, %11, %12, %13, %14, %15, %16, %17, %18, %19, %20, %21, %22, %23, %24, %25, %26, %27, %28, %29, %30, %31, %32, %33, %34, %35}, {%40, %41, %42, %43}, db, 1, 1, 1, 0;\n"
    "add.s64 db, %52, %53 + 4;\n"
    "wgmma.mma_async.sync.aligned.m64n72k16.f32.bf16.bf16 {%0, %1, %2, %3, %4, %5, %6, %7, %8, %9, %10, %11, %12, %13, %14, %15, %16, %17, %18, %19, %20, %21, %22, %23, %24, %25, %26, %27, %28, %29, %30, %31, %32, %33, %34, %35}, {%44, %45, %46, %47}, db, 1, 1, 1, 0;\n"
    "add.s64 db, %52, %53 + 6;\n"
    "wgmma.mma_async.sync.aligned.m64n72k16.f32.bf16.bf16 {%0, %1, %2, %3, %4, %5, %6, %7, %8, %9, %10, %11, %12, %13, %14, %15, %16, %17, %18, %19, %20, %21, %22, %23, %24, %25, %26, %27, %28, %29, %30, %31, %32, %33, %34, %35}, {%48, %49, %50, %51}, db, 1, 1, 1, 0;\n"
    "wgmma.commit_group.sync.aligned;\n}\n"
    : "+f"(d[0]), "+f"(d[1]), "+f"(d[2]), "+f"(d[3]), "+f"(d[4]), "+f"(d[5]), "+f"(d[6]), "+f"(d[7]), "+f"(d[8]), "+f"(d[9]), "+f"(d[10]), "+f"(d[11]), "+f"(d[12]), "+f"(d[13]), "+f"(d[14]), "+f"(d[15]), "+f"(d[16]), "+f"(d[17]), "+f"(d[18]), "+f"(d[19]), "+f"(d[20]), "+f"(d[21]), "+f"(d[22]), "+f"(d[23]), "+f"(d[24]), "+f"(d[25]), "+f"(d[26]), "+f"(d[27]), "+f"(d[28]), "+f"(d[29]), "+f"(d[30]), "+f"(d[31]), "+f"(d[32]), "+f"(d[33]), "+f"(d[34]), "+f"(d[35])
    : "r"(a[0]), "r"(a[1]), "r"(a[2]), "r"(a[3]), "r"(a[4]), "r"(a[5]), "r"(a[6]), "r"(a[7]), "r"(a[8]), "r"(a[9]), "r"(a[10]), "r"(a[11]), "r"(a[12]), "r"(a[13]), "r"(a[14]), "r"(a[15]), "l"(db), "n"(D)
    : "memory");
}
template<int D> __device__ __forceinline__ void gemm1(float (&d)[40], const uint32_t (&a)[16], uint64_t db) {
  asm volatile("{\n.reg .b64 db;\n"
    "add.s64 db, %56, %57 + 0;\n"
    "wgmma.mma_async.sync.aligned.m64n80k16.f32.bf16.bf16 {%0, %1, %2, %3, %4, %5, %6, %7, %8, %9, %10, %11, %12, %13, %14, %15, %16, %17, %18, %19, %20, %21, %22, %23, %24, %25, %26, %27, %28, %29, %30, %31, %32, %33, %34, %35, %36, %37, %38, %39}, {%40, %41, %42, %43}, db, 1, 1, 1, 0;\n"
    "add.s64 db, %56, %57 + 2;\n"
    "wgmma.mma_async.sync.aligned.m64n80k16.f32.bf16.bf16 {%0, %1, %2, %3, %4, %5, %6, %7, %8, %9, %10, %11, %12, %13, %14, %15, %16, %17, %18, %19, %20, %21, %22, %23, %24, %25, %26, %27, %28, %29, %30, %31, %32, %33, %34, %35, %36, %37, %38, %39}, {%44, %45, %46, %47}, db, 1, 1, 1, 0;\n"
    "add.s64 db, %56, %57 + 4;\n"
    "wgmma.mma_async.sync.aligned.m64n80k16.f32.bf16.bf16 {%0, %1, %2, %3, %4, %5, %6, %7, %8, %9, %10, %11, %12, %13, %14, %15, %16, %17, %18, %19, %20, %21, %22, %23, %24, %25, %26, %27, %28, %29, %30, %31, %32, %33, %34, %35, %36, %37, %38, %39}, {%48, %49, %50, %51}, db, 1, 1, 1, 0;\n"
    "add.s64 db, %56, %57 + 6;\n"
    "wgmma.mma_async.sync.aligned.m64n80k16.f32.bf16.bf16 {%0, %1, %2, %3, %4, %5, %6, %7, %8, %9, %10, %11, %12, %13, %14, %15, %16, %17, %18, %19, %20, %21, %22, %23, %24, %25, %26, %27, %28, %29, %30, %31, %32, %33, %34, %35, %36, %37, %38, %39}, {%52, %53, %54, %55}, db, 1, 1, 1, 0;\n"
    "wgmma.commit_group.sync.aligned;\n}\n"
    : "+f"(d[0]), "+f"(d[1]), "+f"(d[2]), "+f"(d[3]), "+f"(d[4]), "+f"(d[5]), "+f"(d[6]), "+f"(d[7]), "+f"(d[8]), "+f"(d[9]), "+f"(d[10]), "+f"(d[11]), "+f"(d[12]), "+f"(d[13]), "+f"(d[14]), "+f"(d[15]), "+f"(d[16]), "+f"(d[17]), "+f"(d[18]), "+f"(d[19]), "+f"(d[20]), "+f"(d[21]), "+f"(d[22]), "+f"(d[23]), "+f"(d[24]), "+f"(d[25]), "+f"(d[26]), "+f"(d[27]), "+f"(d[28]), "+f"(d[29]), "+f"(d[30]), "+f"(d[31]), "+f"(d[32]), "+f"(d[33]), "+f"(d[34]), "+f"(d[35]), "+f"(d[36]), "+f"(d[37]), "+f"(d[38]), "+f"(d[39])
    : "r"(a[0]), "r"(a[1]), "r"(a[2]), "r"(a[3]), "r"(a[4]), "r"(a[5]), "r"(a[6]), "r"(a[7]), "r"(a[8]), "r"(a[9]), "r"(a[10]), "r"(a[11]), "r"(a[12]), "r"(a[13]), "r"(a[14]), "r"(a[15]), "l"(db), "n"(D)
    : "memory");
}
template<int D> __device__ __forceinline__ void gemm1(float (&d)[44], const uint32_t (&a)[16], uint64_t db) {
  asm volatile("{\n.reg .b64 db;\n"
    "add.s64 db, %60, %61 + 0;\n"
    "wgmma.mma_async.sync.aligned.m64n88k16.f32.bf16.bf16 {%0, %1, %2, %3, %4, %5, %6, %7, %8, %9, %10, %11, %12, %13, %14, %15, %16, %17, %18, %19, %20, %21, %22, %23, %24, %25, %26, %27, %28, %29, %30, %31, %32, %33, %34, %35, %36, %37, %38, %39, %40, %41, %42, %43}, {%44, %45, %46, %47}, db, 1, 1, 1, 0;\n"
    "add.s64 db, %60, %61 + 2;\n"
    "wgmma.mma_async.sync.aligned.m64n88k16.f32.bf16.bf16 {%0, %1, %2, %3, %4, %5, %6, %7, %8, %9, %10, %11, %12, %13, %14, %15, %16, %17, %18, %19, %20, %21, %22, %23, %24, %25, %26, %27, %28, %29, %30, %31, %32, %33, %34, %35, %36, %37, %38, %39, %40, %41, %42, %43}, {%48, %49, %50, %51}, db, 1, 1, 1, 0;\n"
    "add.s64 db, %60, %61 + 4;\n"
    "wgmma.mma_async.sync.aligned.m64n88k16.f32.bf16.bf16 {%0, %1, %2, %3, %4, %5, %6, %7, %8, %9, %10, %11, %12, %13, %14, %15, %16, %17, %18, %19, %20, %21, %22, %23, %24, %25, %26, %27, %28, %29, %30, %31, %32, %33, %34, %35, %36, %37, %38, %39, %40, %41, %42, %43}, {%52, %53, %54, %55}, db, 1, 1, 1, 0;\n"
    "add.s64 db, %60, %61 + 6;\n"
    "wgmma.mma_async.sync.aligned.m64n88k16.f32.bf16.bf16 {%0, %1, %2, %3, %4, %5, %6, %7, %8, %9, %10, %11, %12, %13, %14, %15, %16, %17, %18, %19, %20, %21, %22, %23, %24, %25, %26, %27, %28, %29, %30, %31, %32, %33, %34, %35, %36, %37, %38, %39, %40, %41, %42, %43}, {%56, %57, %58, %59}, db, 1, 1, 1, 0;\n"
    "wgmma.commit_group.sync.aligned;\n}\n"
    : "+f"(d[0]), "+f"(d[1]), "+f"(d[2]), "+f"(d[3]), "+f"(d[4]), "+f"(d[5]), "+f"(d[6]), "+f"(d[7]), "+f"(d[8]), "+f"(d[9]), "+f"(d[10]), "+f"(d[11]), "+f"(d[12]), "+f"(d[13]), "+f"(d[14]), "+f"(d[15]), "+f"(d[16]), "+f"(d[17]), "+f"(d[18]), "+f"(d[19]), "+f"(d[20]), "+f"(d[21]), "+f"(d[22]), "+f"(d[23]), "+f"(d[24]), "+f"(d[25]), "+f"(d[26]), "+f"(d[27]), "+f"(d[28]), "+f"(d[29]), "+f"(d[30]), "+f"(d[31]), "+f"(d[32]), "+f"(d[33]), "+f"(d[34]), "+f"(d[35]), "+f"(d[36]), "+f"(d[37]), "+f"(d[38]), "+f"(d[39]), "+f"(d[40]), "+f"(d[41]), "+f"(d[42]), "+f"(d[43])
    : "r"(a[0]), "r"(a[1]), "r"(a[2]), "r"(a[3]), "r"(a[4]), "r"(a[5]), "r"(a[6]), "r"(a[7]), "r"(a[8]), "r"(a[9]), "r"(a[10]), "r"(a[11]), "r"(a[12]), "r"(a[13]), "r"(a[14]), "r"(a[15]), "l"(db), "n"(D)
    : "memory");
}
template<int D> __device__ __forceinline__ void bias_out(float (&d)[4], const uint32_t (&a)[16], uint64_t db) {
  asm volatile("{\n.reg .b64 db;\n"
    "add.s64 db, %20, %21 + 0;\n"
    "wgmma.mma_async.sync.aligned.m64n8k16.f32.bf16.bf16 {%0, %1, %2, %3}, {%4, %5, %6, %7}, db, 0, 1, 1, 0;\n"
    "add.s64 db, %20, %21 + 2;\n"
    "wgmma.mma_async.sync.aligned.m64n8k16.f32.bf16.bf16 {%0, %1, %2, %3}, {%8, %9, %10, %11}, db, 1, 1, 1, 0;\n"
    "add.s64 db, %20, %21 + 4;\n"
    "wgmma.mma_async.sync.aligned.m64n8k16.f32.bf16.bf16 {%0, %1, %2, %3}, {%12, %13, %14, %15}, db, 1, 1, 1, 0;\n"
    "add.s64 db, %20, %21 + 6;\n"
    "wgmma.mma_async.sync.aligned.m64n8k16.f32.bf16.bf16 {%0, %1, %2, %3}, {%16, %17, %18, %19}, db, 1, 1, 1, 0;\n"
    "wgmma.commit_group.sync.aligned;\n}\n"
    : "=f"(d[0]), "=f"(d[1]), "=f"(d[2]), "=f"(d[3])
    : "r"(a[0]), "r"(a[1]), "r"(a[2]), "r"(a[3]), "r"(a[4]), "r"(a[5]), "r"(a[6]), "r"(a[7]), "r"(a[8]), "r"(a[9]), "r"(a[10]), "r"(a[11]), "r"(a[12]), "r"(a[13]), "r"(a[14]), "r"(a[15]), "l"(db), "n"(D)
    : "memory");
}
template<int D> __device__ __forceinline__ void gemm2_first(float (&d)[16], const uint32_t (&a)[12], uint64_t db, uint32_t meta) {
  asm volatile("{\n.reg .b64 db;\n"
    "wgmma.fence.sync.aligned;\n"
    "add.s64 db, %28, %29 + 0;\n"
    "wgmma.mma_async.sp.sync.aligned.m64n32k32.f32.bf16.bf16 {%0, %1, %2, %3, %4, %5, %6, %7, %8, %9, %10, %11, %12, %13, %14, %15}, {%16, %17, %18, %19}, db, %30, 0, 0, 1, 1, 1;\n"
    "add.s64 db, %28, %29 + 128;\n"
    "wgmma.mma_async.sp.sync.aligned.m64n32k32.f32.bf16.bf16 {%0, %1, %2, %3, %4, %5, %6, %7, %8, %9, %10, %11, %12, %13, %14, %15}, {%20, %21, %22, %23}, db, %30, 0, 1, 1, 1, 1;\n"
    "add.s64 db, %28, %29 + 256;\n"
    "wgmma.mma_async.sp.sync.aligned.m64n32k32.f32.bf16.bf16 {%0, %1, %2, %3, %4, %5, %6, %7, %8, %9, %10, %11, %12, %13, %14, %15}, {%24, %25, %26, %27}, db, %30, 0, 1, 1, 1, 1;\n"
    "wgmma.commit_group.sync.aligned;\n}\n"
    : "=f"(d[0]), "=f"(d[1]), "=f"(d[2]), "=f"(d[3]), "=f"(d[4]), "=f"(d[5]), "=f"(d[6]), "=f"(d[7]), "=f"(d[8]), "=f"(d[9]), "=f"(d[10]), "=f"(d[11]), "=f"(d[12]), "=f"(d[13]), "=f"(d[14]), "=f"(d[15])
    : "r"(a[0]), "r"(a[1]), "r"(a[2]), "r"(a[3]), "r"(a[4]), "r"(a[5]), "r"(a[6]), "r"(a[7]), "r"(a[8]), "r"(a[9]), "r"(a[10]), "r"(a[11]), "l"(db), "n"(D), "r"(meta)
    : "memory");
}
template<int D> __device__ __forceinline__ void gemm2_first(float (&d)[16], const uint32_t (&a)[16], uint64_t db, uint32_t meta) {
  asm volatile("{\n.reg .b64 db;\n"
    "wgmma.fence.sync.aligned;\n"
    "add.s64 db, %32, %33 + 0;\n"
    "wgmma.mma_async.sp.sync.aligned.m64n32k32.f32.bf16.bf16 {%0, %1, %2, %3, %4, %5, %6, %7, %8, %9, %10, %11, %12, %13, %14, %15}, {%16, %17, %18, %19}, db, %34, 0, 0, 1, 1, 1;\n"
    "add.s64 db, %32, %33 + 128;\n"
    "wgmma.mma_async.sp.sync.aligned.m64n32k32.f32.bf16.bf16 {%0, %1, %2, %3, %4, %5, %6, %7, %8, %9, %10, %11, %12, %13, %14, %15}, {%20, %21, %22, %23}, db, %34, 0, 1, 1, 1, 1;\n"
    "add.s64 db, %32, %33 + 256;\n"
    "wgmma.mma_async.sp.sync.aligned.m64n32k32.f32.bf16.bf16 {%0, %1, %2, %3, %4, %5, %6, %7, %8, %9, %10, %11, %12, %13, %14, %15}, {%24, %25, %26, %27}, db, %34, 0, 1, 1, 1, 1;\n"
    "add.s64 db, %32, %33 + 384;\n"
    "wgmma.mma_async.sp.sync.aligned.m64n32k32.f32.bf16.bf16 {%0, %1, %2, %3, %4, %5, %6, %7, %8, %9, %10, %11, %12, %13, %14, %15}, {%28, %29, %30, %31}, db, %34, 0, 1, 1, 1, 1;\n"
    "wgmma.commit_group.sync.aligned;\n}\n"
    : "=f"(d[0]), "=f"(d[1]), "=f"(d[2]), "=f"(d[3]), "=f"(d[4]), "=f"(d[5]), "=f"(d[6]), "=f"(d[7]), "=f"(d[8]), "=f"(d[9]), "=f"(d[10]), "=f"(d[11]), "=f"(d[12]), "=f"(d[13]), "=f"(d[14]), "=f"(d[15])
    : "r"(a[0]), "r"(a[1]), "r"(a[2]), "r"(a[3]), "r"(a[4]), "r"(a[5]), "r"(a[6]), "r"(a[7]), "r"(a[8]), "r"(a[9]), "r"(a[10]), "r"(a[11]), "r"(a[12]), "r"(a[13]), "r"(a[14]), "r"(a[15]), "l"(db), "n"(D), "r"(meta)
    : "memory");
}
template<int D> __device__ __forceinline__ void gemm2_first(float (&d)[16], const uint32_t (&a)[20], uint64_t db, uint32_t meta) {
  asm volatile("{\n.reg .b64 db;\n"
    "wgmma.fence.sync.aligned;\n"
    "add.s64 db, %36, %37 + 0;\n"
    "wgmma.mma_async.sp.sync.aligned.m64n32k32.f32.bf16.bf16 {%0, %1, %2, %3, %4, %5, %6, %7, %8, %9, %10, %11, %12, %13, %14, %15}, {%16, %17, %18, %19}, db, %38, 0, 0, 1, 1, 1;\n"
    "add.s64 db, %36, %37 + 128;\n"
    "wgmma.mma_async.sp.sync.aligned.m64n32k32.f32.bf16.bf16 {%0, %1, %2, %3, %4, %5, %6, %7, %8, %9, %10, %11, %12, %13, %14, %15}, {%20, %21, %22, %23}, db, %38, 0, 1, 1, 1, 1;\n"
    "add.s64 db, %36, %37 + 256;\n"
    "wgmma.mma_async.sp.sync.aligned.m64n32k32.f32.bf16.bf16 {%0, %1, %2, %3, %4, %5, %6, %7, %8, %9, %10, %11, %12, %13, %14, %15}, {%24, %25, %26, %27}, db, %38, 0, 1, 1, 1, 1;\n"
    "add.s64 db, %36, %37 + 384;\n"
    "wgmma.mma_async.sp.sync.aligned.m64n32k32.f32.bf16.bf16 {%0, %1, %2, %3, %4, %5, %6, %7, %8, %9, %10, %11, %12, %13, %14, %15}, {%28, %29, %30, %31}, db, %38, 0, 1, 1, 1, 1;\n"
    "add.s64 db, %36, %37 + 512;\n"
    "wgmma.mma_async.sp.sync.aligned.m64n32k32.f32.bf16.bf16 {%0, %1, %2, %3, %4, %5, %6, %7, %8, %9, %10, %11, %12, %13, %14, %15}, {%32, %33, %34, %35}, db, %38, 0, 1, 1, 1, 1;\n"
    "wgmma.commit_group.sync.aligned;\n}\n"
    : "=f"(d[0]), "=f"(d[1]), "=f"(d[2]), "=f"(d[3]), "=f"(d[4]), "=f"(d[5]), "=f"(d[6]), "=f"(d[7]), "=f"(d[8]), "=f"(d[9]), "=f"(d[10]), "=f"(d[11]), "=f"(d[12]), "=f"(d[13]), "=f"(d[14]), "=f"(d[15])
    : "r"(a[0]), "r"(a[1]), "r"(a[2]), "r"(a[3]), "r"(a[4]), "r"(a[5]), "r"(a[6]), "r"(a[7]), "r"(a[8]), "r"(a[9]), "r"(a[10]), "r"(a[11]), "r"(a[12]), "r"(a[13]), "r"(a[14]), "r"(a[15]), "r"(a[16]), "r"(a[17]), "r"(a[18]), "r"(a[19]), "l"(db), "n"(D), "r"(meta)
    : "memory");
}
template<int D> __device__ __forceinline__ void gemm2_more(float (&d)[16], const uint32_t (&a)[4], uint64_t db, uint32_t meta) {
  asm volatile("{\n.reg .b64 db;\n"
    "wgmma.fence.sync.aligned;\n"
    "add.s64 db, %20, %21 + 0;\n"
    "wgmma.mma_async.sp.sync.aligned.m64n32k32.f32.bf16.bf16 {%0, %1, %2, %3, %4, %5, %6, %7, %8, %9, %10, %11, %12, %13, %14, %15}, {%16, %17, %18, %19}, db, %22, 0, 1, 1, 1, 1;\n"
    "wgmma.commit_group.sync.aligned;\n}\n"
    : "+f"(d[0]), "+f"(d[1]), "+f"(d[2]), "+f"(d[3]), "+f"(d[4]), "+f"(d[5]), "+f"(d[6]), "+f"(d[7]), "+f"(d[8]), "+f"(d[9]), "+f"(d[10]), "+f"(d[11]), "+f"(d[12]), "+f"(d[13]), "+f"(d[14]), "+f"(d[15])
    : "r"(a[0]), "r"(a[1]), "r"(a[2]), "r"(a[3]), "l"(db), "n"(D), "r"(meta)
    : "memory");
}
template<int D> __device__ __forceinline__ void gemm2_more(float (&d)[16], const uint32_t (&a)[8], uint64_t db, uint32_t meta) {
  asm volatile("{\n.reg .b64 db;\n"
    "wgmma.fence.sync.aligned;\n"
    "add.s64 db, %24, %25 + 0;\n"
    "wgmma.mma_async.sp.sync.aligned.m64n32k32.f32.bf16.bf16 {%0, %1, %2, %3, %4, %5, %6, %7, %8, %9, %10, %11, %12, %13, %14, %15}, {%16, %17, %18, %19}, db, %26, 0, 1, 1, 1, 1;\n"
    "add.s64 db, %24, %25 + 128;\n"
    "wgmma.mma_async.sp.sync.aligned.m64n32k32.f32.bf16.bf16 {%0, %1, %2, %3, %4, %5, %6, %7, %8, %9, %10, %11, %12, %13, %14, %15}, {%20, %21, %22, %23}, db, %26, 0, 1, 1, 1, 1;\n"
    "wgmma.commit_group.sync.aligned;\n}\n"
    : "+f"(d[0]), "+f"(d[1]), "+f"(d[2]), "+f"(d[3]), "+f"(d[4]), "+f"(d[5]), "+f"(d[6]), "+f"(d[7]), "+f"(d[8]), "+f"(d[9]), "+f"(d[10]), "+f"(d[11]), "+f"(d[12]), "+f"(d[13]), "+f"(d[14]), "+f"(d[15])
    : "r"(a[0]), "r"(a[1]), "r"(a[2]), "r"(a[3]), "r"(a[4]), "r"(a[5]), "r"(a[6]), "r"(a[7]), "l"(db), "n"(D), "r"(meta)
    : "memory");
}
template<int D> __device__ __forceinline__ void gemm2_more(float (&d)[16], const uint32_t (&a)[12], uint64_t db, uint32_t meta) {
  asm volatile("{\n.reg .b64 db;\n"
    "wgmma.fence.sync.aligned;\n"
    "add.s64 db, %28, %29 + 0;\n"
    "wgmma.mma_async.sp.sync.aligned.m64n32k32.f32.bf16.bf16 {%0, %1, %2, %3, %4, %5, %6, %7, %8, %9, %10, %11, %12, %13, %14, %15}, {%16, %17, %18, %19}, db, %30, 0, 1, 1, 1, 1;\n"
    "add.s64 db, %28, %29 + 128;\n"
    "wgmma.mma_async.sp.sync.aligned.m64n32k32.f32.bf16.bf16 {%0, %1, %2, %3, %4, %5, %6, %7, %8, %9, %10, %11, %12, %13, %14, %15}, {%20, %21, %22, %23}, db, %30, 0, 1, 1, 1, 1;\n"
    "add.s64 db, %28, %29 + 256;\n"
    "wgmma.mma_async.sp.sync.aligned.m64n32k32.f32.bf16.bf16 {%0, %1, %2, %3, %4, %5, %6, %7, %8, %9, %10, %11, %12, %13, %14, %15}, {%24, %25, %26, %27}, db, %30, 0, 1, 1, 1, 1;\n"
    "wgmma.commit_group.sync.aligned;\n}\n"
    : "+f"(d[0]), "+f"(d[1]), "+f"(d[2]), "+f"(d[3]), "+f"(d[4]), "+f"(d[5]), "+f"(d[6]), "+f"(d[7]), "+f"(d[8]), "+f"(d[9]), "+f"(d[10]), "+f"(d[11]), "+f"(d[12]), "+f"(d[13]), "+f"(d[14]), "+f"(d[15])
    : "r"(a[0]), "r"(a[1]), "r"(a[2]), "r"(a[3]), "r"(a[4]), "r"(a[5]), "r"(a[6]), "r"(a[7]), "r"(a[8]), "r"(a[9]), "r"(a[10]), "r"(a[11]), "l"(db), "n"(D), "r"(meta)
    : "memory");
}
template<int D> __device__ __forceinline__ void gemm2_more(float (&d)[16], const uint32_t (&a)[16], uint64_t db, uint32_t meta) {
  asm volatile("{\n.reg .b64 db;\n"
    "wgmma.fence.sync.aligned;\n"
    "add.s64 db, %32, %33 + 0;\n"
    "wgmma.mma_async.sp.sync.aligned.m64n32k32.f32.bf16.bf16 {%0, %1, %2, %3, %4, %5, %6, %7, %8, %9, %10, %11, %12, %13, %14, %15}, {%16, %17, %18, %19}, db, %34, 0, 1, 1, 1, 1;\n"
    "add.s64 db, %32, %33 + 128;\n"
    "wgmma.mma_async.sp.sync.aligned.m64n32k32.f32.bf16.bf16 {%0, %1, %2, %3, %4, %5, %6, %7, %8, %9, %10, %11, %12, %13, %14, %15}, {%20, %21, %22, %23}, db, %34, 0, 1, 1, 1, 1;\n"
    "add.s64 db, %32, %33 + 256;\n"
    "wgmma.mma_async.sp.sync.aligned.m64n32k32.f32.bf16.bf16 {%0, %1, %2, %3, %4, %5, %6, %7, %8, %9, %10, %11, %12, %13, %14, %15}, {%24, %25, %26, %27}, db, %34, 0, 1, 1, 1, 1;\n"
    "add.s64 db, %32, %33 + 384;\n"
    "wgmma.mma_async.sp.sync.aligned.m64n32k32.f32.bf16.bf16 {%0, %1, %2, %3, %4, %5, %6, %7, %8, %9, %10, %11, %12, %13, %14, %15}, {%28, %29, %30, %31}, db, %34, 0, 1, 1, 1, 1;\n"
    "wgmma.commit_group.sync.aligned;\n}\n"
    : "+f"(d[0]), "+f"(d[1]), "+f"(d[2]), "+f"(d[3]), "+f"(d[4]), "+f"(d[5]), "+f"(d[6]), "+f"(d[7]), "+f"(d[8]), "+f"(d[9]), "+f"(d[10]), "+f"(d[11]), "+f"(d[12]), "+f"(d[13]), "+f"(d[14]), "+f"(d[15])
    : "r"(a[0]), "r"(a[1]), "r"(a[2]), "r"(a[3]), "r"(a[4]), "r"(a[5]), "r"(a[6]), "r"(a[7]), "r"(a[8]), "r"(a[9]), "r"(a[10]), "r"(a[11]), "r"(a[12]), "r"(a[13]), "r"(a[14]), "r"(a[15]), "l"(db), "n"(D), "r"(meta)
    : "memory");
}
template<int N> __device__ __forceinline__ void mma_wait(float (&d)[4]) {
  asm volatile("wgmma.wait_group.sync.aligned %4;"
    : "+f"(d[0]), "+f"(d[1]), "+f"(d[2]), "+f"(d[3])
    : "n"(N) : "memory");
}
template<int N> __device__ __forceinline__ void mma_wait(float (&d)[16]) {
  asm volatile("wgmma.wait_group.sync.aligned %16;"
    : "+f"(d[0]), "+f"(d[1]), "+f"(d[2]), "+f"(d[3]), "+f"(d[4]), "+f"(d[5]), "+f"(d[6]), "+f"(d[7]), "+f"(d[8]), "+f"(d[9]), "+f"(d[10]), "+f"(d[11]), "+f"(d[12]), "+f"(d[13]), "+f"(d[14]), "+f"(d[15])
    : "n"(N) : "memory");
}
template<int N> __device__ __forceinline__ void mma_wait(float (&d)[20]) {
  asm volatile("wgmma.wait_group.sync.aligned %20;"
    : "+f"(d[0]), "+f"(d[1]), "+f"(d[2]), "+f"(d[3]), "+f"(d[4]), "+f"(d[5]), "+f"(d[6]), "+f"(d[7]), "+f"(d[8]), "+f"(d[9]), "+f"(d[10]), "+f"(d[11]), "+f"(d[12]), "+f"(d[13]), "+f"(d[14]), "+f"(d[15]), "+f"(d[16]), "+f"(d[17]), "+f"(d[18]), "+f"(d[19])
    : "n"(N) : "memory");
}
template<int N> __device__ __forceinline__ void mma_wait(float (&d)[28]) {
  asm volatile("wgmma.wait_group.sync.aligned %28;"
    : "+f"(d[0]), "+f"(d[1]), "+f"(d[2]), "+f"(d[3]), "+f"(d[4]), "+f"(d[5]), "+f"(d[6]), "+f"(d[7]), "+f"(d[8]), "+f"(d[9]), "+f"(d[10]), "+f"(d[11]), "+f"(d[12]), "+f"(d[13]), "+f"(d[14]), "+f"(d[15]), "+f"(d[16]), "+f"(d[17]), "+f"(d[18]), "+f"(d[19]), "+f"(d[20]), "+f"(d[21]), "+f"(d[22]), "+f"(d[23]), "+f"(d[24]), "+f"(d[25]), "+f"(d[26]), "+f"(d[27])
    : "n"(N) : "memory");
}
template<int N> __device__ __forceinline__ void mma_wait(float (&d)[32]) {
  asm volatile("wgmma.wait_group.sync.aligned %32;"
    : "+f"(d[0]), "+f"(d[1]), "+f"(d[2]), "+f"(d[3]), "+f"(d[4]), "+f"(d[5]), "+f"(d[6]), "+f"(d[7]), "+f"(d[8]), "+f"(d[9]), "+f"(d[10]), "+f"(d[11]), "+f"(d[12]), "+f"(d[13]), "+f"(d[14]), "+f"(d[15]), "+f"(d[16]), "+f"(d[17]), "+f"(d[18]), "+f"(d[19]), "+f"(d[20]), "+f"(d[21]), "+f"(d[22]), "+f"(d[23]), "+f"(d[24]), "+f"(d[25]), "+f"(d[26]), "+f"(d[27]), "+f"(d[28]), "+f"(d[29]), "+f"(d[30]), "+f"(d[31])
    : "n"(N) : "memory");
}
template<int N> __device__ __forceinline__ void mma_wait(float (&d)[36]) {
  asm volatile("wgmma.wait_group.sync.aligned %36;"
    : "+f"(d[0]), "+f"(d[1]), "+f"(d[2]), "+f"(d[3]), "+f"(d[4]), "+f"(d[5]), "+f"(d[6]), "+f"(d[7]), "+f"(d[8]), "+f"(d[9]), "+f"(d[10]), "+f"(d[11]), "+f"(d[12]), "+f"(d[13]), "+f"(d[14]), "+f"(d[15]), "+f"(d[16]), "+f"(d[17]), "+f"(d[18]), "+f"(d[19]), "+f"(d[20]), "+f"(d[21]), "+f"(d[22]), "+f"(d[23]), "+f"(d[24]), "+f"(d[25]), "+f"(d[26]), "+f"(d[27]), "+f"(d[28]), "+f"(d[29]), "+f"(d[30]), "+f"(d[31]), "+f"(d[32]), "+f"(d[33]), "+f"(d[34]), "+f"(d[35])
    : "n"(N) : "memory");
}
template<int N> __device__ __forceinline__ void mma_wait(float (&d)[40]) {
  asm volatile("wgmma.wait_group.sync.aligned %40;"
    : "+f"(d[0]), "+f"(d[1]), "+f"(d[2]), "+f"(d[3]), "+f"(d[4]), "+f"(d[5]), "+f"(d[6]), "+f"(d[7]), "+f"(d[8]), "+f"(d[9]), "+f"(d[10]), "+f"(d[11]), "+f"(d[12]), "+f"(d[13]), "+f"(d[14]), "+f"(d[15]), "+f"(d[16]), "+f"(d[17]), "+f"(d[18]), "+f"(d[19]), "+f"(d[20]), "+f"(d[21]), "+f"(d[22]), "+f"(d[23]), "+f"(d[24]), "+f"(d[25]), "+f"(d[26]), "+f"(d[27]), "+f"(d[28]), "+f"(d[29]), "+f"(d[30]), "+f"(d[31]), "+f"(d[32]), "+f"(d[33]), "+f"(d[34]), "+f"(d[35]), "+f"(d[36]), "+f"(d[37]), "+f"(d[38]), "+f"(d[39])
    : "n"(N) : "memory");
}
template<int N> __device__ __forceinline__ void mma_wait(float (&d)[44]) {
  asm volatile("wgmma.wait_group.sync.aligned %44;"
    : "+f"(d[0]), "+f"(d[1]), "+f"(d[2]), "+f"(d[3]), "+f"(d[4]), "+f"(d[5]), "+f"(d[6]), "+f"(d[7]), "+f"(d[8]), "+f"(d[9]), "+f"(d[10]), "+f"(d[11]), "+f"(d[12]), "+f"(d[13]), "+f"(d[14]), "+f"(d[15]), "+f"(d[16]), "+f"(d[17]), "+f"(d[18]), "+f"(d[19]), "+f"(d[20]), "+f"(d[21]), "+f"(d[22]), "+f"(d[23]), "+f"(d[24]), "+f"(d[25]), "+f"(d[26]), "+f"(d[27]), "+f"(d[28]), "+f"(d[29]), "+f"(d[30]), "+f"(d[31]), "+f"(d[32]), "+f"(d[33]), "+f"(d[34]), "+f"(d[35]), "+f"(d[36]), "+f"(d[37]), "+f"(d[38]), "+f"(d[39]), "+f"(d[40]), "+f"(d[41]), "+f"(d[42]), "+f"(d[43])
    : "n"(N) : "memory");
}
__device__ __forceinline__ void mma_fence() { asm volatile("wgmma.fence.sync.aligned;" ::: "memory"); }

__device__ __forceinline__ uint32_t smem_u32(const void* p) { return (uint32_t)__cvta_generic_to_shared(p); }

__device__ __forceinline__ void mbar_init(uint32_t bar, uint32_t cnt) {
  asm volatile("mbarrier.init.shared::cta.b64 [%0], %1;" :: "r"(bar), "r"(cnt) : "memory");
}
__device__ __forceinline__ void mbar_arrive(uint32_t bar) {
  asm volatile("mbarrier.arrive.shared::cta.b64 _, [%0];" :: "r"(bar) : "memory");
}
__device__ __forceinline__ void mbar_wait(uint32_t bar, uint32_t parity) {
  asm volatile("{\n.reg .pred p;\n.reg .u32 n;\n"
               "mov.u32 n, 0;\n"
               "WAIT_LOOP:\n"
               "mbarrier.try_wait.parity.shared::cta.b64 p, [%0], %1;\n"
               "@p bra.uni WAIT_DONE;\n"
               "add.u32 n, n, 1;\n"
               "setp.lt.u32 p, n, 0x1000000;\n"
               "@p bra.uni WAIT_LOOP;\n"
               "trap;\n"
               "WAIT_DONE:\n}\n"
               :: "r"(bar), "r"(parity) : "memory");
}
__device__ __forceinline__ void mbar_wait_unless(uint32_t ok, uint32_t bar, uint32_t parity) {
  asm volatile("{\n.reg .pred p;\n.reg .u32 n;\n"
               "setp.ne.u32 p, %2, 0;\n"
               "@p bra.uni WAIT_DONE;\n"
               "mov.u32 n, 0;\n"
               "WAIT_LOOP:\n"
               "mbarrier.try_wait.parity.shared::cta.b64 p, [%0], %1;\n"
               "@p bra.uni WAIT_DONE;\n"
               "add.u32 n, n, 1;\n"
               "setp.lt.u32 p, n, 0x1000000;\n"
               "@p bra.uni WAIT_LOOP;\n"
               "trap;\n"
               "WAIT_DONE:\n}\n"
               :: "r"(bar), "r"(parity), "r"(ok) : "memory");
}
__device__ __forceinline__ uint32_t mbar_test(uint32_t bar, uint32_t parity) {
  uint32_t ok;
  asm volatile("{\n.reg .pred p;\nmbarrier.test_wait.parity.shared::cta.b64 p, [%1], %2;\nselp.u32 %0, 1, 0, p;\n}\n"
               : "=r"(ok) : "r"(bar), "r"(parity) : "memory");
  return ok;
}
__device__ __forceinline__ void cp_async16(uint32_t dst, const void* src) {
  asm volatile("cp.async.cg.shared.global [%0], [%1], 16;" :: "r"(dst), "l"(src) : "memory");
}
#define DIN_ADDR4                                                                        \
  "mov.b64 {x, y}, %0;\ndp4a.u32.u32 x, %8, 0x80, %11;\nmov.b64 %0, {x, y};\n"           \
  "mov.b64 {x, y}, %1;\ndp4a.u32.u32 x, %8, 0x8000, %11;\nmov.b64 %1, {x, y};\n"         \
  "mov.b64 {x, y}, %2;\ndp4a.u32.u32 x, %8, 0x800000, %11;\nmov.b64 %2, {x, y};\n"       \
  "mov.b64 {x, y}, %3;\ndp4a.u32.u32 x, %8, 0x80000000, %11;\nmov.b64 %3, {x, y};\n"
template<int T>
__device__ __forceinline__ void cp_group(const uint32_t (&dst)[4], uint64_t (&a)[4], uint32_t rows4, uint32_t base, uint64_t pol) {
  asm volatile("{\n.reg .u32 x, y;\n" DIN_ADDR4
               "cp.async.cg.shared.global.L2::cache_hint [%4 + %10], [%0], 16, %9;\n"
               "cp.async.cg.shared.global.L2::cache_hint [%5 + %10], [%1], 16, %9;\n"
               "cp.async.cg.shared.global.L2::cache_hint [%6 + %10], [%2], 16, %9;\n"
               "cp.async.cg.shared.global.L2::cache_hint [%7 + %10], [%3], 16, %9;\n}\n"
               : "+l"(a[0]), "+l"(a[1]), "+l"(a[2]), "+l"(a[3])
               : "r"(dst[0]), "r"(dst[1]), "r"(dst[2]), "r"(dst[3]), "r"(rows4), "l"(pol), "n"(T * 2048), "r"(base) : "memory");
}
template<int T>
__device__ __forceinline__ void cp_group_z(const uint32_t (&dst)[4], uint64_t (&a)[4], uint32_t rows4, uint32_t base, int left, uint64_t pol) {
  asm volatile("{\n.reg .u32 x, y;\n.reg .pred p0, p1, p2, p3;\n" DIN_ADDR4
               "setp.le.s32 p0, %12, %13;\nsetp.le.s32 p1, %12, %13 + 1;\nsetp.le.s32 p2, %12, %13 + 2;\nsetp.le.s32 p3, %12, %13 + 3;\n"
               "cp.async.cg.shared.global.L2::cache_hint [%4 + %10], [%0], 16, p0, %9;\n"
               "cp.async.cg.shared.global.L2::cache_hint [%5 + %10], [%1], 16, p1, %9;\n"
               "cp.async.cg.shared.global.L2::cache_hint [%6 + %10], [%2], 16, p2, %9;\n"
               "cp.async.cg.shared.global.L2::cache_hint [%7 + %10], [%3], 16, p3, %9;\n}\n"
               : "+l"(a[0]), "+l"(a[1]), "+l"(a[2]), "+l"(a[3])
               : "r"(dst[0]), "r"(dst[1]), "r"(dst[2]), "r"(dst[3]), "r"(rows4), "l"(pol), "n"(T * 2048), "r"(base),
                 "r"(left), "n"(T * 16) : "memory");
}
__device__ __forceinline__ void wait_for(uint32_t t, uint32_t most) {
  asm volatile("{\n.reg .u32 c;\n.reg .pred p;\n"
               "SPIN:\n"
               "mov.u32 c, %%globaltimer_lo;\n"
               "sub.u32 c, c, %0;\n"
               "setp.gt.u32 p, c, %1;\n"
               "@p bra.uni SPIN;\n}\n" :: "r"(t), "r"(~most) : "memory");
}
template<int T, int SH>
__device__ __forceinline__ void cp_group_m(const uint32_t (&dst)[4], uint64_t (&a)[4], uint32_t rows4, uint32_t base, uint32_t have, uint32_t go, uint64_t pol) {
  asm volatile("{\n.reg .u32 x, y;\n.reg .pred p0, p1, p2, p3, g;\n" DIN_ADDR4
               "setp.ne.u32 g, %14, 0;\n"
               "and.b32 x, %12, 1 << %13;\nsetp.eq.u32 p0, x, 0;\nand.b32 x, %12, 2 << %13;\nsetp.eq.u32 p1, x, 0;\n"
               "and.b32 x, %12, 4 << %13;\nsetp.eq.u32 p2, x, 0;\nand.b32 x, %12, 8 << %13;\nsetp.eq.u32 p3, x, 0;\n"
               "@g cp.async.cg.shared.global.L2::cache_hint [%4 + %10], [%0], 16, p0, %9;\n"
               "@g cp.async.cg.shared.global.L2::cache_hint [%5 + %10], [%1], 16, p1, %9;\n"
               "@g cp.async.cg.shared.global.L2::cache_hint [%6 + %10], [%2], 16, p2, %9;\n"
               "@g cp.async.cg.shared.global.L2::cache_hint [%7 + %10], [%3], 16, p3, %9;\n}\n"
               : "+l"(a[0]), "+l"(a[1]), "+l"(a[2]), "+l"(a[3])
               : "r"(dst[0]), "r"(dst[1]), "r"(dst[2]), "r"(dst[3]), "r"(rows4), "l"(pol), "n"(T * 2048), "r"(base),
                 "r"(have), "n"(SH), "r"(go) : "memory");
}
__device__ __forceinline__ uint32_t prmt(uint32_t a, uint32_t b, uint32_t sel) {
  uint32_t d;
  asm("prmt.b32 %0, %1, %2, %3;" : "=r"(d) : "r"(a), "r"(b), "r"(sel));
  return d;
}
__device__ __forceinline__ uint32_t ballot_bit(uint32_t x, uint32_t bit) {
  uint32_t d;
  asm volatile("{\n.reg .pred p;\n.reg .u32 t;\nand.b32 t, %1, %2;\nsetp.ne.u32 p, t, 0;\nvote.sync.ballot.b32 %0, p, 0xffffffff;\n}\n"
               : "=r"(d) : "r"(x), "r"(bit));
  return d;
}
__device__ __forceinline__ uint4 load_mask(const void* mask, uint32_t b, uint32_t i) {
  uint4 m;
  asm volatile("ld.global.nc.L1::no_allocate.v4.u32 {%0,%1,%2,%3}, [%4];"
               : "=r"(m.x), "=r"(m.y), "=r"(m.z), "=r"(m.w) : "l"(reinterpret_cast<const uint4*>(mask) + (b * 25u + i)));
  return m;
}
__device__ __forceinline__ uint32_t nonzero_as_one(uint32_t x) {
  uint32_t d;
  asm("set.neu.bf16x2.bf16x2 %0, %1, %2;" : "=r"(d) : "r"(x), "r"(0u));
  return d;
}
__device__ __forceinline__ void cp_async_arrive_noinc(uint32_t bar) {
  asm volatile("cp.async.mbarrier.arrive.noinc.shared::cta.b64 [%0];" :: "r"(bar) : "memory");
}
__device__ __forceinline__ void ldsm_x4(uint32_t addr, uint32_t& r0, uint32_t& r1, uint32_t& r2, uint32_t& r3) {
  asm volatile("ldmatrix.sync.aligned.m8n8.x4.shared.b16 {%0,%1,%2,%3}, [%4];"
               : "=r"(r0), "=r"(r1), "=r"(r2), "=r"(r3) : "r"(addr) : "memory");
}
__device__ __forceinline__ void ldsm_x4_t(uint32_t addr, uint32_t& r0, uint32_t& r1, uint32_t& r2, uint32_t& r3) {
  asm volatile("ldmatrix.sync.aligned.m8n8.x4.trans.shared.b16 {%0,%1,%2,%3}, [%4];"
               : "=r"(r0), "=r"(r1), "=r"(r2), "=r"(r3) : "r"(addr) : "memory");
}
__device__ __forceinline__ void stsm_x4(uint32_t addr, uint32_t r0, uint32_t r1, uint32_t r2, uint32_t r3) {
  asm volatile("stmatrix.sync.aligned.m8n8.x4.shared.b16 [%0], {%1,%2,%3,%4};"
               :: "r"(addr), "r"(r0), "r"(r1), "r"(r2), "r"(r3) : "memory");
}
__device__ __forceinline__ void stsm_x2(uint32_t addr, uint32_t r0, uint32_t r1) {
  asm volatile("stmatrix.sync.aligned.m8n8.x2.shared.b16 [%0], {%1,%2};"
               :: "r"(addr), "r"(r0), "r"(r1) : "memory");
}
__device__ __forceinline__ void mma_bf16(float (&c)[4], const uint32_t (&a)[4], uint32_t b) {
  asm("mma.sync.aligned.m16n8k16.row.col.f32.bf16.bf16.f32 {%0,%1,%2,%3}, {%4,%5,%6,%7}, {%8,%8}, {%0,%1,%2,%3};"
      : "+f"(c[0]), "+f"(c[1]), "+f"(c[2]), "+f"(c[3]) : "r"(a[0]), "r"(a[1]), "r"(a[2]), "r"(a[3]), "r"(b));
}
__device__ __forceinline__ uint32_t hfma2_bf16(uint32_t a, uint32_t b, uint32_t c) {
  uint32_t d;
  asm volatile("fma.rn.bf16x2 %0, %1, %2, %3;" : "=r"(d) : "r"(a), "r"(b), "r"(c));
  return d;
}
__device__ __forceinline__ uint32_t pack_bf16(float lo, float hi) {
  uint32_t d;
  asm("cvt.rn.bf16x2.f32 %0, %1, %2;" : "=r"(d) : "f"(hi), "f"(lo));
  return d;
}
__device__ __forceinline__ uint32_t lds32(uint32_t a) {
  uint32_t v; asm volatile("ld.shared.u32 %0, [%1];" : "=r"(v) : "r"(a) : "memory"); return v;
}
__device__ __forceinline__ uint32_t lds16(uint32_t a) {
  uint32_t v; asm volatile("ld.shared.u16 %0, [%1];" : "=r"(v) : "r"(a) : "memory"); return v;
}
__device__ __forceinline__ void sts32(uint32_t a, uint32_t v) {
  asm volatile("st.shared.u32 [%0], %1;" :: "r"(a), "r"(v) : "memory");
}
__device__ __forceinline__ void sts16(uint32_t a, uint32_t v) {
  asm volatile("st.shared.u16 [%0], %1;" :: "r"(a), "h"((unsigned short)v) : "memory");
}
__device__ __forceinline__ void sts8(uint32_t a, uint32_t v) {
  asm volatile("st.shared.u8 [%0], %1;" :: "r"(a), "r"(v) : "memory");
}
constexpr uint32_t DESC_ROWS = 0x40000040u, DESC_HALVES = 0x80000020u;
__device__ __forceinline__ uint32_t desc_lo(uint32_t addr) { return ((addr & 0x3FFFF) >> 4) | (1u << 16); }

__device__ __forceinline__ uint4 lds128(uint32_t a) {
  uint4 v;
  asm volatile("ld.shared.v4.u32 {%0,%1,%2,%3}, [%4];" : "=r"(v.x), "=r"(v.y), "=r"(v.z), "=r"(v.w) : "r"(a) : "memory");
  return v;
}
__device__ __forceinline__ void sts128(uint32_t a, uint4 v) {
  asm volatile("st.shared.v4.u32 [%0], {%1,%2,%3,%4};" :: "r"(a), "r"(v.x), "r"(v.y), "r"(v.z), "r"(v.w) : "memory");
}
__device__ __forceinline__ void prefetch_l2(const void* p, uint32_t bytes) {
  asm volatile("cp.async.bulk.prefetch.L2.global [%0], %1;" :: "l"(p), "r"(bytes) : "memory");
}

template<int ND>
__device__ __forceinline__ void tanh_range(float (&d)[ND], int i0, int i1) {
#pragma unroll
  for (int i = i0; i < i1; i++) asm volatile("tanh.approx.f32 %0, %0;" : "+f"(d[i ^ 2]));
}
template<int ND>
__device__ __forceinline__ uint32_t mix(const float (&d)[ND], int i, float w2a, float w2b, float c32) {
  uint32_t p;
  asm volatile("{\n.reg .f32 x, y;\nfma.rn.f32 x, %3, %6, %7;\nfma.rn.f32 y, %4, %6, %7;\n"
               "fma.rn.f32 x, %1, %5, x;\nfma.rn.f32 y, %2, %5, y;\ncvt.rn.bf16x2.f32 %0, y, x;\n}\n"
               : "=r"(p) : "f"(d[4 * i]), "f"(d[4 * i + 1]), "f"(d[4 * i + 2]), "f"(d[4 * i + 3]), "f"(w2a), "f"(w2b), "f"(c32));
  return p;
}
__device__ __forceinline__ uint32_t size_bit(int n) { return n > 120 ? H_16 : H_12 << (max(n - 89, 0) >> 3); }
template<int V> struct Int { static constexpr int value = V; };

__global__ void __launch_bounds__(NTHREADS, 1)
din_kernel(const __nv_bfloat16* __restrict__ mask, const __nv_bfloat16* __restrict__ target, int B, int grid,
           uint32_t pf_mask, uint32_t pf_tgt, const __nv_bfloat16* __restrict__ w1, const __nv_bfloat16* __restrict__ hist,
           const __nv_bfloat16* __restrict__ b1, const __nv_bfloat16* __restrict__ w2,
           const __nv_bfloat16* __restrict__ b2, __nv_bfloat16* __restrict__ out, unsigned int* counter, int pace,
           int slow_from, int pace_slow, int spread) {
  {
    const char* pm = reinterpret_cast<const char*>(mask) + (size_t)blockIdx.x * pf_mask;
    const char* pt = reinterpret_cast<const char*>(target) + (size_t)blockIdx.x * pf_tgt;
    const uint32_t o = threadIdx.x * 128;
    asm volatile("{\n.reg .pred p;\nsetp.lt.u32 p, %1, %2;\n@p prefetch.global.L2 [%0];\n}\n" :: "l"(pm + o), "r"(o), "r"(pf_mask));
    asm volatile("{\n.reg .pred p;\nsetp.lt.u32 p, %1, %2;\n@p prefetch.global.L2 [%0];\n}\n" :: "l"(pt + o), "r"(o), "r"(pf_tgt));
  }
  extern __shared__ unsigned char smem_raw[];
  const uint32_t sb = (smem_u32(smem_raw) + 1023u) & ~1023u;
  const int tid = threadIdx.x, lane = tid & 31;
  const int warp = __shfl_sync(0xffffffffu, tid >> 5, 0);
#define ACT NCW
  const int bstep = ACT * grid;

  STAMP(0);
  if (warp < NCW * 4) {
    const int wg = warp >> 2, w = warp & 3;
    const int g = lane >> 2;
    const uint32_t ring = sb + wg * RING_BYTES;
    const bool active = wg * grid + (int)blockIdx.x < B && wg < ACT;
    {
      const int t = tid & 127;
      const uint32_t dst = sb + ((t ^ ((t >> 3) & 7)) << 4);
      const char* src = reinterpret_cast<const char*>(w1) + t * 16;
#pragma unroll
      for (int i = 0; i < 4; i++) cp_async16(dst + w1_at(i) + wg * 2048, src + i * 8192 + wg * 2048);
      cp_async16(dst + w1_at(0) + (wg >> 1) * RING_BYTES + (wg & 1) * SLOT_BYTES + 6144, src + wg * 8192 + 6144);
      if (wg == 0) cp_async16(dst + w1_at(3) + 6144, src + 3 * 8192 + 6144);
      if (lane < 8) {
        if (w == 0 && active) cp_async16(ring + R_TGT0 + lane * 16, target + (size_t)(wg * grid + blockIdx.x) * kD + lane * 8);
        if (w == 1 && wg < 2) cp_async16(ring + R_VEC + lane * 16, (wg ? w2 : b1) + lane * 8);
      }
    }
    if (w == 2) sts32(ring + R_SEL + lane * 4, 0x3f803f80u);
    uint32_t rb2;
    asm volatile("ld.global.nc.u16 %0, [%1];" : "=r"(rb2) : "l"(b2));
    asm volatile("setmaxnreg.inc.sync.aligned.u32 %0;" :: "n"(CONS_REGS));
    asm volatile("cp.async.wait_all;" ::: "memory");
    STAMP(5);
    asm volatile("bar.sync 1, %0;" :: "n"(NCW * 160) : "memory");
    const uint32_t half2 = 0x3f003f00u, nhalf2 = 0xbf00bf00u, nzero2 = 0x80008000u;
    const uint32_t vec = sb + R_VEC + (16 * w + g) * 2;
    const float w2a = 0.5f * __uint_as_float(lds16(vec + RING_BYTES) << 16);
    const float w2b = 0.5f * __uint_as_float(lds16(vec + RING_BYTES + 16) << 16);
    const uint32_t rw2 = lds32(sb + RING_BYTES + R_VEC + lane * 4);
    float c32 = __uint_as_float(rw2 << 16) + __uint_as_float(rw2 & 0xffff0000u);
#pragma unroll
    for (int o = 16; o; o >>= 1) c32 += __shfl_xor_sync(0xffffffffu, c32, o);
    c32 = (0.5f * c32 + __uint_as_float(rb2 << 16)) * (1.0f / 32.0f);
    uint32_t bq[4];
    bq[2] = hfma2_bf16(lds16(vec), half2, nzero2);
    bq[3] = hfma2_bf16(lds16(vec + 16), half2, nzero2);
    if (lane & 3) bq[2] = bq[3] = 0;
    uint32_t wac[16], wd[16], wbc[16];
    {
      const int mi = lane >> 3, rr = lane & 7;
      const uint32_t a0 = sb + (8 * (mi >> 1) + rr) * 128 + (((2 * w + (mi & 1)) ^ rr) << 4);
#pragma unroll
      for (int ks = 0; ks < 4; ks++) {
        uint32_t A[4], Bm[4], C[4], Dm[4];
        ldsm_x4_t(a0 + ks * 2048 + w1_at(0), A[0], A[1], A[2], A[3]);
        ldsm_x4_t(a0 + ks * 2048 + w1_at(1), Bm[0], Bm[1], Bm[2], Bm[3]);
        ldsm_x4_t(a0 + ks * 2048 + w1_at(2), C[0], C[1], C[2], C[3]);
        ldsm_x4_t(a0 + ks * 2048 + w1_at(3), Dm[0], Dm[1], Dm[2], Dm[3]);
#pragma unroll
        for (int e = 0; e < 4; e++) {
          wac[4 * ks + e] = hfma2_bf16(A[e], half2, hfma2_bf16(C[e], half2, nzero2));
          wbc[4 * ks + e] = hfma2_bf16(Bm[e], half2, hfma2_bf16(C[e], nhalf2, nzero2));
          wd[4 * ks + e] = hfma2_bf16(Dm[e], half2, nzero2);
        }
      }
    }
    asm volatile("fence.proxy.async.shared::cta;" ::: "memory");
    asm volatile("bar.sync 5, %0;" :: "n"(NCW * 128) : "memory");

    const uint32_t ln = __shfl_sync(0xffffffffu, lane, lane);
    const uint32_t q0 = __shfl_sync(0xffffffffu, (lane & 3) ? 0u : 0xffffffffu, lane);
    const uint32_t meta = __shfl_sync(0xffffffffu, 0x88dddd88u + (grid >> 20), lane);
    const uint32_t zr = grid >> 20;
    const uint32_t sel = (ring + R_SEL) >> 4;
    const uint32_t ost = __shfl_sync(0xffffffffu, w * 1024 + lane * 16, lane);
    const uint32_t first = ring;
    const uint32_t last = first + (NSLOT - 1) * SLOT_BYTES;
    uint32_t sa = first, phase = 0;
    uint32_t we[16];
    auto make_weff = [&](uint32_t ta) {
      uint32_t t[8];
      ta += (ln & 24) << 1;
      ldsm_x4(ta, t[0], t[1], t[2], t[3]);
      ldsm_x4(ta + 64, t[4], t[5], t[6], t[7]);
#pragma unroll
      for (int i = 0; i < 16; i++) we[i] = hfma2_bf16(t[i >> 1], wd[i], wac[i]);
    };
    auto make_bq = [&](const float (&bz)[4]) {
#pragma unroll
      for (int e = 0; e < 2; e++) {
        const uint32_t v = __float_as_uint(bz[2 * e]) & q0;
        const float hi = __uint_as_float(v & 0xffff0000u);
        bq[e] = pack_bf16(__uint_as_float(v) - hi, hi);
      }
    };
    if (active) {
      {
        float bz[4];
        uint64_t d0 = (uint64_t)DESC_ROWS << 32 | (ring + R_TGT0) >> 4;
        mma_fence();
        bias_out<0>(bz, wbc, d0);
        make_weff(ring + R_TGT0);
        mma_wait<0>(bz);
        make_bq(bz);
      }
      STAMP(1);
      uint32_t raw = 0, cur, hdr;
      uint32_t full = 0;
      uint32_t ra, bar, *dst;
      auto finish_at = [&]() {
        ra = cur + S_OUT + w * 256 + (ln >> 4) * 1024 + (ln & 15) * 16;
        dst = reinterpret_cast<uint32_t*>(out) + (lds32(cur + S_ROW + (hdr >> 31) * 4) * 32u + 4 * w + (ln & 4) * 4 + (ln >> 3));
        bar = 2 + wg;
      };
      auto finish = [&](uint32_t skip) {
        asm volatile("bar.sync %0, 128;" :: "r"(bar) : "memory");
        uint32_t f0[4], f1[4];
        ldsm_x4_t(ra, f0[0], f0[1], f0[2], f0[3]);
        ldsm_x4_t(ra + 2048, f1[0], f1[1], f1[2], f1[3]);
        float c0[4] = {0.f, 0.f, 0.f, 0.f}, c1[4] = {0.f, 0.f, 0.f, 0.f};
        mma_bf16(c0, f0, 0x3f803f80u);
        mma_bf16(c1, f1, 0x3f803f80u);
        asm volatile("{\n.reg .pred p;\nsetp.eq.u32 p, %2, 0;\n@p st.global.u32 [%0], %1;\n}\n"
                     :: "l"(dst), "r"(pack_bf16(c0[0] + c1[0], c0[2] + c1[2])), "r"(skip) : "memory");
      };
      auto chunk = [&](auto groups, auto is_last) {
        constexpr int N8 = decltype(groups)::value, NY = N8 - NA;
        constexpr bool LAST = decltype(is_last)::value;
        constexpr int KT = (N8 + 1) / 2, E1 = KT - (N8 == 16 ? 3 : N8 == 14 ? KL14 : KL), E0 = N8 < 16 && K0 < E1 ? K0 : E1;
        float x[4 * NA], y[4 * NY], bz[4], o[16];
        uint32_t a[4 * E0], a1[E1 > E0 ? 4 * (E1 - E0) : 4], a2[4 * (KT - E1)];
        auto M = [&](int i0, int i1) {
#pragma unroll
          for (int i = i0; i < i1; i++) {
            uint32_t p = i < NA ? mix(x, i, w2a, w2b, c32) : i < N8 ? mix(y, i - NA, w2a, w2b, c32) : 0;
            if (N8 == 16) {
              uint32_t m = 0x3f803f80u;
              asm volatile("{\n.reg .pred p;\nsetp.ne.u32 p, %1, 0;\n@p ld.shared.u32 %0, [%2];\n}\n"
                           : "+r"(m) : "r"(hdr & H_GENERAL), "r"(cur + S_MASK + i * 16 + (ln & 3) * 4) : "memory");
              p = hfma2_bf16(p, m, 0x80008000u);
            }
            if (i < 2 * E0) a[2 * i] = a[2 * i + 1] = p;
            else if (i < 2 * E1) a1[2 * i - 4 * E0] = a1[2 * i - 4 * E0 + 1] = p;
            else a2[2 * i - 4 * E1] = a2[2 * i - 4 * E1 + 1] = p;
          }
        };
        auto header = [&]() {
          raw = lds32(sa + S_HDR);
          raw = (raw >> 31) == phase ? 0 : raw;
        };
        const uint32_t sta = cur + S_OUT + ost;
        uint64_t db = (uint64_t)(DESC_ROWS + (cur >> 24)) << 32 | cur >> 4;
        const uint32_t par = phase;
        phase ^= sa == last;
        sa = sa == last ? first : sa + SLOT_BYTES;
        mma_fence();
        bias_in(x, bq, sel);
        bias_in(y, bq, sel);
        mbar_wait_unless(full, cur + S_FULL, par);
        LOGT(0);
        mma_fence();
        gemm1<0>(x, we, db);
        if (!LAST) bias_out<S_TGT / 16>(bz, wbc, db);
        mma_wait<!LAST>(x);
        const uint32_t there = mbar_test(cur + S_REST, par);
        if (LAST) finish_at();
        tanh_range(x, 0, 4 * SA);
        mbar_wait_unless(there, cur + S_REST, par);
        LOGT(2);
        mma_fence();
        gemm1<64 * NA>(y, we, db);
        tanh_range(x, 4 * SA, 4 * (SA + SB));
        if (__builtin_expect(zr != 0, 0)) {
          __nanosleep(zr);
#pragma unroll
          for (int i = 4 * (SA + SB); i < 4 * NA; i++) asm volatile("mov.b32 %0, %1;" : "=f"(x[i]) : "r"(ln));
        }
        tanh_range(x, 4 * (SA + SB), 4 * NA);
        M(0, NA - 1);
        if (__builtin_expect(zr != 0, 0)) {
          __nanosleep(zr);
#pragma unroll
          for (int i = 0; i < NA - 1; i++) sts32(zr + i, a[2 * i]);
#pragma unroll
          for (int i = 4 * NA - 4; i < 4 * NA; i++) sts32(zr + i, __float_as_uint(x[i]));
          if (LAST) asm volatile("mov.b32 %0, %3;\nmov.b32 %1, %3;\nmov.b64 %2, {%3, %3};" : "=r"(ra), "=r"(bar), "=l"(dst) : "r"(ln));
        }
        mma_wait<0>(y);
        if (!LAST) asm volatile("" : "+f"(bz[0]), "+f"(bz[2]) :: "memory");
        if (!LAST) header();
        tanh_range(y, 0, 4 * (2 * E0 - NA));
        if (!LAST) make_weff(cur + S_TGT);
        M(NA - 1, 2 * E0);
        auto after = [&](uint32_t g, uint32_t u, auto more) {
          asm volatile("{\n.reg .b32 lo, hi, z;\n.reg .pred p;\nand.b32 z, %1, %2;\nsetp.ne.u32 p, z, 0;\nvote.sync.ballot.b32 z, p, 0xffffffff;\n"
                       "and.b32 z, z, %4;\nmov.b64 {lo, hi}, %0;\nadd.u32 hi, hi, %3;\nadd.u32 hi, hi, z;\nmov.b64 %0, {lo, hi};\n}\n"
                       : "+l"(db) : "r"(g), "r"(zr), "n"(decltype(more)::value), "r"(u));
        };
        constexpr int EP = LAST ? 0 : TP == 3 && E1 == E0 ? 2 : TP;
        if (EP >= 2) { make_bq(bz); raw = __shfl_sync(0xffffffffu, raw, 0); }
        after(a[4 * E0 - 2] | a[4 * E0 - 4] | (EP == 2 ? bq[0] | bq[1] | sta : 0), EP == 2 ? raw : ~0u, Int<(int)(DESC_HALVES - DESC_ROWS)>());
        gemm2_first<0>(o, a, db, meta);
        if constexpr (E1 > E0) {
          tanh_range(y, 4 * (2 * E0 - NA), 4 * (2 * E1 - NA));
          M(2 * E0, 2 * E1);
          if (EP == 3) after(bq[0] | bq[1] | sta, raw, Int<0>());
          gemm2_more<128 * E0>(o, a1, db, meta);
        }
        tanh_range(y, 4 * (2 * E1 - NA), 4 * NY);
        M(2 * E1, 2 * KT);
        gemm2_more<128 * E1>(o, a2, db, meta);
        if (!LAST) {
          full = mbar_test(sa + S_FULL, phase);
        }
        mma_wait<0>(o);
#pragma unroll
        for (int j = 0; j < 2; j++)
          stsm_x4(sta + j * 512, pack_bf16(o[8 * j], o[8 * j + 2]), pack_bf16(o[8 * j + 1], o[8 * j + 3]),
                  pack_bf16(o[8 * j + 4], o[8 * j + 6]), pack_bf16(o[8 * j + 5], o[8 * j + 7]));
        LOGT(1);
        if (LAST) {
          finish(0);
        } else {
          __syncwarp();
          asm volatile("{\n.reg .pred p;\nsetp.eq.u32 p, %1, 0;\n@p mbarrier.arrive.shared::cta.b64 _, [%0];\n}\n"
                       :: "r"(cur + S_EMPTY), "r"(FIN && N8 < 16 ? ln : ln | (hdr & H_SELF)) : "memory");
        }
      };
      while (true) {
        hdr = __shfl_sync(0xffffffffu, raw, 0);
        cur = sa;
        if (hdr & H_13) { chunk(Int<13>(), Int<0>()); if (hdr & H_FINAL) break; }
        else if (hdr & H_12) { chunk(Int<12>(), Int<0>()); if (hdr & H_FINAL) break; }
        else if (hdr & H_14) { chunk(Int<14>(), Int<0>()); if (hdr & H_FINAL) break; }
        else if (hdr & H_15) { chunk(Int<15>(), Int<0>()); if (hdr & H_FINAL) break; }
        else if (FIN && (hdr & 0x1e0)) break;
        else if (hdr) { chunk(Int<16>(), Int<0>()); if (hdr & H_FINAL) break; }
        else {
          asm volatile("{\n.reg .pred p;\n.reg .u32 n, t;\nmov.u32 n, 0;\n"
                       "AGAIN:\nnanosleep.u32 32;\nld.shared.u32 %0, [%1];\nshfl.sync.idx.b32 %0, %0, 0, 31, 0xffffffff;\n"
                       "shr.u32 t, %0, 31;\nsetp.ne.u32 p, t, %2;\n@p bra.uni THERE;\n"
                       "add.u32 n, n, 1;\nsetp.lt.u32 p, n, 0x1000000;\n@p bra.uni AGAIN;\ntrap;\nTHERE:\n}\n"
                       : "=r"(raw) : "r"(sa + S_HDR), "r"(phase) : "memory");
        }
      }
      if (FIN && (hdr & H_13 << 4)) chunk(Int<13>(), Int<1>());
      else if (FIN && (hdr & H_12 << 4)) chunk(Int<12>(), Int<1>());
      else if (FIN && (hdr & H_14 << 4)) chunk(Int<14>(), Int<1>());
      else if (FIN && (hdr & H_15 << 4)) chunk(Int<15>(), Int<1>());
      else
      {
        finish_at();
        finish(~hdr & H_SELF);
      }
    }
    STAMP(4);
  } else {
    const int pw = warp - NCW * 4;
    const uint32_t ring = sb + pw * RING_BYTES;
    asm volatile("setmaxnreg.dec.sync.aligned.u32 %0;" :: "n"(PROD_REGS));
    if (pw < NCW) {
      int b = pw * grid + blockIdx.x, bn = b + bstep;
      uint4 mw = load_mask(mask, min(b, B - 1), min(lane, 24));
      if (lane == 0) {
#pragma unroll
        for (int i = 0; i < NSLOT; i++) {
          mbar_init(ring + i * SLOT_BYTES + S_FULL, 33);
          mbar_init(ring + i * SLOT_BYTES + S_REST, 33);
          mbar_arrive(ring + i * SLOT_BYTES + S_REST);
          mbar_init(ring + i * SLOT_BYTES + S_EMPTY, 4);
          sts32(ring + i * SLOT_BYTES + S_HDR, 0);
        }
        sts32(ring + R_STOP, b < B && pw < ACT ? 0 : ring);
      }
      sts32(sb + R_PACE + lane * 4, 0);
      asm volatile("bar.arrive 1, %0;" :: "n"(NCW * 160) : "memory");
      asm volatile("bar.arrive 6, 128;" ::: "memory");
      if (pw >= ACT) return;
      const uint32_t list = ring + R_LIST;
      uint32_t lt;
      asm("mov.u32 %0, %%lanemask_lt;" : "=r"(lt));
      const uint32_t ln = __shfl_sync(0xffffffffu, lane, lane);
      const uint32_t r4 = (ln >> 3) * 4, c16 = (ln & 7) * 16, l25 = min(ln, 24u);
      const uint32_t pick = ln < 25 ? 0xeca8 : 0x9999;
      uint32_t dst[4];
#pragma unroll
      for (int i = 0; i < 4; i++) dst[i] = ring + (r4 + i) * 128 + (c16 ^ (((r4 + i) & 7) << 4));
      uint64_t pol;
      asm("createpolicy.fractional.L2::evict_first.b64 %0, 1.0;" : "=l"(pol));
      uint32_t sa = ring, phase = 1;
      const uint32_t wrap = (uint32_t)(max(B - NSTATIC * bstep, 0) + bstep - 1);
      auto next_slot = [&]() {
        const bool wrapped = sa == ring + (NSLOT - 1) * SLOT_BYTES;
        const int step = wrapped ? -(NSLOT - 1) * SLOT_BYTES : SLOT_BYTES;
        sa += step;
        phase ^= wrapped;
#pragma unroll
        for (int i = 0; i < 4; i++) dst[i] += step;
      };
      uint32_t claimer = ln;
      uint32_t drawn, started = 0;
      auto draw = [&]() {
        drawn = B;
        asm volatile("{\n.reg .pred p;\nsetp.eq.u32 p, %3, 0;\n@p atom.global.inc.u32 %0, [%1], %2;\n}\n"
                     : "+r"(drawn) : "l"(counter), "r"(wrap), "r"(claimer) : "memory");
      };
      if (b >= B) draw();
      while (b < B) {
        const uint32_t e0 = nonzero_as_one(mw.x), e1 = nonzero_as_one(mw.y);
        const uint32_t e2 = nonzero_as_one(mw.z), e3 = nonzero_as_one(mw.w);
        const uint32_t nonbin = (e0 ^ mw.x) | (e1 ^ mw.y) | (e2 ^ mw.z) | (e3 ^ mw.w);
        const uint32_t sA = prmt(e0, e1, pick), sB = prmt(e2, e3, pick);
        const uint32_t pA = (sA & 0x01010101u) * 0x01010101u;
        const uint32_t pB = ((sB & 0x01010101u) + (pA >> 24)) * 0x01010101u;
        uint32_t pos = 0;
        int n = 0;
#pragma unroll
        for (int k = 0; k < 4; k++) {
          const uint32_t bal = ballot_bit(pB, 0x01000000u << k);
          pos += __popc(bal & lt) << k;
          n += __popc(bal) << k;
        }
        const uint32_t general = __any_sync(0xffffffffu, nonbin != 0);
        const uint32_t aA = (pA + pos * 0x01010101u) | ~sA, aB = (pB + pos * 0x01010101u) | ~sB;
#pragma unroll
        for (int i = 0; i < 8; i++) sts8(list - 1 + prmt(i < 4 ? aA : aB, 0, 0x4440 + (i & 3)), 8 * ln + i);
        __syncwarp();

        const uint64_t src = reinterpret_cast<uint64_t>(hist) + (uint64_t)b * (kL * kD * 2);
        const bool no_carry = (uint32_t)src <= 0xffffffffu - kL * kD * 2;
        auto begin_fill = [&](uint32_t h, uint32_t part, int nc, int bt, auto extra) {
          LOGT(0);
          mbar_wait(sa + S_EMPTY, phase);
          if (bt >= B) h = part ? h | H_FINAL : (FIN && h < H_16 ? h << 4 : h) | H_FINAL | H_SELF;
          asm volatile("{\n.reg .pred p;\nsetp.ne.u32 p, %2, 0;\n@p st.shared.u32 [%0], %1;\n}\n"
                       :: "r"(ring + R_STOP), "r"(sa + (phase ^ 1)), "r"(h & H_SELF) : "memory");
          extra();
          sts32(sa + S_HDR, h | phase << 31);
          sts32(sa + S_ROW + phase * 4, b | part);
          asm volatile("{\n.reg .pred p;\nsetp.eq.u32 p, %1, 0;\n@p mbarrier.arrive.shared::cta.b64 _, [%0];\n}\n"
                       :: "r"(sa + S_FULL), "r"(ln) : "memory");
          asm volatile("{\n.reg .u32 c;\n"
                       "mov.u32 c, %%globaltimer_lo;\n"
                       "red.shared.max.u32 [%1], c;\n"
                       "atom.shared.add.u32 %0, [%1], %2;\n}\n"
                       : "=r"(started) : "r"(sb + R_PACE + ln * 4), "r"(nc * (bn >= slow_from ? pace_slow : pace) >> 4) : "memory");
          started = __shfl_sync(0xffffffffu, started, 0);
          if (!(part & ROW_REST)) mw = load_mask(mask, min(bn, B - 1), l25);
          wait_for(started, pace * (CHUNK / 4));
          LOGT(1);
          if (!(part & ROW_REST)) draw();
          asm volatile("cp.async.ca.shared.global [%0], [%1], 4;"
                       :: "r"(sa + S_TGT + ln * 4), "l"(reinterpret_cast<const uint32_t*>(target) + ((uint32_t)min(bt, B - 1) * 32u + ln)) : "memory");
        };
        auto end_fill = [&](int nc) {
          cp_async_arrive_noinc(sa + S_REST);
          next_slot();
          LOGT(2);
        };
        const uint32_t base = (uint32_t)src + c16;
        uint64_t a[4];
        a[0] = a[1] = a[2] = a[3] = (uint64_t)((uint32_t)(src >> 32) + (ln >> 5)) << 32;
        if (__builtin_expect(no_carry && !general && n >= 80 && n <= CHUNK, 1)) {
          uint32_t idx[7];
#pragma unroll
          for (int t = 0; t < 7; t++) idx[t] = lds32(list + r4 + t * 16);
          uint32_t have;
          asm("bmsk.clamp.b32 %0, 0, %1;" : "=r"(have) : "r"(max(n - 80 - (int)r4, 0)));
          begin_fill(size_bit(n), 0, n, bn, [](){});
          cp_group<0>(dst, a, idx[0], base, pol);
          cp_group<1>(dst, a, idx[1], base, pol);
          cp_group<2>(dst, a, idx[2], base, pol);
          cp_async_arrive_noinc(sa + S_FULL);
          if (bn >= slow_from) wait_for(started + spread, spread);
          cp_group<3>(dst, a, idx[3], base, pol);
          cp_group<4>(dst, a, idx[4], base, pol);
          cp_group_m<5, 0>(dst, a, idx[5], base, have, 1, pol);
          cp_group_m<6, 16>(dst, a, idx[6], base, have, n > 96, pol);
          if (n > 112) cp_group_z<7>(dst, a, lds32(list + r4 + 112), base, n - r4, pol);
          end_fill(n);
        } else if (no_carry && !general) {
          int nc = n <= CHUNK ? n : n <= 160 ? 64 : 96;
          uint32_t la = list + r4, part = n <= CHUNK ? 0 : ROW_MORE;
#pragma unroll 1
          while (true) {
            begin_fill(size_bit(nc), part, nc, part == ROW_MORE ? b : bn, [](){});
            const int left = nc - r4;
            cp_group_z<0>(dst, a, lds32(la), base, left, pol);
            cp_group_z<1>(dst, a, lds32(la + 16), base, left, pol);
            cp_group_z<2>(dst, a, lds32(la + 32), base, left, pol);
            cp_async_arrive_noinc(sa + S_FULL);
            if (bn >= slow_from) wait_for(started + spread, spread);
            cp_group_z<3>(dst, a, lds32(la + 48), base, left, pol);
            cp_group_z<4>(dst, a, lds32(la + 64), base, left, pol);
            cp_group_z<5>(dst, a, lds32(la + 80), base, left, pol);
            cp_group_z<6>(dst, a, lds32(la + 96), base, left, pol);
            cp_group_z<7>(dst, a, lds32(la + 112), base, left, pol);
            end_fill(nc);
            if (part != ROW_MORE) break;
            la += nc;
            nc = n - nc;
            part = ROW_REST;
          }
        } else {
          int r0 = 0;
#pragma unroll 1
          do {
            const int nc = min(n - r0, CHUNK);
            const bool more = r0 + CHUNK < n;
            begin_fill(general ? H_GENERAL : H_16, (more ? ROW_MORE : 0u) | (r0 ? ROW_REST : 0u), nc, more ? b : bn, [&]() {
#pragma unroll 1
              for (int z = ln; general && z < CHUNK; z += 32) {
                uint32_t v = 0;
                if (z < nc) {
                  uint32_t row;
                  asm volatile("ld.shared.u8 %0, [%1];" : "=r"(row) : "r"(list + r0 + z) : "memory");
                  v = __bfloat16_as_ushort(mask[(size_t)b * kL + row]);
                }
                sts16(sa + S_MASK + z * 2, v);
              }
              __syncwarp();
            });
#pragma unroll 1
            for (int z = r4 >> 2; z < CHUNK; z += 4) {
              uint32_t row;
              asm volatile("ld.shared.u8 %0, [%1];" : "=r"(row) : "r"(list + r0 + z) : "memory");
              asm volatile("cp.async.cg.shared.global [%0], [%1], 16, %2;"
                           :: "r"(sa + z * 128 + (c16 ^ ((z & 7) << 4))), "l"(src + c16 + (z < nc ? row : 0) * 128),
                              "r"(z < nc ? 16 : 0) : "memory");
            }
            cp_async_arrive_noinc(sa + S_FULL);
            end_fill(nc);
            r0 += CHUNK;
          } while (r0 < n);
        }
        b = bn;
        bn = __shfl_sync(0xffffffffu, drawn, 0) + NSTATIC * bstep;
        if (bn >= B) claimer = 1;
      }
      STAMP(3);
      if (lds32(ring + R_STOP) == 0) sts32(ring + R_STOP, sa + (phase ^ 1));
      asm volatile("cp.async.wait_all;" ::: "memory");
      STAMP(4);
    } else {
      uint32_t due = clock();
      int s0 = NSTATIC * bstep + (PF_EARLY * grid + blockIdx.x) * PF_ROWS;
      auto prefetch = [&]() {
        const int cnt = min(PF_ROWS, B - s0);
        if (lane == 0) {
          prefetch_l2(mask + (size_t)s0 * kL, cnt * kL * 2);
          prefetch_l2(target + (size_t)s0 * kD, cnt * kD * 2);
        }
        s0 += grid * PF_ROWS;
      };
#pragma unroll 1
      for (int j = PF_EARLY; j < PF_FAST && s0 < B; j++) {
        while ((int)(due - (uint32_t)clock()) > 0) {}
        prefetch();
        due += PF_CYCLES;
      }
      due += (PF_FAST - 1) * PF_SLOW - (PF_FAST - PF_EARLY) * PF_CYCLES + (blockIdx.x & 255) * (PF_SLOW / 256);
      asm volatile("bar.sync 6, 128;" ::: "memory");
      const uint32_t ln = __shfl_sync(0xffffffffu, lane, lane);
      const uint32_t home = sb + min(ln, NCW - 1u) * RING_BYTES;
      uint32_t mine = ln < NCW ? home : 0;
      const uint32_t rd = __shfl_sync(0xffffffffu, S_OUT + (lane >> 4) * 1024 + (lane & 15) * 16, lane);
      const uint32_t word = __shfl_sync(0xffffffffu, (lane & 4) * 4 + (lane & 3) * 4 + (lane >> 3), lane);
      uint32_t idle = 0, r = 0, at;
      auto poll = [&]() {
        uint32_t ready;
        asm volatile("{\n.reg .pred p;\nsetp.ne.u32 p, %3, 0;\n@p mbarrier.test_wait.parity.shared::cta.b64 p, [%1], %2;\n"
                     "vote.sync.ballot.b32 %0, p, 0xffffffff;\n}\n"
                     : "=r"(ready) : "r"((mine & ~1u) + S_EMPTY), "r"(mine & 1), "r"(mine) : "memory");
        static_assert(NCW == 3, "");
        const uint32_t pick = ((r == 0 ? 0x5a53u : r == 1 ? 0xaa13u : 0x1213u) >> (2 * ready)) & 3;
        at = __shfl_sync(0xffffffffu, mine, pick);
        r = ready ? pick : r;
      };
      poll();
#pragma unroll 1
      while (true) {
        if (at) {
          const uint32_t sa = at & ~1u, carry = sb + r * RING_BYTES + R_CARRY + ln * 8;
          uint32_t f[8][4];
#pragma unroll
          for (int i = 0; i < 8; i++) ldsm_x4_t(sa + rd + (i >> 2) * 2048 + (i & 3) * 256, f[i][0], f[i][1], f[i][2], f[i][3]);
          const uint32_t row = lds32(sa + S_ROW + 4 - (at & 1) * 4);
          if (ln == r) mine = sa == home + (NSLOT - 1) * SLOT_BYTES ? (at - (NSLOT - 1) * SLOT_BYTES) ^ 1 : at + SLOT_BYTES;
          float c[8][4];
#pragma unroll
          for (int i = 0; i < 8; i++) {
            c[i][0] = c[i][1] = c[i][2] = c[i][3] = 0.f;
            mma_bf16(c[i], f[i], 0x3f803f80u);
          }
          poll();
          asm volatile("{\n.reg .pred p;\nsetp.eq.u32 p, %1, 0;\n@p mbarrier.arrive.shared::cta.b64 _, [%0];\n}\n"
                       :: "r"(sa + S_REST), "r"(ln) : "memory");
          float e[2];
#pragma unroll
          for (int k = 0; k < 2; k++) {
            const float u0 = ln & 1 ? c[1][2 * k] : c[0][2 * k], u1 = ln & 1 ? c[3][2 * k] : c[2][2 * k];
            const float u2 = ln & 1 ? c[5][2 * k] : c[4][2 * k], u3 = ln & 1 ? c[7][2 * k] : c[6][2 * k];
            e[k] = ln & 2 ? u1 + u3 : u0 + u2;
          }
          asm volatile("{\n.reg .pred p, q;\n.reg .f32 a, b;\n.reg .u32 t;\nshr.u32 t, %3, 30;\nsetp.eq.u32 p, t, 1;\nsetp.eq.u32 q, t, 2;\n"
                       "@p ld.shared.v2.f32 {a, b}, [%2];\n@p add.f32 %0, %0, a;\n@p add.f32 %1, %1, b;\n@q st.shared.v2.f32 [%2], {%0, %1};\n}\n"
                       : "+f"(e[0]), "+f"(e[1]) : "r"(carry), "r"(row) : "memory");
          asm volatile("{\n.reg .pred p;\nsetp.ge.s32 p, %2, 0;\n@p st.global.u32 [%0], %1;\n}\n"
                       :: "l"(reinterpret_cast<uint32_t*>(out) + (row * 32u + word)), "r"(pack_bf16(e[0], e[1])), "r"(row) : "memory");
        } else {
          const uint32_t stop = lds32(home + R_STOP);
          poll();
          if (stop == mine) mine = 0;
          if (!__any_sync(0xffffffffu, mine)) break;
          if (s0 < B) {
            if ((int)(due - (uint32_t)clock()) <= 0) { prefetch(); due += PF_SLOW; }
          } else if (++idle > 0x10000000) __trap();
          if (RED_SLEEP) __nanosleep(RED_SLEEP);
        }
      }
      STAMP(4);
    }
  }
}

}

extern "C" void kernel_launch(void* const* d_in, const int* in_sizes, int n_in, void* d_out, int out_size) {
  const __nv_bfloat16* target = (const __nv_bfloat16*)d_in[0];
  const __nv_bfloat16* hist = (const __nv_bfloat16*)d_in[1];
  const __nv_bfloat16* mask = (const __nv_bfloat16*)d_in[2];
  const __nv_bfloat16* w1 = (const __nv_bfloat16*)d_in[3];
  const __nv_bfloat16* b1 = (const __nv_bfloat16*)d_in[4];
  const __nv_bfloat16* w2 = (const __nv_bfloat16*)d_in[5];
  const __nv_bfloat16* b2 = (const __nv_bfloat16*)d_in[6];
  const int B = in_sizes[0] / din::kD;
  if (B <= 0) return;
  static int sms = 0, pace = 0;
  static unsigned int* counter = nullptr;
  if (sms == 0) {
    int dev = 0, khz = 0, bits = 0;
    cudaGetDevice(&dev);
    cudaDeviceGetAttribute(&sms, cudaDevAttrMultiProcessorCount, dev);
    cudaDeviceGetAttribute(&khz, cudaDevAttrMemoryClockRate, dev);
    cudaDeviceGetAttribute(&bits, cudaDevAttrGlobalMemoryBusWidth, dev);
    if (khz > 0 && bits > 0) pace = (int)(16.0 * 128.0 * sms / (khz * 1e-6 * 2.0 * bits / 8.0));
    if (pace > 256) pace = 0;
    cudaGetSymbolAddress((void**)&counter, din::g_next);
    cudaFuncSetAttribute(din::din_kernel, cudaFuncAttributeMaxDynamicSharedMemorySize, din::SMEM_BYTES);
  }
  const long long early = (long long)(din::NSTATIC * NCW + PF_EARLY * PF_ROWS) * sms, line = 128LL * sms;
  long long pf_mask = (early * din::kL * 2 + line - 1) / line, pf_tgt = early * din::kD * 2 / line;
  if (pf_mask > (long long)B * din::kL * 2 / line) pf_mask = (long long)B * din::kL * 2 / line;
  if (pf_tgt > (long long)B * din::kD * 2 / line) pf_tgt = (long long)B * din::kD * 2 / line;
  din::din_kernel<<<sms, din::NTHREADS, din::SMEM_BYTES>>>(mask, target, B, sms, (uint32_t)pf_mask * 128, (uint32_t)pf_tgt * 128,
                                                          w1, hist, b1, w2, b2, (__nv_bfloat16*)d_out, counter, pace,
                                                          B - SLOW_ROUNDS * NCW * sms / 2, pace + (pace * SLOW_BY + 40) / 80,
                                                          pace * SPREAD / 16);
}
```

```cpp
#include <cuda_runtime.h>
#include <cuda_bf16.h>
#include <stdint.h>

namespace din {

constexpr int kL = 200, kD = 64;
#define NCW 3
#define NSLOT 3
constexpr int CHUNK = 128;
constexpr int NTHREADS = NCW * 128 + 128;
#define PREGS 56
#define CREGS 152
constexpr int PROD_REGS = PREGS, CONS_REGS = CREGS;
#define PF_ROWS 8
#define PF_FAST 10
#define PF_SLOW 2000
#define PF_CYCLES 280
#define RED_SLEEP 0
#define KL 2
#define KL14 2
#define K0 3
#define SA 2
#define SB 1
#define TP 3
#define SPREAD 62
#define SLOW_ROUNDS 12
#define SLOW_BY 9
#define PF_EARLY 3
constexpr int NSTATIC = 2;
constexpr int S_TGT = CHUNK * 128;
constexpr int S_HDR = S_TGT + 128;
constexpr int S_FULL = S_HDR + 8;
constexpr int S_EMPTY = S_HDR + 16;
constexpr int S_ROW = S_HDR + 24;
constexpr int S_REST = S_HDR + 32;
constexpr int S_MASK = S_TGT + 256;
constexpr int S_OUT = S_TGT + 1024;
constexpr int SLOT_BYTES = S_OUT + 8192;
constexpr int RING_BYTES_ = NSLOT * SLOT_BYTES;
constexpr int R_PACE = 2 * RING_BYTES_ + S_TGT + 768;
constexpr int R_STOP = S_HDR + 40;
constexpr int R_LIST = S_TGT + 512;
constexpr int R_VEC = S_TGT + 768;
constexpr int R_SEL = S_TGT + 896;
constexpr int R_CARRY = SLOT_BYTES + S_TGT + 512;
constexpr int R_TGT0 = (NSLOT - 1) * SLOT_BYTES + S_OUT;
constexpr int RING_BYTES = NSLOT * SLOT_BYTES;
constexpr int SMEM_BYTES = NCW * RING_BYTES + 1024;
__device__ constexpr int w1_at(int i) { return (i >> 1) * RING_BYTES + (i & 1) * SLOT_BYTES + S_OUT; }
#define LOGT(slot)
static_assert(SMEM_BYTES <= 232448, "shared memory");
constexpr uint32_t H_12 = 2, H_13 = 4, H_14 = 8, H_15 = 16, H_16 = 1u << 16;
constexpr uint32_t H_GENERAL = 1u << 17, H_FINAL = 1u << 18, H_STOP = 1u << 19;
constexpr uint32_t ROW_REST = 1u << 30, ROW_MORE = 1u << 31;

__device__ unsigned int g_next;

#define STAMP(k)

#define STR2(x) #x
#define STR(x) STR2(x)
constexpr int NA = 5;
__device__ __forceinline__ void bias_in(float (&d)[20], const uint32_t (&a)[4], uint32_t lo) {
  asm volatile("{\n.reg .b64 db;\n"
    "cvt.u64.u32 db, %24;\n"
    "wgmma.mma_async.sync.aligned.m64n40k16.f32.bf16.bf16 {%0, %1, %2, %3, %4, %5, %6, %7, %8, %9, %10, %11, %12, %13, %14, %15, %16, %17, %18, %19}, {%20, %21, %22, %23}, db, 0, 1, 1, 0;\n}\n"
    : "=f"(d[0]), "=f"(d[1]), "=f"(d[2]), "=f"(d[3]), "=f"(d[4]), "=f"(d[5]), "=f"(d[6]), "=f"(d[7]), "=f"(d[8]), "=f"(d[9]), "=f"(d[10]), "=f"(d[11]), "=f"(d[12]), "=f"(d[13]), "=f"(d[14]), "=f"(d[15]), "=f"(d[16]), "=f"(d[17]), "=f"(d[18]), "=f"(d[19])
    : "r"(a[0]), "r"(a[1]), "r"(a[2]), "r"(a[3]), "r"(lo)
    : "memory");
}
__device__ __forceinline__ void bias_in(float (&d)[28], const uint32_t (&a)[4], uint32_t lo) {
  asm volatile("{\n.reg .b64 db;\n"
    "cvt.u64.u32 db, %32;\n"
    "wgmma.mma_async.sync.aligned.m64n56k16.f32.bf16.bf16 {%0, %1, %2, %3, %4, %5, %6, %7, %8, %9, %10, %11, %12, %13, %14, %15, %16, %17, %18, %19, %20, %21, %22, %23, %24, %25, %26, %27}, {%28, %29, %30, %31}, db, 0, 1, 1, 0;\n}\n"
    : "=f"(d[0]), "=f"(d[1]), "=f"(d[2]), "=f"(d[3]), "=f"(d[4]), "=f"(d[5]), "=f"(d[6]), "=f"(d[7]), "=f"(d[8]), "=f"(d[9]), "=f"(d[10]), "=f"(d[11]), "=f"(d[12]), "=f"(d[13]), "=f"(d[14]), "=f"(d[15]), "=f"(d[16]), "=f"(d[17]), "=f"(d[18]), "=f"(d[19]), "=f"(d[20]), "=f"(d[21]), "=f"(d[22]), "=f"(d[23]), "=f"(d[24]), "=f"(d[25]), "=f"(d[26]), "=f"(d[27])
    : "r"(a[0]), "r"(a[1]), "r"(a[2]), "r"(a[3]), "r"(lo)
    : "memory");
}
__device__ __forceinline__ void bias_in(float (&d)[32], const uint32_t (&a)[4], uint32_t lo) {
  asm volatile("{\n.reg .b64 db;\n"
    "cvt.u64.u32 db, %36;\n"
    "wgmma.mma_async.sync.aligned.m64n64k16.f32.bf16.bf16 {%0, %1, %2, %3, %4, %5, %6, %7, %8, %9, %10, %11, %12, %13, %14, %15, %16, %17, %18, %19, %20, %21, %22, %23, %24, %25, %26, %27, %28, %29, %30, %31}, {%32, %33, %34, %35}, db, 0, 1, 1, 0;\n}\n"
    : "=f"(d[0]), "=f"(d[1]), "=f"(d[2]), "=f"(d[3]), "=f"(d[4]), "=f"(d[5]), "=f"(d[6]), "=f"(d[7]), "=f"(d[8]), "=f"(d[9]), "=f"(d[10]), "=f"(d[11]), "=f"(d[12]), "=f"(d[13]), "=f"(d[14]), "=f"(d[15]), "=f"(d[16]), "=f"(d[17]), "=f"(d[18]), "=f"(d[19]), "=f"(d[20]), "=f"(d[21]), "=f"(d[22]), "=f"(d[23]), "=f"(d[24]), "=f"(d[25]), "=f"(d[26]), "=f"(d[27]), "=f"(d[28]), "=f"(d[29]), "=f"(d[30]), "=f"(d[31])
    : "r"(a[0]), "r"(a[1]), "r"(a[2]), "r"(a[3]), "r"(lo)
    : "memory");
}
__device__ __forceinline__ void bias_in(float (&d)[36], const uint32_t (&a)[4], uint32_t lo) {
  asm volatile("{\n.reg .b64 db;\n"
    "cvt.u64.u32 db, %40;\n"
    "wgmma.mma_async.sync.aligned.m64n72k16.f32.bf16.bf16 {%0, %1, %2, %3, %4, %5, %6, %7, %8, %9, %10, %11, %12, %13, %14, %15, %16, %17, %18, %19, %20, %21, %22, %23, %24, %25, %26, %27, %28, %29, %30, %31, %32, %33, %34, %35}, {%36, %37, %38, %39}, db, 0, 1, 1, 0;\n}\n"
    : "=f"(d[0]), "=f"(d[1]), "=f"(d[2]), "=f"(d[3]), "=f"(d[4]), "=f"(d[5]), "=f"(d[6]), "=f"(d[7]), "=f"(d[8]), "=f"(d[9]), "=f"(d[10]), "=f"(d[11]), "=f"(d[12]), "=f"(d[13]), "=f"(d[14]), "=f"(d[15]), "=f"(d[16]), "=f"(d[17]), "=f"(d[18]), "=f"(d[19]), "=f"(d[20]), "=f"(d[21]), "=f"(d[22]), "=f"(d[23]), "=f"(d[24]), "=f"(d[25]), "=f"(d[26]), "=f"(d[27]), "=f"(d[28]), "=f"(d[29]), "=f"(d[30]), "=f"(d[31]), "=f"(d[32]), "=f"(d[33]), "=f"(d[34]), "=f"(d[35])
    : "r"(a[0]), "r"(a[1]), "r"(a[2]), "r"(a[3]), "r"(lo)
    : "memory");
}
__device__ __forceinline__ void bias_in(float (&d)[40], const uint32_t (&a)[4], uint32_t lo) {
  asm volatile("{\n.reg .b64 db;\n"
    "cvt.u64.u32 db, %44;\n"
    "wgmma.mma_async.sync.aligned.m64n80k16.f32.bf16.bf16 {%0, %1, %2, %3, %4, %5, %6, %7, %8, %9, %10, %11, %12, %13, %14, %15, %16, %17, %18, %19, %20, %21, %22, %23, %24, %25, %26, %27, %28, %29, %30, %31, %32, %33, %34, %35, %36, %37, %38, %39}, {%40, %41, %42, %43}, db, 0, 1, 1, 0;\n}\n"
    : "=f"(d[0]), "=f"(d[1]), "=f"(d[2]), "=f"(d[3]), "=f"(d[4]), "=f"(d[5]), "=f"(d[6]), "=f"(d[7]), "=f"(d[8]), "=f"(d[9]), "=f"(d[10]), "=f"(d[11]), "=f"(d[12]), "=f"(d[13]), "=f"(d[14]), "=f"(d[15]), "=f"(d[16]), "=f"(d[17]), "=f"(d[18]), "=f"(d[19]), "=f"(d[20]), "=f"(d[21]), "=f"(d[22]), "=f"(d[23]), "=f"(d[24]), "=f"(d[25]), "=f"(d[26]), "=f"(d[27]), "=f"(d[28]), "=f"(d[29]), "=f"(d[30]), "=f"(d[31]), "=f"(d[32]), "=f"(d[33]), "=f"(d[34]), "=f"(d[35]), "=f"(d[36]), "=f"(d[37]), "=f"(d[38]), "=f"(d[39])
    : "r"(a[0]), "r"(a[1]), "r"(a[2]), "r"(a[3]), "r"(lo)
    : "memory");
}
__device__ __forceinline__ void bias_in(float (&d)[44], const uint32_t (&a)[4], uint32_t lo) {
  asm volatile("{\n.reg .b64 db;\n"
    "cvt.u64.u32 db, %48;\n"
    "wgmma.mma_async.sync.aligned.m64n88k16.f32.bf16.bf16 {%0, %1, %2, %3, %4, %5, %6, %7, %8, %9, %10, %11, %12, %13, %14, %15, %16, %17, %18, %19, %20, %21, %22, %23, %24, %25, %26, %27, %28, %29, %30, %31, %32, %33, %34, %35, %36, %37, %38, %39, %40, %41, %42, %43}, {%44, %45, %46, %47}, db, 0, 1, 1, 0;\n}\n"
    : "=f"(d[0]), "=f"(d[1]), "=f"(d[2]), "=f"(d[3]), "=f"(d[4]), "=f"(d[5]), "=f"(d[6]), "=f"(d[7]), "=f"(d[8]), "=f"(d[9]), "=f"(d[10]), "=f"(d[11]), "=f"(d[12]), "=f"(d[13]), "=f"(d[14]), "=f"(d[15]), "=f"(d[16]), "=f"(d[17]), "=f"(d[18]), "=f"(d[19]), "=f"(d[20]), "=f"(d[21]), "=f"(d[22]), "=f"(d[23]), "=f"(d[24]), "=f"(d[25]), "=f"(d[26]), "=f"(d[27]), "=f"(d[28]), "=f"(d[29]), "=f"(d[30]), "=f"(d[31]), "=f"(d[32]), "=f"(d[33]), "=f"(d[34]), "=f"(d[35]), "=f"(d[36]), "=f"(d[37]), "=f"(d[38]), "=f"(d[39]), "=f"(d[40]), "=f"(d[41]), "=f"(d[42]), "=f"(d[43])
    : "r"(a[0]), "r"(a[1]), "r"(a[2]), "r"(a[3]), "r"(lo)
    : "memory");
}
template<int D> __device__ __forceinline__ void gemm1(float (&d)[20], const uint32_t (&a)[16], uint64_t db) {
  asm volatile("{\n.reg .b64 db;\n"
    "add.s64 db, %36, %37 + 0;\n"
    "wgmma.mma_async.sync.aligned.m64n40k16.f32.bf16.bf16 {%0, %1, %2, %3, %4, %5, %6, %7, %8, %9, %10, %11, %12, %13, %14, %15, %16, %17, %18, %19}, {%20, %21, %22, %23}, db, 1, 1, 1, 0;\n"
    "add.s64 db, %36, %37 + 2;\n"
    "wgmma.mma_async.sync.aligned.m64n40k16.f32.bf16.bf16 {%0, %1, %2, %3, %4, %5, %6, %7, %8, %9, %10, %11, %12, %13, %14, %15, %16, %17, %18, %19}, {%24, %25, %26, %27}, db, 1, 1, 1, 0;\n"
    "add.s64 db, %36, %37 + 4;\n"
    "wgmma.mma_async.sync.aligned.m64n40k16.f32.bf16.bf16 {%0, %1, %2, %3, %4, %5, %6, %7, %8, %9, %10, %11, %12, %13, %14, %15, %16, %17, %18, %19}, {%28, %29, %30, %31}, db, 1, 1, 1, 0;\n"
    "add.s64 db, %36, %37 + 6;\n"
    "wgmma.mma_async.sync.aligned.m64n40k16.f32.bf16.bf16 {%0, %1, %2, %3, %4, %5, %6, %7, %8, %9, %10, %11, %12, %13, %14, %15, %16, %17, %18, %19}, {%32, %33, %34, %35}, db, 1, 1, 1, 0;\n"
    "wgmma.commit_group.sync.aligned;\n}\n"
    : "+f"(d[0]), "+f"(d[1]), "+f"(d[2]), "+f"(d[3]), "+f"(d[4]), "+f"(d[5]), "+f"(d[6]), "+f"(d[7]), "+f"(d[8]), "+f"(d[9]), "+f"(d[10]), "+f"(d[11]), "+f"(d[12]), "+f"(d[13]), "+f"(d[14]), "+f"(d[15]), "+f"(d[16]), "+f"(d[17]), "+f"(d[18]), "+f"(d[19])
    : "r"(a[0]), "r"(a[1]), "r"(a[2]), "r"(a[3]), "r"(a[4]), "r"(a[5]), "r"(a[6]), "r"(a[7]), "r"(a[8]), "r"(a[9]), "r"(a[10]), "r"(a[11]), "r"(a[12]), "r"(a[13]), "r"(a[14]), "r"(a[15]), "l"(db), "n"(D)
    : "memory");
}
template<int D> __device__ __forceinline__ void gemm1(float (&d)[28], const uint32_t (&a)[16], uint64_t db) {
  asm volatile("{\n.reg .b64 db;\n"
    "add.s64 db, %44, %45 + 0;\n"
    "wgmma.mma_async.sync.aligned.m64n56k16.f32.bf16.bf16 {%0, %1, %2, %3, %4, %5, %6, %7, %8, %9, %10, %11, %12, %13, %14, %15, %16, %17, %18, %19, %20, %21, %22, %23, %24, %25, %26, %27}, {%28, %29, %30, %31}, db, 1, 1, 1, 0;\n"
    "add.s64 db, %44, %45 + 2;\n"
    "wgmma.mma_async.sync.aligned.m64n56k16.f32.bf16.bf16 {%0, %1, %2, %3, %4, %5, %6, %7, %8, %9, %10, %11, %12, %13, %14, %15, %16, %17, %18, %19, %20, %21, %22, %23, %24, %25, %26, %27}, {%32, %33, %34, %35}, db, 1, 1, 1, 0;\n"
    "add.s64 db, %44, %45 + 4;\n"
    "wgmma.mma_async.sync.aligned.m64n56k16.f32.bf16.bf16 {%0, %1, %2, %3, %4, %5, %6, %7, %8, %9, %10, %11, %12, %13, %14, %15, %16, %17, %18, %19, %20, %21, %22, %23, %24, %25, %26, %27}, {%36, %37, %38, %39}, db, 1, 1, 1, 0;\n"
    "add.s64 db, %44, %45 + 6;\n"
    "wgmma.mma_async.sync.aligned.m64n56k16.f32.bf16.bf16 {%0, %1, %2, %3, %4, %5, %6, %7, %8, %9, %10, %11, %12, %13, %14, %15, %16, %17, %18, %19, %20, %21, %22, %23, %24, %25, %26, %27}, {%40, %41, %42, %43}, db, 1, 1, 1, 0;\n"
    "wgmma.commit_group.sync.aligned;\n}\n"
    : "+f"(d[0]), "+f"(d[1]), "+f"(d[2]), "+f"(d[3]), "+f"(d[4]), "+f"(d[5]), "+f"(d[6]), "+f"(d[7]), "+f"(d[8]), "+f"(d[9]), "+f"(d[10]), "+f"(d[11]), "+f"(d[12]), "+f"(d[13]), "+f"(d[14]), "+f"(d[15]), "+f"(d[16]), "+f"(d[17]), "+f"(d[18]), "+f"(d[19]), "+f"(d[20]), "+f"(d[21]), "+f"(d[22]), "+f"(d[23]), "+f"(d[24]), "+f"(d[25]), "+f"(d[26]), "+f"(d[27])
    : "r"(a[0]), "r"(a[1]), "r"(a[2]), "r"(a[3]), "r"(a[4]), "r"(a[5]), "r"(a[6]), "r"(a[7]), "r"(a[8]), "r"(a[9]), "r"(a[10]), "r"(a[11]), "r"(a[12]), "r"(a[13]), "r"(a[14]), "r"(a[15]), "l"(db), "n"(D)
    : "memory");
}
template<int D> __device__ __forceinline__ void gemm1(float (&d)[32], const uint32_t (&a)[16], uint64_t db) {
  asm volatile("{\n.reg .b64 db;\n"
    "add.s64 db, %48, %49 + 0;\n"
    "wgmma.mma_async.sync.aligned.m64n64k16.f32.bf16.bf16 {%0, %1, %2, %3, %4, %5, %6, %7, %8, %9, %10, %11, %12, %13, %14, %15, %16, %17, %18, %19, %20, %21, %22, %23, %24, %25, %26, %27, %28, %29, %30, %31}, {%32, %33, %34, %35}, db, 1, 1, 1, 0;\n"
    "add.s64 db, %48, %49 + 2;\n"
    "wgmma.mma_async.sync.aligned.m64n64k16.f32.bf16.bf16 {%0, %1, %2, %3, %4, %5, %6, %7, %8, %9, %10, %11, %12, %13, %14, %15, %16, %17, %18, %19, %20, %21, %22, %23, %24, %25, %26, %27, %28, %29, %30, %31}, {%36, %37, %38, %39}, db, 1, 1, 1, 0;\n"
    "add.s64 db, %48, %49 + 4;\n"
    "wgmma.mma_async.sync.aligned.m64n64k16.f32.bf16.bf16 {%0, %1, %2, %3, %4, %5, %6, %7, %8, %9, %10, %11, %12, %13, %14, %15, %16, %17, %18, %19, %20, %21, %22, %23, %24, %25, %26, %27, %28, %29, %30, %31}, {%40, %41, %42, %43}, db, 1, 1, 1, 0;\n"
    "add.s64 db, %48, %49 + 6;\n"
    "wgmma.mma_async.sync.aligned.m64n64k16.f32.bf16.bf16 {%0, %1, %2, %3, %4, %5, %6, %7, %8, %9, %10, %11, %12, %13, %14, %15, %16, %17, %18, %19, %20, %21, %22, %23, %24, %25, %26, %27, %28, %29, %30, %31}, {%44, %45, %46, %47}, db, 1, 1, 1, 0;\n"
    "wgmma.commit_group.sync.aligned;\n}\n"
    : "+f"(d[0]), "+f"(d[1]), "+f"(d[2]), "+f"(d[3]), "+f"(d[4]), "+f"(d[5]), "+f"(d[6]), "+f"(d[7]), "+f"(d[8]), "+f"(d[9]), "+f"(d[10]), "+f"(d[11]), "+f"(d[12]), "+f"(d[13]), "+f"(d[14]), "+f"(d[15]), "+f"(d[16]), "+f"(d[17]), "+f"(d[18]), "+f"(d[19]), "+f"(d[20]), "+f"(d[21]), "+f"(d[22]), "+f"(d[23]), "+f"(d[24]), "+f"(d[25]), "+f"(d[26]), "+f"(d[27]), "+f"(d[28]), "+f"(d[29]), "+f"(d[30]), "+f"(d[31])
    : "r"(a[0]), "r"(a[1]), "r"(a[2]), "r"(a[3]), "r"(a[4]), "r"(a[5]), "r"(a[6]), "r"(a[7]), "r"(a[8]), "r"(a[9]), "r"(a[10]), "r"(a[11]), "r"(a[12]), "r"(a[13]), "r"(a[14]), "r"(a[15]), "l"(db), "n"(D)
    : "memory");
}
template<int D> __device__ __forceinline__ void gemm1(float (&d)[36], const uint32_t (&a)[16], uint64_t db) {
  asm volatile("{\n.reg .b64 db;\n"
    "add.s64 db, %52, %53 + 0;\n"
    "wgmma.mma_async.sync.aligned.m64n72k16.f32.bf16.bf16 {%0, %1, %2, %3, %4, %5, %6, %7, %8, %9, %10, %11, %12, %13, %14, %15, %16, %17, %18, %19, %20, %21, %22, %23, %24, %25, %26, %27, %28, %29, %30, %31, %32, %33, %34, %35}, {%36, %37, %38, %39}, db, 1, 1, 1, 0;\n"
    "add.s64 db, %52, %53 + 2;\n"
    "wgmma.mma_async.sync.aligned.m64n72k16.f32.bf16.bf16 {%0, %1, %2, %3, %4, %5, %6, %7, %8, %9, %10, %11, %12, %13, %14, %15, %16, %17, %18, %19, %20, %21, %22, %23, %24, %25, %26, %27, %28, %29, %30, %31, %32, %33, %34, %35}, {%40, %41, %42, %43}, db, 1, 1, 1, 0;\n"
    "add.s64 db, %52, %53 + 4;\n"
    "wgmma.mma_async.sync.aligned.m64n72k16.f32.bf16.bf16 {%0, %1, %2, %3, %4, %5, %6, %7, %8, %9, %10, %11, %12, %13, %14, %15, %16, %17, %18, %19, %20, %21, %22, %23, %24, %25, %26, %27, %28, %29, %30, %31, %32, %33, %34, %35}, {%44, %45, %46, %47}, db, 1, 1, 1, 0;\n"
    "add.s64 db, %52, %53 + 6;\n"
    "wgmma.mma_async.sync.aligned.m64n72k16.f32.bf16.bf16 {%0, %1, %2, %3, %4, %5, %6, %7, %8, %9, %10, %11, %12, %13, %14, %15, %16, %17, %18, %19, %20, %21, %22, %23, %24, %25, %26, %27, %28, %29, %30, %31, %32, %33, %34, %35}, {%48, %49, %50, %51}, db, 1, 1, 1, 0;\n"
    "wgmma.commit_group.sync.aligned;\n}\n"
    : "+f"(d[0]), "+f"(d[1]), "+f"(d[2]), "+f"(d[3]), "+f"(d[4]), "+f"(d[5]), "+f"(d[6]), "+f"(d[7]), "+f"(d[8]), "+f"(d[9]), "+f"(d[10]), "+f"(d[11]), "+f"(d[12]), "+f"(d[13]), "+f"(d[14]), "+f"(d[15]), "+f"(d[16]), "+f"(d[17]), "+f"(d[18]), "+f"(d[19]), "+f"(d[20]), "+f"(d[21]), "+f"(d[22]), "+f"(d[23]), "+f"(d[24]), "+f"(d[25]), "+f"(d[26]), "+f"(d[27]), "+f"(d[28]), "+f"(d[29]), "+f"(d[30]), "+f"(d[31]), "+f"(d[32]), "+f"(d[33]), "+f"(d[34]), "+f"(d[35])
    : "r"(a[0]), "r"(a[1]), "r"(a[2]), "r"(a[3]), "r"(a[4]), "r"(a[5]), "r"(a[6]), "r"(a[7]), "r"(a[8]), "r"(a[9]), "r"(a[10]), "r"(a[11]), "r"(a[12]), "r"(a[13]), "r"(a[14]), "r"(a[15]), "l"(db), "n"(D)
    : "memory");
}
template<int D> __device__ __forceinline__ void gemm1(float (&d)[40], const uint32_t (&a)[16], uint64_t db) {
  asm volatile("{\n.reg .b64 db;\n"
    "add.s64 db, %56, %57 + 0;\n"
    "wgmma.mma_async.sync.aligned.m64n80k16.f32.bf16.bf16 {%0, %1, %2, %3, %4, %5, %6, %7, %8, %9, %10, %11, %12, %13, %14, %15, %16, %17, %18, %19, %20, %21, %22, %23, %24, %25, %26, %27, %28, %29, %30, %31, %32, %33, %34, %35, %36, %37, %38, %39}, {%40, %41, %42, %43}, db, 1, 1, 1, 0;\n"
    "add.s64 db, %56, %57 + 2;\n"
    "wgmma.mma_async.sync.aligned.m64n80k16.f32.bf16.bf16 {%0, %1, %2, %3, %4, %5, %6, %7, %8, %9, %10, %11, %12, %13, %14, %15, %16, %17, %18, %19, %20, %21, %22, %23, %24, %25, %26, %27, %28, %29, %30, %31, %32, %33, %34, %35, %36, %37, %38, %39}, {%44, %45, %46, %47}, db, 1, 1, 1, 0;\n"
    "add.s64 db, %56, %57 + 4;\n"
    "wgmma.mma_async.sync.aligned.m64n80k16.f32.bf16.bf16 {%0, %1, %2, %3, %4, %5, %6, %7, %8, %9, %10, %11, %12, %13, %14, %15, %16, %17, %18, %19, %20, %21, %22, %23, %24, %25, %26, %27, %28, %29, %30, %31, %32, %33, %34, %35, %36, %37, %38, %39}, {%48, %49, %50, %51}, db, 1, 1, 1, 0;\n"
    "add.s64 db, %56, %57 + 6;\n"
    "wgmma.mma_async.sync.aligned.m64n80k16.f32.bf16.bf16 {%0, %1, %2, %3, %4, %5, %6, %7, %8, %9, %10, %11, %12, %13, %14, %15, %16, %17, %18, %19, %20, %21, %22, %23, %24, %25, %26, %27, %28, %29, %30, %31, %32, %33, %34, %35, %36, %37, %38, %39}, {%52, %53, %54, %55}, db, 1, 1, 1, 0;\n"
    "wgmma.commit_group.sync.aligned;\n}\n"
    : "+f"(d[0]), "+f"(d[1]), "+f"(d[2]), "+f"(d[3]), "+f"(d[4]), "+f"(d[5]), "+f"(d[6]), "+f"(d[7]), "+f"(d[8]), "+f"(d[9]), "+f"(d[10]), "+f"(d[11]), "+f"(d[12]), "+f"(d[13]), "+f"(d[14]), "+f"(d[15]), "+f"(d[16]), "+f"(d[17]), "+f"(d[18]), "+f"(d[19]), "+f"(d[20]), "+f"(d[21]), "+f"(d[22]), "+f"(d[23]), "+f"(d[24]), "+f"(d[25]), "+f"(d[26]), "+f"(d[27]), "+f"(d[28]), "+f"(d[29]), "+f"(d[30]), "+f"(d[31]), "+f"(d[32]), "+f"(d[33]), "+f"(d[34]), "+f"(d[35]), "+f"(d[36]), "+f"(d[37]), "+f"(d[38]), "+f"(d[39])
    : "r"(a[0]), "r"(a[1]), "r"(a[2]), "r"(a[3]), "r"(a[4]), "r"(a[5]), "r"(a[6]), "r"(a[7]), "r"(a[8]), "r"(a[9]), "r"(a[10]), "r"(a[11]), "r"(a[12]), "r"(a[13]), "r"(a[14]), "r"(a[15]), "l"(db), "n"(D)
    : "memory");
}
template<int D> __device__ __forceinline__ void gemm1(float (&d)[44], const uint32_t (&a)[16], uint64_t db) {
  asm volatile("{\n.reg .b64 db;\n"
    "add.s64 db, %60, %61 + 0;\n"
    "wgmma.mma_async.sync.aligned.m64n88k16.f32.bf16.bf16 {%0, %1, %2, %3, %4, %5, %6, %7, %8, %9, %10, %11, %12, %13, %14, %15, %16, %17, %18, %19, %20, %21, %22, %23, %24, %25, %26, %27, %28, %29, %30, %31, %32, %33, %34, %35, %36, %37, %38, %39, %40, %41, %42, %43}, {%44, %45, %46, %47}, db, 1, 1, 1, 0;\n"
    "add.s64 db, %60, %61 + 2;\n"
    "wgmma.mma_async.sync.aligned.m64n88k16.f32.bf16.bf16 {%0, %1, %2, %3, %4, %5, %6, %7, %8, %9, %10, %11, %12, %13, %14, %15, %16, %17, %18, %19, %20, %21, %22, %23, %24, %25, %26, %27, %28, %29, %30, %31, %32, %33, %34, %35, %36, %37, %38, %39, %40, %41, %42, %43}, {%48, %49, %50, %51}, db, 1, 1, 1, 0;\n"
    "add.s64 db, %60, %61 + 4;\n"
    "wgmma.mma_async.sync.aligned.m64n88k16.f32.bf16.bf16 {%0, %1, %2, %3, %4, %5, %6, %7, %8, %9, %10, %11, %12, %13, %14, %15, %16, %17, %18, %19, %20, %21, %22, %23, %24, %25, %26, %27, %28, %29, %30, %31, %32, %33, %34, %35, %36, %37, %38, %39, %40, %41, %42, %43}, {%52, %53, %54, %55}, db, 1, 1, 1, 0;\n"
    "add.s64 db, %60, %61 + 6;\n"
    "wgmma.mma_async.sync.aligned.m64n88k16.f32.bf16.bf16 {%0, %1, %2, %3, %4, %5, %6, %7, %8, %9, %10, %11, %12, %13, %14, %15, %16, %17, %18, %19, %20, %21, %22, %23, %24, %25, %26, %27, %28, %29, %30, %31, %32, %33, %34, %35, %36, %37, %38, %39, %40, %41, %42, %43}, {%56, %57, %58, %59}, db, 1, 1, 1, 0;\n"
    "wgmma.commit_group.sync.aligned;\n}\n"
    : "+f"(d[0]), "+f"(d[1]), "+f"(d[2]), "+f"(d[3]), "+f"(d[4]), "+f"(d[5]), "+f"(d[6]), "+f"(d[7]), "+f"(d[8]), "+f"(d[9]), "+f"(d[10]), "+f"(d[11]), "+f"(d[12]), "+f"(d[13]), "+f"(d[14]), "+f"(d[15]), "+f"(d[16]), "+f"(d[17]), "+f"(d[18]), "+f"(d[19]), "+f"(d[20]), "+f"(d[21]), "+f"(d[22]), "+f"(d[23]), "+f"(d[24]), "+f"(d[25]), "+f"(d[26]), "+f"(d[27]), "+f"(d[28]), "+f"(d[29]), "+f"(d[30]), "+f"(d[31]), "+f"(d[32]), "+f"(d[33]), "+f"(d[34]), "+f"(d[35]), "+f"(d[36]), "+f"(d[37]), "+f"(d[38]), "+f"(d[39]), "+f"(d[40]), "+f"(d[41]), "+f"(d[42]), "+f"(d[43])
    : "r"(a[0]), "r"(a[1]), "r"(a[2]), "r"(a[3]), "r"(a[4]), "r"(a[5]), "r"(a[6]), "r"(a[7]), "r"(a[8]), "r"(a[9]), "r"(a[10]), "r"(a[11]), "r"(a[12]), "r"(a[13]), "r"(a[14]), "r"(a[15]), "l"(db), "n"(D)
    : "memory");
}
template<int D> __device__ __forceinline__ void bias_out(float (&d)[4], const uint32_t (&a)[16], uint64_t db) {
  asm volatile("{\n.reg .b64 db;\n"
    "add.s64 db, %20, %21 + 0;\n"
    "wgmma.mma_async.sync.aligned.m64n8k16.f32.bf16.bf16 {%0, %1, %2, %3}, {%4, %5, %6, %7}, db, 0, 1, 1, 0;\n"
    "add.s64 db, %20, %21 + 2;\n"
    "wgmma.mma_async.sync.aligned.m64n8k16.f32.bf16.bf16 {%0, %1, %2, %3}, {%8, %9, %10, %11}, db, 1, 1, 1, 0;\n"
    "add.s64 db, %20, %21 + 4;\n"
    "wgmma.mma_async.sync.aligned.m64n8k16.f32.bf16.bf16 {%0, %1, %2, %3}, {%12, %13, %14, %15}, db, 1, 1, 1, 0;\n"
    "add.s64 db, %20, %21 + 6;\n"
    "wgmma.mma_async.sync.aligned.m64n8k16.f32.bf16.bf16 {%0, %1, %2, %3}, {%16, %17, %18, %19}, db, 1, 1, 1, 0;\n"
    "wgmma.commit_group.sync.aligned;\n}\n"
    : "=f"(d[0]), "=f"(d[1]), "=f"(d[2]), "=f"(d[3])
    : "r"(a[0]), "r"(a[1]), "r"(a[2]), "r"(a[3]), "r"(a[4]), "r"(a[5]), "r"(a[6]), "r"(a[7]), "r"(a[8]), "r"(a[9]), "r"(a[10]), "r"(a[11]), "r"(a[12]), "r"(a[13]), "r"(a[14]), "r"(a[15]), "l"(db), "n"(D)
    : "memory");
}
template<int D> __device__ __forceinline__ void gemm2_first(float (&d)[16], const uint32_t (&a)[12], uint64_t db, uint32_t meta) {
  asm volatile("{\n.reg .b64 db;\n"
    "wgmma.fence.sync.aligned;\n"
    "add.s64 db, %28, %29 + 0;\n"
    "wgmma.mma_async.sp.sync.aligned.m64n32k32.f32.bf16.bf16 {%0, %1, %2, %3, %4, %5, %6, %7, %8, %9, %10, %11, %12, %13, %14, %15}, {%16, %17, %18, %19}, db, %30, 0, 0, 1, 1, 1;\n"
    "add.s64 db, %28, %29 + 128;\n"
    "wgmma.mma_async.sp.sync.aligned.m64n32k32.f32.bf16.bf16 {%0, %1, %2, %3, %4, %5, %6, %7, %8, %9, %10, %11, %12, %13, %14, %15}, {%20, %21, %22, %23}, db, %30, 0, 1, 1, 1, 1;\n"
    "add.s64 db, %28, %29 + 256;\n"
    "wgmma.mma_async.sp.sync.aligned.m64n32k32.f32.bf16.bf16 {%0, %1, %2, %3, %4, %5, %6, %7, %8, %9, %10, %11, %12, %13, %14, %15}, {%24, %25, %26, %27}, db, %30, 0, 1, 1, 1, 1;\n"
    "wgmma.commit_group.sync.aligned;\n}\n"
    : "=f"(d[0]), "=f"(d[1]), "=f"(d[2]), "=f"(d[3]), "=f"(d[4]), "=f"(d[5]), "=f"(d[6]), "=f"(d[7]), "=f"(d[8]), "=f"(d[9]), "=f"(d[10]), "=f"(d[11]), "=f"(d[12]), "=f"(d[13]), "=f"(d[14]), "=f"(d[15])
    : "r"(a[0]), "r"(a[1]), "r"(a[2]), "r"(a[3]), "r"(a[4]), "r"(a[5]), "r"(a[6]), "r"(a[7]), "r"(a[8]), "r"(a[9]), "r"(a[10]), "r"(a[11]), "l"(db), "n"(D), "r"(meta)
    : "memory");
}
template<int D> __device__ __forceinline__ void gemm2_first(float (&d)[16], const uint32_t (&a)[16], uint64_t db, uint32_t meta) {
  asm volatile("{\n.reg .b64 db;\n"
    "wgmma.fence.sync.aligned;\n"
    "add.s64 db, %32, %33 + 0;\n"
    "wgmma.mma_async.sp.sync.aligned.m64n32k32.f32.bf16.bf16 {%0, %1, %2, %3, %4, %5, %6, %7, %8, %9, %10, %11, %12, %13, %14, %15}, {%16, %17, %18, %19}, db, %34, 0, 0, 1, 1, 1;\n"
    "add.s64 db, %32, %33 + 128;\n"
    "wgmma.mma_async.sp.sync.aligned.m64n32k32.f32.bf16.bf16 {%0, %1, %2, %3, %4, %5, %6, %7, %8, %9, %10, %11, %12, %13, %14, %15}, {%20, %21, %22, %23}, db, %34, 0, 1, 1, 1, 1;\n"
    "add.s64 db, %32, %33 + 256;\n"
    "wgmma.mma_async.sp.sync.aligned.m64n32k32.f32.bf16.bf16 {%0, %1, %2, %3, %4, %5, %6, %7, %8, %9, %10, %11, %12, %13, %14, %15}, {%24, %25, %26, %27}, db, %34, 0, 1, 1, 1, 1;\n"
    "add.s64 db, %32, %33 + 384;\n"
    "wgmma.mma_async.sp.sync.aligned.m64n32k32.f32.bf16.bf16 {%0, %1, %2, %3, %4, %5, %6, %7, %8, %9, %10, %11, %12, %13, %14, %15}, {%28, %29, %30, %31}, db, %34, 0, 1, 1, 1, 1;\n"
    "wgmma.commit_group.sync.aligned;\n}\n"
    : "=f"(d[0]), "=f"(d[1]), "=f"(d[2]), "=f"(d[3]), "=f"(d[4]), "=f"(d[5]), "=f"(d[6]), "=f"(d[7]), "=f"(d[8]), "=f"(d[9]), "=f"(d[10]), "=f"(d[11]), "=f"(d[12]), "=f"(d[13]), "=f"(d[14]), "=f"(d[15])
    : "r"(a[0]), "r"(a[1]), "r"(a[2]), "r"(a[3]), "r"(a[4]), "r"(a[5]), "r"(a[6]), "r"(a[7]), "r"(a[8]), "r"(a[9]), "r"(a[10]), "r"(a[11]), "r"(a[12]), "r"(a[13]), "r"(a[14]), "r"(a[15]), "l"(db), "n"(D), "r"(meta)
    : "memory");
}
template<int D> __device__ __forceinline__ void gemm2_first(float (&d)[16], const uint32_t (&a)[20], uint64_t db, uint32_t meta) {
  asm volatile("{\n.reg .b64 db;\n"
    "wgmma.fence.sync.aligned;\n"
    "add.s64 db, %36, %37 + 0;\n"
    "wgmma.mma_async.sp.sync.aligned.m64n32k32.f32.bf16.bf16 {%0, %1, %2, %3, %4, %5, %6, %7, %8, %9, %10, %11, %12, %13, %14, %15}, {%16, %17, %18, %19}, db, %38, 0, 0, 1, 1, 1;\n"
    "add.s64 db, %36, %37 + 128;\n"
    "wgmma.mma_async.sp.sync.aligned.m64n32k32.f32.bf16.bf16 {%0, %1, %2, %3, %4, %5, %6, %7, %8, %9, %10, %11, %12, %13, %14, %15}, {%20, %21, %22, %23}, db, %38, 0, 1, 1, 1, 1;\n"
    "add.s64 db, %36, %37 + 256;\n"
    "wgmma.mma_async.sp.sync.aligned.m64n32k32.f32.bf16.bf16 {%0, %1, %2, %3, %4, %5, %6, %7, %8, %9, %10, %11, %12, %13, %14, %15}, {%24, %25, %26, %27}, db, %38, 0, 1, 1, 1, 1;\n"
    "add.s64 db, %36, %37 + 384;\n"
    "wgmma.mma_async.sp.sync.aligned.m64n32k32.f32.bf16.bf16 {%0, %1, %2, %3, %4, %5, %6, %7, %8, %9, %10, %11, %12, %13, %14, %15}, {%28, %29, %30, %31}, db, %38, 0, 1, 1, 1, 1;\n"
    "add.s64 db, %36, %37 + 512;\n"
    "wgmma.mma_async.sp.sync.aligned.m64n32k32.f32.bf16.bf16 {%0, %1, %2, %3, %4, %5, %6, %7, %8, %9, %10, %11, %12, %13, %14, %15}, {%32, %33, %34, %35}, db, %38, 0, 1, 1, 1, 1;\n"
    "wgmma.commit_group.sync.aligned;\n}\n"
    : "=f"(d[0]), "=f"(d[1]), "=f"(d[2]), "=f"(d[3]), "=f"(d[4]), "=f"(d[5]), "=f"(d[6]), "=f"(d[7]), "=f"(d[8]), "=f"(d[9]), "=f"(d[10]), "=f"(d[11]), "=f"(d[12]), "=f"(d[13]), "=f"(d[14]), "=f"(d[15])
    : "r"(a[0]), "r"(a[1]), "r"(a[2]), "r"(a[3]), "r"(a[4]), "r"(a[5]), "r"(a[6]), "r"(a[7]), "r"(a[8]), "r"(a[9]), "r"(a[10]), "r"(a[11]), "r"(a[12]), "r"(a[13]), "r"(a[14]), "r"(a[15]), "r"(a[16]), "r"(a[17]), "r"(a[18]), "r"(a[19]), "l"(db), "n"(D), "r"(meta)
    : "memory");
}
template<int D> __device__ __forceinline__ void gemm2_more(float (&d)[16], const uint32_t (&a)[4], uint64_t db, uint32_t meta) {
  asm volatile("{\n.reg .b64 db;\n"
    "wgmma.fence.sync.aligned;\n"
    "add.s64 db, %20, %21 + 0;\n"
    "wgmma.mma_async.sp.sync.aligned.m64n32k32.f32.bf16.bf16 {%0, %1, %2, %3, %4, %5, %6, %7, %8, %9, %10, %11, %12, %13, %14, %15}, {%16, %17, %18, %19}, db, %22, 0, 1, 1, 1, 1;\n"
    "wgmma.commit_group.sync.aligned;\n}\n"
    : "+f"(d[0]), "+f"(d[1]), "+f"(d[2]), "+f"(d[3]), "+f"(d[4]), "+f"(d[5]), "+f"(d[6]), "+f"(d[7]), "+f"(d[8]), "+f"(d[9]), "+f"(d[10]), "+f"(d[11]), "+f"(d[12]), "+f"(d[13]), "+f"(d[14]), "+f"(d[15])
    : "r"(a[0]), "r"(a[1]), "r"(a[2]), "r"(a[3]), "l"(db), "n"(D), "r"(meta)
    : "memory");
}
template<int D> __device__ __forceinline__ void gemm2_more(float (&d)[16], const uint32_t (&a)[8], uint64_t db, uint32_t meta) {
  asm volatile("{\n.reg .b64 db;\n"
    "wgmma.fence.sync.aligned;\n"
    "add.s64 db, %24, %25 + 0;\n"
    "wgmma.mma_async.sp.sync.aligned.m64n32k32.f32.bf16.bf16 {%0, %1, %2, %3, %4, %5, %6, %7, %8, %9, %10, %11, %12, %13, %14, %15}, {%16, %17, %18, %19}, db, %26, 0, 1, 1, 1, 1;\n"
    "add.s64 db, %24, %25 + 128;\n"
    "wgmma.mma_async.sp.sync.aligned.m64n32k32.f32.bf16.bf16 {%0, %1, %2, %3, %4, %5, %6, %7, %8, %9, %10, %11, %12, %13, %14, %15}, {%20, %21, %22, %23}, db, %26, 0, 1, 1, 1, 1;\n"
    "wgmma.commit_group.sync.aligned;\n}\n"
    : "+f"(d[0]), "+f"(d[1]), "+f"(d[2]), "+f"(d[3]), "+f"(d[4]), "+f"(d[5]), "+f"(d[6]), "+f"(d[7]), "+f"(d[8]), "+f"(d[9]), "+f"(d[10]), "+f"(d[11]), "+f"(d[12]), "+f"(d[13]), "+f"(d[14]), "+f"(d[15])
    : "r"(a[0]), "r"(a[1]), "r"(a[2]), "r"(a[3]), "r"(a[4]), "r"(a[5]), "r"(a[6]), "r"(a[7]), "l"(db), "n"(D), "r"(meta)
    : "memory");
}
template<int D> __device__ __forceinline__ void gemm2_more(float (&d)[16], const uint32_t (&a)[12], uint64_t db, uint32_t meta) {
  asm volatile("{\n.reg .b64 db;\n"
    "wgmma.fence.sync.aligned;\n"
    "add.s64 db, %28, %29 + 0;\n"
    "wgmma.mma_async.sp.sync.aligned.m64n32k32.f32.bf16.bf16 {%0, %1, %2, %3, %4, %5, %6, %7, %8, %9, %10, %11, %12, %13, %14, %15}, {%16, %17, %18, %19}, db, %30, 0, 1, 1, 1, 1;\n"
    "add.s64 db, %28, %29 + 128;\n"
    "wgmma.mma_async.sp.sync.aligned.m64n32k32.f32.bf16.bf16 {%0, %1, %2, %3, %4, %5, %6, %7, %8, %9, %10, %11, %12, %13, %14, %15}, {%20, %21, %22, %23}, db, %30, 0, 1, 1, 1, 1;\n"
    "add.s64 db, %28, %29 + 256;\n"
    "wgmma.mma_async.sp.sync.aligned.m64n32k32.f32.bf16.bf16 {%0, %1, %2, %3, %4, %5, %6, %7, %8, %9, %10, %11, %12, %13, %14, %15}, {%24, %25, %26, %27}, db, %30, 0, 1, 1, 1, 1;\n"
    "wgmma.commit_group.sync.aligned;\n}\n"
    : "+f"(d[0]), "+f"(d[1]), "+f"(d[2]), "+f"(d[3]), "+f"(d[4]), "+f"(d[5]), "+f"(d[6]), "+f"(d[7]), "+f"(d[8]), "+f"(d[9]), "+f"(d[10]), "+f"(d[11]), "+f"(d[12]), "+f"(d[13]), "+f"(d[14]), "+f"(d[15])
    : "r"(a[0]), "r"(a[1]), "r"(a[2]), "r"(a[3]), "r"(a[4]), "r"(a[5]), "r"(a[6]), "r"(a[7]), "r"(a[8]), "r"(a[9]), "r"(a[10]), "r"(a[11]), "l"(db), "n"(D), "r"(meta)
    : "memory");
}
template<int D> __device__ __forceinline__ void gemm2_more(float (&d)[16], const uint32_t (&a)[16], uint64_t db, uint32_t meta) {
  asm volatile("{\n.reg .b64 db;\n"
    "wgmma.fence.sync.aligned;\n"
    "add.s64 db, %32, %33 + 0;\n"
    "wgmma.mma_async.sp.sync.aligned.m64n32k32.f32.bf16.bf16 {%0, %1, %2, %3, %4, %5, %6, %7, %8, %9, %10, %11, %12, %13, %14, %15}, {%16, %17, %18, %19}, db, %34, 0, 1, 1, 1, 1;\n"
    "add.s64 db, %32, %33 + 128;\n"
    "wgmma.mma_async.sp.sync.aligned.m64n32k32.f32.bf16.bf16 {%0, %1, %2, %3, %4, %5, %6, %7, %8, %9, %10, %11, %12, %13, %14, %15}, {%20, %21, %22, %23}, db, %34, 0, 1, 1, 1, 1;\n"
    "add.s64 db, %32, %33 + 256;\n"
    "wgmma.mma_async.sp.sync.aligned.m64n32k32.f32.bf16.bf16 {%0, %1, %2, %3, %4, %5, %6, %7, %8, %9, %10, %11, %12, %13, %14, %15}, {%24, %25, %26, %27}, db, %34, 0, 1, 1, 1, 1;\n"
    "add.s64 db, %32, %33 + 384;\n"
    "wgmma.mma_async.sp.sync.aligned.m64n32k32.f32.bf16.bf16 {%0, %1, %2, %3, %4, %5, %6, %7, %8, %9, %10, %11, %12, %13, %14, %15}, {%28, %29, %30, %31}, db, %34, 0, 1, 1, 1, 1;\n"
    "wgmma.commit_group.sync.aligned;\n}\n"
    : "+f"(d[0]), "+f"(d[1]), "+f"(d[2]), "+f"(d[3]), "+f"(d[4]), "+f"(d[5]), "+f"(d[6]), "+f"(d[7]), "+f"(d[8]), "+f"(d[9]), "+f"(d[10]), "+f"(d[11]), "+f"(d[12]), "+f"(d[13]), "+f"(d[14]), "+f"(d[15])
    : "r"(a[0]), "r"(a[1]), "r"(a[2]), "r"(a[3]), "r"(a[4]), "r"(a[5]), "r"(a[6]), "r"(a[7]), "r"(a[8]), "r"(a[9]), "r"(a[10]), "r"(a[11]), "r"(a[12]), "r"(a[13]), "r"(a[14]), "r"(a[15]), "l"(db), "n"(D), "r"(meta)
    : "memory");
}
template<int N> __device__ __forceinline__ void mma_wait(float (&d)[4]) {
  asm volatile("wgmma.wait_group.sync.aligned %4;"
    : "+f"(d[0]), "+f"(d[1]), "+f"(d[2]), "+f"(d[3])
    : "n"(N) : "memory");
}
template<int N> __device__ __forceinline__ void mma_wait(float (&d)[16]) {
  asm volatile("wgmma.wait_group.sync.aligned %16;"
    : "+f"(d[0]), "+f"(d[1]), "+f"(d[2]), "+f"(d[3]), "+f"(d[4]), "+f"(d[5]), "+f"(d[6]), "+f"(d[7]), "+f"(d[8]), "+f"(d[9]), "+f"(d[10]), "+f"(d[11]), "+f"(d[12]), "+f"(d[13]), "+f"(d[14]), "+f"(d[15])
    : "n"(N) : "memory");
}
template<int N> __device__ __forceinline__ void mma_wait(float (&d)[20]) {
  asm volatile("wgmma.wait_group.sync.aligned %20;"
    : "+f"(d[0]), "+f"(d[1]), "+f"(d[2]), "+f"(d[3]), "+f"(d[4]), "+f"(d[5]), "+f"(d[6]), "+f"(d[7]), "+f"(d[8]), "+f"(d[9]), "+f"(d[10]), "+f"(d[11]), "+f"(d[12]), "+f"(d[13]), "+f"(d[14]), "+f"(d[15]), "+f"(d[16]), "+f"(d[17]), "+f"(d[18]), "+f"(d[19])
    : "n"(N) : "memory");
}
template<int N> __device__ __forceinline__ void mma_wait(float (&d)[28]) {
  asm volatile("wgmma.wait_group.sync.aligned %28;"
    : "+f"(d[0]), "+f"(d[1]), "+f"(d[2]), "+f"(d[3]), "+f"(d[4]), "+f"(d[5]), "+f"(d[6]), "+f"(d[7]), "+f"(d[8]), "+f"(d[9]), "+f"(d[10]), "+f"(d[11]), "+f"(d[12]), "+f"(d[13]), "+f"(d[14]), "+f"(d[15]), "+f"(d[16]), "+f"(d[17]), "+f"(d[18]), "+f"(d[19]), "+f"(d[20]), "+f"(d[21]), "+f"(d[22]), "+f"(d[23]), "+f"(d[24]), "+f"(d[25]), "+f"(d[26]), "+f"(d[27])
    : "n"(N) : "memory");
}
template<int N> __device__ __forceinline__ void mma_wait(float (&d)[32]) {
  asm volatile("wgmma.wait_group.sync.aligned %32;"
    : "+f"(d[0]), "+f"(d[1]), "+f"(d[2]), "+f"(d[3]), "+f"(d[4]), "+f"(d[5]), "+f"(d[6]), "+f"(d[7]), "+f"(d[8]), "+f"(d[9]), "+f"(d[10]), "+f"(d[11]), "+f"(d[12]), "+f"(d[13]), "+f"(d[14]), "+f"(d[15]), "+f"(d[16]), "+f"(d[17]), "+f"(d[18]), "+f"(d[19]), "+f"(d[20]), "+f"(d[21]), "+f"(d[22]), "+f"(d[23]), "+f"(d[24]), "+f"(d[25]), "+f"(d[26]), "+f"(d[27]), "+f"(d[28]), "+f"(d[29]), "+f"(d[30]), "+f"(d[31])
    : "n"(N) : "memory");
}
template<int N> __device__ __forceinline__ void mma_wait(float (&d)[36]) {
  asm volatile("wgmma.wait_group.sync.aligned %36;"
    : "+f"(d[0]), "+f"(d[1]), "+f"(d[2]), "+f"(d[3]), "+f"(d[4]), "+f"(d[5]), "+f"(d[6]), "+f"(d[7]), "+f"(d[8]), "+f"(d[9]), "+f"(d[10]), "+f"(d[11]), "+f"(d[12]), "+f"(d[13]), "+f"(d[14]), "+f"(d[15]), "+f"(d[16]), "+f"(d[17]), "+f"(d[18]), "+f"(d[19]), "+f"(d[20]), "+f"(d[21]), "+f"(d[22]), "+f"(d[23]), "+f"(d[24]), "+f"(d[25]), "+f"(d[26]), "+f"(d[27]), "+f"(d[28]), "+f"(d[29]), "+f"(d[30]), "+f"(d[31]), "+f"(d[32]), "+f"(d[33]), "+f"(d[34]), "+f"(d[35])
    : "n"(N) : "memory");
}
template<int N> __device__ __forceinline__ void mma_wait(float (&d)[40]) {
  asm volatile("wgmma.wait_group.sync.aligned %40;"
    : "+f"(d[0]), "+f"(d[1]), "+f"(d[2]), "+f"(d[3]), "+f"(d[4]), "+f"(d[5]), "+f"(d[6]), "+f"(d[7]), "+f"(d[8]), "+f"(d[9]), "+f"(d[10]), "+f"(d[11]), "+f"(d[12]), "+f"(d[13]), "+f"(d[14]), "+f"(d[15]), "+f"(d[16]), "+f"(d[17]), "+f"(d[18]), "+f"(d[19]), "+f"(d[20]), "+f"(d[21]), "+f"(d[22]), "+f"(d[23]), "+f"(d[24]), "+f"(d[25]), "+f"(d[26]), "+f"(d[27]), "+f"(d[28]), "+f"(d[29]), "+f"(d[30]), "+f"(d[31]), "+f"(d[32]), "+f"(d[33]), "+f"(d[34]), "+f"(d[35]), "+f"(d[36]), "+f"(d[37]), "+f"(d[38]), "+f"(d[39])
    : "n"(N) : "memory");
}
template<int N> __device__ __forceinline__ void mma_wait(float (&d)[44]) {
  asm volatile("wgmma.wait_group.sync.aligned %44;"
    : "+f"(d[0]), "+f"(d[1]), "+f"(d[2]), "+f"(d[3]), "+f"(d[4]), "+f"(d[5]), "+f"(d[6]), "+f"(d[7]), "+f"(d[8]), "+f"(d[9]), "+f"(d[10]), "+f"(d[11]), "+f"(d[12]), "+f"(d[13]), "+f"(d[14]), "+f"(d[15]), "+f"(d[16]), "+f"(d[17]), "+f"(d[18]), "+f"(d[19]), "+f"(d[20]), "+f"(d[21]), "+f"(d[22]), "+f"(d[23]), "+f"(d[24]), "+f"(d[25]), "+f"(d[26]), "+f"(d[27]), "+f"(d[28]), "+f"(d[29]), "+f"(d[30]), "+f"(d[31]), "+f"(d[32]), "+f"(d[33]), "+f"(d[34]), "+f"(d[35]), "+f"(d[36]), "+f"(d[37]), "+f"(d[38]), "+f"(d[39]), "+f"(d[40]), "+f"(d[41]), "+f"(d[42]), "+f"(d[43])
    : "n"(N) : "memory");
}
__device__ __forceinline__ void mma_fence() { asm volatile("wgmma.fence.sync.aligned;" ::: "memory"); }

__device__ __forceinline__ uint32_t smem_u32(const void* p) { return (uint32_t)__cvta_generic_to_shared(p); }

__device__ __forceinline__ void mbar_init(uint32_t bar, uint32_t cnt) {
  asm volatile("mbarrier.init.shared::cta.b64 [%0], %1;" :: "r"(bar), "r"(cnt) : "memory");
}
__device__ __forceinline__ void mbar_arrive(uint32_t bar) {
  asm volatile("mbarrier.arrive.shared::cta.b64 _, [%0];" :: "r"(bar) : "memory");
}
__device__ __forceinline__ void mbar_wait(uint32_t bar, uint32_t parity) {
  asm volatile("{\n.reg .pred p;\n.reg .u32 n;\n"
               "mov.u32 n, 0;\n"
               "WAIT_LOOP:\n"
               "mbarrier.try_wait.parity.shared::cta.b64 p, [%0], %1;\n"
               "@p bra.uni WAIT_DONE;\n"
               "add.u32 n, n, 1;\n"
               "setp.lt.u32 p, n, 0x1000000;\n"
               "@p bra.uni WAIT_LOOP;\n"
               "trap;\n"
               "WAIT_DONE:\n}\n"
               :: "r"(bar), "r"(parity) : "memory");
}
__device__ __forceinline__ void mbar_wait_unless(uint32_t ok, uint32_t bar, uint32_t parity) {
  asm volatile("{\n.reg .pred p;\n.reg .u32 n;\n"
               "setp.ne.u32 p, %2, 0;\n"
               "@p bra.uni WAIT_DONE;\n"
               "mov.u32 n, 0;\n"
               "WAIT_LOOP:\n"
               "mbarrier.try_wait.parity.shared::cta.b64 p, [%0], %1;\n"
               "@p bra.uni WAIT_DONE;\n"
               "add.u32 n, n, 1;\n"
               "setp.lt.u32 p, n, 0x1000000;\n"
               "@p bra.uni WAIT_LOOP;\n"
               "trap;\n"
               "WAIT_DONE:\n}\n"
               :: "r"(bar), "r"(parity), "r"(ok) : "memory");
}
__device__ __forceinline__ uint32_t mbar_test(uint32_t bar, uint32_t parity) {
  uint32_t ok;
  asm volatile("{\n.reg .pred p;\nmbarrier.test_wait.parity.shared::cta.b64 p, [%1], %2;\nselp.u32 %0, 1, 0, p;\n}\n"
               : "=r"(ok) : "r"(bar), "r"(parity) : "memory");
  return ok;
}
__device__ __forceinline__ void cp_async16(uint32_t dst, const void* src) {
  asm volatile("cp.async.cg.shared.global [%0], [%1], 16;" :: "r"(dst), "l"(src) : "memory");
}
#define DIN_ADDR4                                                                        \
  "mov.b64 {x, y}, %0;\ndp4a.u32.u32 x, %8, 0x80, %11;\nmov.b64 %0, {x, y};\n"           \
  "mov.b64 {x, y}, %1;\ndp4a.u32.u32 x, %8, 0x8000, %11;\nmov.b64 %1, {x, y};\n"         \
  "mov.b64 {x, y}, %2;\ndp4a.u32.u32 x, %8, 0x800000, %11;\nmov.b64 %2, {x, y};\n"       \
  "mov.b64 {x, y}, %3;\ndp4a.u32.u32 x, %8, 0x80000000, %11;\nmov.b64 %3, {x, y};\n"
template<int T>
__device__ __forceinline__ void cp_group(const uint32_t (&dst)[4], uint64_t (&a)[4], uint32_t rows4, uint32_t base, uint64_t pol) {
  asm volatile("{\n.reg .u32 x, y;\n" DIN_ADDR4
               "cp.async.cg.shared.global.L2::cache_hint [%4 + %10], [%0], 16, %9;\n"
               "cp.async.cg.shared.global.L2::cache_hint [%5 + %10], [%1], 16, %9;\n"
               "cp.async.cg.shared.global.L2::cache_hint [%6 + %10], [%2], 16, %9;\n"
               "cp.async.cg.shared.global.L2::cache_hint [%7 + %10], [%3], 16, %9;\n}\n"
               : "+l"(a[0]), "+l"(a[1]), "+l"(a[2]), "+l"(a[3])
               : "r"(dst[0]), "r"(dst[1]), "r"(dst[2]), "r"(dst[3]), "r"(rows4), "l"(pol), "n"(T * 2048), "r"(base) : "memory");
}
template<int T>
__device__ __forceinline__ void cp_group_z(const uint32_t (&dst)[4], uint64_t (&a)[4], uint32_t rows4, uint32_t base, int left, uint64_t pol) {
  asm volatile("{\n.reg .u32 x, y;\n.reg .pred p0, p1, p2, p3;\n" DIN_ADDR4
               "setp.le.s32 p0, %12, %13;\nsetp.le.s32 p1, %12, %13 + 1;\nsetp.le.s32 p2, %12, %13 + 2;\nsetp.le.s32 p3, %12, %13 + 3;\n"
               "cp.async.cg.shared.global.L2::cache_hint [%4 + %10], [%0], 16, p0, %9;\n"
               "cp.async.cg.shared.global.L2::cache_hint [%5 + %10], [%1], 16, p1, %9;\n"
               "cp.async.cg.shared.global.L2::cache_hint [%6 + %10], [%2], 16, p2, %9;\n"
               "cp.async.cg.shared.global.L2::cache_hint [%7 + %10], [%3], 16, p3, %9;\n}\n"
               : "+l"(a[0]), "+l"(a[1]), "+l"(a[2]), "+l"(a[3])
               : "r"(dst[0]), "r"(dst[1]), "r"(dst[2]), "r"(dst[3]), "r"(rows4), "l"(pol), "n"(T * 2048), "r"(base),
                 "r"(left), "n"(T * 16) : "memory");
}
__device__ __forceinline__ void wait_for(uint32_t t, uint32_t most) {
  asm volatile("{\n.reg .u32 c;\n.reg .pred p;\n"
               "SPIN:\n"
               "mov.u32 c, %%globaltimer_lo;\n"
               "sub.u32 c, c, %0;\n"
               "setp.gt.u32 p, c, %1;\n"
               "@p bra.uni SPIN;\n}\n" :: "r"(t), "r"(~most) : "memory");
}
template<int T, int SH>
__device__ __forceinline__ void cp_group_m(const uint32_t (&dst)[4], uint64_t (&a)[4], uint32_t rows4, uint32_t base, uint32_t have, uint32_t go, uint64_t pol) {
  asm volatile("{\n.reg .u32 x, y;\n.reg .pred p0, p1, p2, p3, g;\n" DIN_ADDR4
               "setp.ne.u32 g, %14, 0;\n"
               "and.b32 x, %12, 1 << %13;\nsetp.eq.u32 p0, x, 0;\nand.b32 x, %12, 2 << %13;\nsetp.eq.u32 p1, x, 0;\n"
               "and.b32 x, %12, 4 << %13;\nsetp.eq.u32 p2, x, 0;\nand.b32 x, %12, 8 << %13;\nsetp.eq.u32 p3, x, 0;\n"
               "@g cp.async.cg.shared.global.L2::cache_hint [%4 + %10], [%0], 16, p0, %9;\n"
               "@g cp.async.cg.shared.global.L2::cache_hint [%5 + %10], [%1], 16, p1, %9;\n"
               "@g cp.async.cg.shared.global.L2::cache_hint [%6 + %10], [%2], 16, p2, %9;\n"
               "@g cp.async.cg.shared.global.L2::cache_hint [%7 + %10], [%3], 16, p3, %9;\n}\n"
               : "+l"(a[0]), "+l"(a[1]), "+l"(a[2]), "+l"(a[3])
               : "r"(dst[0]), "r"(dst[1]), "r"(dst[2]), "r"(dst[3]), "r"(rows4), "l"(pol), "n"(T * 2048), "r"(base),
                 "r"(have), "n"(SH), "r"(go) : "memory");
}
__device__ __forceinline__ uint32_t prmt(uint32_t a, uint32_t b, uint32_t sel) {
  uint32_t d;
  asm("prmt.b32 %0, %1, %2, %3;" : "=r"(d) : "r"(a), "r"(b), "r"(sel));
  return d;
}
__device__ __forceinline__ uint32_t ballot_bit(uint32_t x, uint32_t bit) {
  uint32_t d;
  asm volatile("{\n.reg .pred p;\n.reg .u32 t;\nand.b32 t, %1, %2;\nsetp.ne.u32 p, t, 0;\nvote.sync.ballot.b32 %0, p, 0xffffffff;\n}\n"
               : "=r"(d) : "r"(x), "r"(bit));
  return d;
}
__device__ __forceinline__ uint4 load_mask(const void* mask, uint32_t b, uint32_t i) {
  uint4 m;
  asm volatile("ld.global.nc.L1::no_allocate.v4.u32 {%0,%1,%2,%3}, [%4];"
               : "=r"(m.x), "=r"(m.y), "=r"(m.z), "=r"(m.w) : "l"(reinterpret_cast<const uint4*>(mask) + (b * 25u + i)));
  return m;
}
__device__ __forceinline__ uint32_t nonzero_as_one(uint32_t x) {
  uint32_t d;
  asm("set.neu.bf16x2.bf16x2 %0, %1, %2;" : "=r"(d) : "r"(x), "r"(0u));
  return d;
}
__device__ __forceinline__ void cp_async_arrive_noinc(uint32_t bar) {
  asm volatile("cp.async.mbarrier.arrive.noinc.shared::cta.b64 [%0];" :: "r"(bar) : "memory");
}
__device__ __forceinline__ void ldsm_x4(uint32_t addr, uint32_t& r0, uint32_t& r1, uint32_t& r2, uint32_t& r3) {
  asm volatile("ldmatrix.sync.aligned.m8n8.x4.shared.b16 {%0,%1,%2,%3}, [%4];"
               : "=r"(r0), "=r"(r1), "=r"(r2), "=r"(r3) : "r"(addr) : "memory");
}
__device__ __forceinline__ void ldsm_x4_t(uint32_t addr, uint32_t& r0, uint32_t& r1, uint32_t& r2, uint32_t& r3) {
  asm volatile("ldmatrix.sync.aligned.m8n8.x4.trans.shared.b16 {%0,%1,%2,%3}, [%4];"
               : "=r"(r0), "=r"(r1), "=r"(r2), "=r"(r3) : "r"(addr) : "memory");
}
__device__ __forceinline__ void stsm_x4(uint32_t addr, uint32_t r0, uint32_t r1, uint32_t r2, uint32_t r3) {
  asm volatile("stmatrix.sync.aligned.m8n8.x4.shared.b16 [%0], {%1,%2,%3,%4};"
               :: "r"(addr), "r"(r0), "r"(r1), "r"(r2), "r"(r3) : "memory");
}
__device__ __forceinline__ void stsm_x2(uint32_t addr, uint32_t r0, uint32_t r1) {
  asm volatile("stmatrix.sync.aligned.m8n8.x2.shared.b16 [%0], {%1,%2};"
               :: "r"(addr), "r"(r0), "r"(r1) : "memory");
}
__device__ __forceinline__ void mma_bf16(float (&c)[4], const uint32_t (&a)[4], uint32_t b) {
  asm("mma.sync.aligned.m16n8k16.row.col.f32.bf16.bf16.f32 {%0,%1,%2,%3}, {%4,%5,%6,%7}, {%8,%8}, {%0,%1,%2,%3};"
      : "+f"(c[0]), "+f"(c[1]), "+f"(c[2]), "+f"(c[3]) : "r"(a[0]), "r"(a[1]), "r"(a[2]), "r"(a[3]), "r"(b));
}
__device__ __forceinline__ uint32_t hfma2_bf16(uint32_t a, uint32_t b, uint32_t c) {
  uint32_t d;
  asm volatile("fma.rn.bf16x2 %0, %1, %2, %3;" : "=r"(d) : "r"(a), "r"(b), "r"(c));
  return d;
}
__device__ __forceinline__ uint32_t pack_bf16(float lo, float hi) {
  uint32_t d;
  asm("cvt.rn.bf16x2.f32 %0, %1, %2;" : "=r"(d) : "f"(hi), "f"(lo));
  return d;
}
__device__ __forceinline__ uint32_t lds32(uint32_t a) {
  uint32_t v; asm volatile("ld.shared.u32 %0, [%1];" : "=r"(v) : "r"(a) : "memory"); return v;
}
__device__ __forceinline__ uint32_t lds16(uint32_t a) {
  uint32_t v; asm volatile("ld.shared.u16 %0, [%1];" : "=r"(v) : "r"(a) : "memory"); return v;
}
__device__ __forceinline__ void sts32(uint32_t a, uint32_t v) {
  asm volatile("st.shared.u32 [%0], %1;" :: "r"(a), "r"(v) : "memory");
}
__device__ __forceinline__ void sts16(uint32_t a, uint32_t v) {
  asm volatile("st.shared.u16 [%0], %1;" :: "r"(a), "h"((unsigned short)v) : "memory");
}
__device__ __forceinline__ void sts8(uint32_t a, uint32_t v) {
  asm volatile("st.shared.u8 [%0], %1;" :: "r"(a), "r"(v) : "memory");
}
constexpr uint32_t DESC_ROWS = 0x40000040u, DESC_HALVES = 0x80000020u;
__device__ __forceinline__ uint32_t desc_lo(uint32_t addr) { return ((addr & 0x3FFFF) >> 4) | (1u << 16); }

__device__ __forceinline__ uint4 lds128(uint32_t a) {
  uint4 v;
  asm volatile("ld.shared.v4.u32 {%0,%1,%2,%3}, [%4];" : "=r"(v.x), "=r"(v.y), "=r"(v.z), "=r"(v.w) : "r"(a) : "memory");
  return v;
}
__device__ __forceinline__ void sts128(uint32_t a, uint4 v) {
  asm volatile("st.shared.v4.u32 [%0], {%1,%2,%3,%4};" :: "r"(a), "r"(v.x), "r"(v.y), "r"(v.z), "r"(v.w) : "memory");
}
__device__ __forceinline__ void prefetch_l2(const void* p, uint32_t bytes) {
  asm volatile("cp.async.bulk.prefetch.L2.global [%0], %1;" :: "l"(p), "r"(bytes) : "memory");
}

template<int ND>
__device__ __forceinline__ void tanh_range(float (&d)[ND], int i0, int i1) {
#pragma unroll
  for (int i = i0; i < i1; i++) asm volatile("tanh.approx.f32 %0, %0;" : "+f"(d[i ^ 2]));
}
template<int ND>
__device__ __forceinline__ uint32_t mix(const float (&d)[ND], int i, float w2a, float w2b, float c32) {
  uint32_t p;
  asm volatile("{\n.reg .f32 x, y;\nfma.rn.f32 x, %3, %6, %7;\nfma.rn.f32 y, %4, %6, %7;\n"
               "fma.rn.f32 x, %1, %5, x;\nfma.rn.f32 y, %2, %5, y;\ncvt.rn.bf16x2.f32 %0, y, x;\n}\n"
               : "=r"(p) : "f"(d[4 * i]), "f"(d[4 * i + 1]), "f"(d[4 * i + 2]), "f"(d[4 * i + 3]), "f"(w2a), "f"(w2b), "f"(c32));
  return p;
}
__device__ __forceinline__ uint32_t size_bit(int n) { return n > 120 ? H_16 : H_12 << (max(n - 89, 0) >> 3); }
template<int V> struct Int { static constexpr int value = V; };

__global__ void __launch_bounds__(NTHREADS, 1)
din_kernel(const __nv_bfloat16* __restrict__ mask, const __nv_bfloat16* __restrict__ target, int B, int grid,
           uint32_t pf_mask, uint32_t pf_tgt, const __nv_bfloat16* __restrict__ w1, const __nv_bfloat16* __restrict__ hist,
           const __nv_bfloat16* __restrict__ b1, const __nv_bfloat16* __restrict__ w2,
           const __nv_bfloat16* __restrict__ b2, __nv_bfloat16* __restrict__ out, unsigned int* counter, int pace,
           int slow_from, int pace_slow, int spread) {
  {
    const char* pm = reinterpret_cast<const char*>(mask) + (size_t)blockIdx.x * pf_mask;
    const char* pt = reinterpret_cast<const char*>(target) + (size_t)blockIdx.x * pf_tgt;
    const uint32_t o = threadIdx.x * 128;
    asm volatile("{\n.reg .pred p;\nsetp.lt.u32 p, %1, %2;\n@p prefetch.global.L2 [%0];\n}\n" :: "l"(pm + o), "r"(o), "r"(pf_mask));
    asm volatile("{\n.reg .pred p;\nsetp.lt.u32 p, %1, %2;\n@p prefetch.global.L2 [%0];\n}\n" :: "l"(pt + o), "r"(o), "r"(pf_tgt));
  }
  extern __shared__ unsigned char smem_raw[];
  const uint32_t sb = (smem_u32(smem_raw) + 1023u) & ~1023u;
  const int tid = threadIdx.x, lane = tid & 31;
  const int warp = __shfl_sync(0xffffffffu, tid >> 5, 0);
#define ACT NCW
  const int bstep = ACT * grid;

  STAMP(0);
  if (warp < NCW * 4) {
    const int wg = warp >> 2, w = warp & 3;
    const int g = lane >> 2;
    const uint32_t ring = sb + wg * RING_BYTES;
    const bool active = wg * grid + (int)blockIdx.x < B && wg < ACT;
    {
      const int t = tid & 127;
      const uint32_t dst = sb + ((t ^ ((t >> 3) & 7)) << 4);
      const char* src = reinterpret_cast<const char*>(w1) + t * 16;
#pragma unroll
      for (int i = 0; i < 4; i++) cp_async16(dst + w1_at(i) + wg * 2048, src + i * 8192 + wg * 2048);
      cp_async16(dst + w1_at(0) + (wg >> 1) * RING_BYTES + (wg & 1) * SLOT_BYTES + 6144, src + wg * 8192 + 6144);
      if (wg == 0) cp_async16(dst + w1_at(3) + 6144, src + 3 * 8192 + 6144);
      if (lane < 8) {
        if (w == 0 && active) cp_async16(ring + R_TGT0 + lane * 16, target + (size_t)(wg * grid + blockIdx.x) * kD + lane * 8);
        if (w == 1 && wg < 2) cp_async16(ring + R_VEC + lane * 16, (wg ? w2 : b1) + lane * 8);
      }
    }
    if (w == 2) sts32(ring + R_SEL + lane * 4, 0x3f803f80u);
    uint32_t rb2;
    asm volatile("ld.global.nc.u16 %0, [%1];" : "=r"(rb2) : "l"(b2));
    asm volatile("setmaxnreg.inc.sync.aligned.u32 %0;" :: "n"(CONS_REGS));
    asm volatile("cp.async.wait_all;" ::: "memory");
    STAMP(5);
    asm volatile("bar.sync 1, %0;" :: "n"(NCW * 160) : "memory");
    const uint32_t half2 = 0x3f003f00u, nhalf2 = 0xbf00bf00u, nzero2 = 0x80008000u;
    const uint32_t vec = sb + R_VEC + (16 * w + g) * 2;
    const float w2a = 0.5f * __uint_as_float(lds16(vec + RING_BYTES) << 16);
    const float w2b = 0.5f * __uint_as_float(lds16(vec + RING_BYTES + 16) << 16);
    const uint32_t rw2 = lds32(sb + RING_BYTES + R_VEC + lane * 4);
    float c32 = __uint_as_float(rw2 << 16) + __uint_as_float(rw2 & 0xffff0000u);
#pragma unroll
    for (int o = 16; o; o >>= 1) c32 += __shfl_xor_sync(0xffffffffu, c32, o);
    c32 = (0.5f * c32 + __uint_as_float(rb2 << 16)) * (1.0f / 32.0f);
    uint32_t bq[4];
    bq[2] = hfma2_bf16(lds16(vec), half2, nzero2);
    bq[3] = hfma2_bf16(lds16(vec + 16), half2, nzero2);
    if (lane & 3) bq[2] = bq[3] = 0;
    uint32_t wac[16], wd[16], wbc[16];
    {
      const int mi = lane >> 3, rr = lane & 7;
      const uint32_t a0 = sb + (8 * (mi >> 1) + rr) * 128 + (((2 * w + (mi & 1)) ^ rr) << 4);
#pragma unroll
      for (int ks = 0; ks < 4; ks++) {
        uint32_t A[4], Bm[4], C[4], Dm[4];
        ldsm_x4_t(a0 + ks * 2048 + w1_at(0), A[0], A[1], A[2], A[3]);
        ldsm_x4_t(a0 + ks * 2048 + w1_at(1), Bm[0], Bm[1], Bm[2], Bm[3]);
        ldsm_x4_t(a0 + ks * 2048 + w1_at(2), C[0], C[1], C[2], C[3]);
        ldsm_x4_t(a0 + ks * 2048 + w1_at(3), Dm[0], Dm[1], Dm[2], Dm[3]);
#pragma unroll
        for (int e = 0; e < 4; e++) {
          wac[4 * ks + e] = hfma2_bf16(A[e], half2, hfma2_bf16(C[e], half2, nzero2));
          wbc[4 * ks + e] = hfma2_bf16(Bm[e], half2, hfma2_bf16(C[e], nhalf2, nzero2));
          wd[4 * ks + e] = hfma2_bf16(Dm[e], half2, nzero2);
        }
      }
    }
    asm volatile("fence.proxy.async.shared::cta;" ::: "memory");
    asm volatile("bar.sync 5, %0;" :: "n"(NCW * 128) : "memory");

    const uint32_t ln = __shfl_sync(0xffffffffu, lane, lane);
    const uint32_t q0 = __shfl_sync(0xffffffffu, (lane & 3) ? 0u : 0xffffffffu, lane);
    const uint32_t meta = __shfl_sync(0xffffffffu, 0x88dddd88u + (grid >> 20), lane);
    const uint32_t zr = grid >> 20;
    const uint32_t sel = (ring + R_SEL) >> 4;
    const uint32_t ost = __shfl_sync(0xffffffffu, (lane >> 4) * 1024 + w * 256 + (lane & 15) * 16, lane);
    const uint32_t first = ring;
    const uint32_t last = first + (NSLOT - 1) * SLOT_BYTES;
    uint32_t sa = first, phase = 0;
    uint32_t we[16];
    auto make_weff = [&](uint32_t ta) {
      uint32_t t[8];
      ta += (ln & 24) << 1;
      ldsm_x4(ta, t[0], t[1], t[2], t[3]);
      ldsm_x4(ta + 64, t[4], t[5], t[6], t[7]);
#pragma unroll
      for (int i = 0; i < 16; i++) we[i] = hfma2_bf16(t[i >> 1], wd[i], wac[i]);
    };
    auto make_bq = [&](const float (&bz)[4]) {
#pragma unroll
      for (int e = 0; e < 2; e++) {
        const uint32_t v = __float_as_uint(bz[2 * e]) & q0;
        const float hi = __uint_as_float(v & 0xffff0000u);
        bq[e] = pack_bf16(__uint_as_float(v) - hi, hi);
      }
    };
    if (active) {
      {
        float bz[4];
        uint64_t d0 = (uint64_t)DESC_ROWS << 32 | (ring + R_TGT0) >> 4;
        mma_fence();
        bias_out<0>(bz, wbc, d0);
        make_weff(ring + R_TGT0);
        mma_wait<0>(bz);
        make_bq(bz);
      }
      STAMP(1);
      uint32_t raw = 0, cur, hdr;
      uint32_t full = 0;
      auto finish = [&]() {
        asm volatile("bar.sync %0, 128;" :: "r"(2 + wg) : "memory");
        const uint32_t ra = cur + S_OUT + w * 1024 + ln * 16;
        uint32_t f0[4], f1[4];
        ldsm_x4_t(ra, f0[0], f0[1], f0[2], f0[3]);
        ldsm_x4_t(ra + 512, f1[0], f1[1], f1[2], f1[3]);
        uint32_t* dst = reinterpret_cast<uint32_t*>(out) + (lds32(first + R_STOP + 4) + 4 * w + (ln & 4) * 4 + (ln >> 3));
        float c0[4] = {0.f, 0.f, 0.f, 0.f}, c1[4] = {0.f, 0.f, 0.f, 0.f};
        mma_bf16(c0, f0, 0x3f803f80u);
        mma_bf16(c1, f1, 0x3f803f80u);
        *dst = pack_bf16(c0[0] + c1[0], c0[2] + c1[2]);
      };
      auto chunk = [&](auto groups) {
        constexpr int N8 = decltype(groups)::value, NY = N8 - NA;
        constexpr int KT = (N8 + 1) / 2, E1 = KT - (N8 == 16 ? 3 : N8 == 14 ? KL14 : KL), E0 = N8 < 16 && K0 < E1 ? K0 : E1;
        float x[4 * NA], y[4 * NY], bz[4], o[16];
        uint32_t a[4 * E0], a1[E1 > E0 ? 4 * (E1 - E0) : 4], a2[4 * (KT - E1)];
        auto M = [&](int i0, int i1) {
#pragma unroll
          for (int i = i0; i < i1; i++) {
            uint32_t p = i < NA ? mix(x, i, w2a, w2b, c32) : i < N8 ? mix(y, i - NA, w2a, w2b, c32) : 0;
            if (N8 == 16) {
              uint32_t m = 0x3f803f80u;
              asm volatile("{\n.reg .pred p;\nsetp.ne.u32 p, %1, 0;\n@p ld.shared.u32 %0, [%2];\n}\n"
                           : "+r"(m) : "r"(hdr & H_GENERAL), "r"(cur + S_MASK + i * 16 + (ln & 3) * 4) : "memory");
              p = hfma2_bf16(p, m, 0x80008000u);
            }
            if (i < 2 * E0) a[2 * i] = a[2 * i + 1] = p;
            else if (i < 2 * E1) a1[2 * i - 4 * E0] = a1[2 * i - 4 * E0 + 1] = p;
            else a2[2 * i - 4 * E1] = a2[2 * i - 4 * E1 + 1] = p;
          }
        };
        auto header = [&]() {
          raw = lds32(sa + S_HDR);
          raw = (raw >> 31) == phase ? 0 : raw;
        };
        const uint32_t sta = cur + S_OUT + ost;
        uint64_t db = (uint64_t)(DESC_ROWS + (cur >> 24)) << 32 | cur >> 4;
        const uint32_t par = phase;
        phase ^= sa == last;
        sa = sa == last ? first : sa + SLOT_BYTES;
        mma_fence();
        bias_in(x, bq, sel);
        bias_in(y, bq, sel);
        mbar_wait_unless(full, cur + S_FULL, par);
        LOGT(0);
        mma_fence();
        gemm1<0>(x, we, db);
        bias_out<S_TGT / 16>(bz, wbc, db);
        mma_wait<1>(x);
        const uint32_t there = mbar_test(cur + S_REST, par);
        tanh_range(x, 0, 4 * SA);
        mbar_wait_unless(there, cur + S_REST, par);
        LOGT(2);
        mma_fence();
        gemm1<64 * NA>(y, we, db);
        tanh_range(x, 4 * SA, 4 * (SA + SB));
        if (__builtin_expect(zr != 0, 0)) {
          __nanosleep(zr);
#pragma unroll
          for (int i = 4 * (SA + SB); i < 4 * NA; i++) asm volatile("mov.b32 %0, %1;" : "=f"(x[i]) : "r"(ln));
        }
        tanh_range(x, 4 * (SA + SB), 4 * NA);
        M(0, NA - 1);
        if (__builtin_expect(zr != 0, 0)) {
          __nanosleep(zr);
#pragma unroll
          for (int i = 0; i < NA - 1; i++) sts32(zr + i, a[2 * i]);
#pragma unroll
          for (int i = 4 * NA - 4; i < 4 * NA; i++) sts32(zr + i, __float_as_uint(x[i]));
        }
        mma_wait<0>(y);
        asm volatile("" : "+f"(bz[0]), "+f"(bz[2]) :: "memory");
        header();
        tanh_range(y, 0, 4 * (2 * E0 - NA));
        make_weff(cur + S_TGT);
        M(NA - 1, 2 * E0);
        auto after = [&](uint32_t g, uint32_t u, auto more) {
          asm volatile("{\n.reg .b32 lo, hi, z;\n.reg .pred p;\nand.b32 z, %1, %2;\nsetp.ne.u32 p, z, 0;\nvote.sync.ballot.b32 z, p, 0xffffffff;\n"
                       "and.b32 z, z, %4;\nmov.b64 {lo, hi}, %0;\nadd.u32 hi, hi, %3;\nadd.u32 hi, hi, z;\nmov.b64 %0, {lo, hi};\n}\n"
                       : "+l"(db) : "r"(g), "r"(zr), "n"(decltype(more)::value), "r"(u));
        };
        constexpr int EP = E1 == E0 ? 2 : TP;
        if (EP >= 2) { make_bq(bz); raw = __shfl_sync(0xffffffffu, raw, 0); }
        after(a[4 * E0 - 2] | a[4 * E0 - 4] | (EP == 2 ? bq[0] | bq[1] | sta : 0), EP == 2 ? raw : ~0u, Int<(int)(DESC_HALVES - DESC_ROWS)>());
        gemm2_first<0>(o, a, db, meta);
        if constexpr (E1 > E0) {
          tanh_range(y, 4 * (2 * E0 - NA), 4 * (2 * E1 - NA));
          M(2 * E0, 2 * E1);
          if (EP == 3) after(bq[0] | bq[1] | sta, raw, Int<0>());
          gemm2_more<128 * E0>(o, a1, db, meta);
        }
        tanh_range(y, 4 * (2 * E1 - NA), 4 * NY);
        M(2 * E1, 2 * KT);
        gemm2_more<128 * E1>(o, a2, db, meta);
        full = mbar_test(sa + S_FULL, phase);
        mma_wait<0>(o);
#pragma unroll
        for (int j = 0; j < 2; j++)
          stsm_x4(sta + j * 2048, pack_bf16(o[8 * j], o[8 * j + 2]), pack_bf16(o[8 * j + 1], o[8 * j + 3]),
                  pack_bf16(o[8 * j + 4], o[8 * j + 6]), pack_bf16(o[8 * j + 5], o[8 * j + 7]));
        LOGT(1);
        __syncwarp();
        asm volatile("{\n.reg .pred p;\nsetp.eq.u32 p, %1, 0;\n@p mbarrier.arrive.shared::cta.b64 _, [%0];\n}\n"
                     :: "r"(cur + S_EMPTY), "r"(ln | (hdr & H_FINAL)) : "memory");
      };
      while (true) {
        hdr = __shfl_sync(0xffffffffu, raw, 0);
        cur = sa;
        if (hdr & H_13) { chunk(Int<13>()); if (hdr & H_FINAL) break; }
        else if (hdr & H_12) { chunk(Int<12>()); if (hdr & H_FINAL) break; }
        else if (hdr & H_14) { chunk(Int<14>()); if (hdr & H_FINAL) break; }
        else if (hdr & H_15) { chunk(Int<15>()); if (hdr & H_FINAL) break; }
        else if (hdr & H_STOP) return;
        else if (hdr) { chunk(Int<16>()); if (hdr & H_FINAL) break; }
        else {
          asm volatile("{\n.reg .pred p;\n.reg .u32 n, t;\nmov.u32 n, 0;\n"
                       "AGAIN:\nnanosleep.u32 32;\nld.shared.u32 %0, [%1];\nshfl.sync.idx.b32 %0, %0, 0, 31, 0xffffffff;\n"
                       "shr.u32 t, %0, 31;\nsetp.ne.u32 p, t, %2;\n@p bra.uni THERE;\n"
                       "add.u32 n, n, 1;\nsetp.lt.u32 p, n, 0x1000000;\n@p bra.uni AGAIN;\ntrap;\nTHERE:\n}\n"
                       : "=r"(raw) : "r"(sa + S_HDR), "r"(phase) : "memory");
        }
      }
      finish();
    }
    STAMP(4);
  } else {
    const int pw = warp - NCW * 4;
    const uint32_t ring = sb + pw * RING_BYTES;
    asm volatile("setmaxnreg.dec.sync.aligned.u32 %0;" :: "n"(PROD_REGS));
    if (pw < NCW) {
      int b = pw * grid + blockIdx.x, bn = b + bstep;
      uint4 mw = load_mask(mask, min(b, B - 1), min(lane, 24));
      if (lane == 0) {
#pragma unroll
        for (int i = 0; i < NSLOT; i++) {
          mbar_init(ring + i * SLOT_BYTES + S_FULL, 33);
          mbar_init(ring + i * SLOT_BYTES + S_REST, 33);
          mbar_arrive(ring + i * SLOT_BYTES + S_REST);
          mbar_init(ring + i * SLOT_BYTES + S_EMPTY, 4);
          sts32(ring + i * SLOT_BYTES + S_HDR, 0);
        }
        sts32(ring + R_STOP, b < B && pw < ACT ? 0 : ring);
      }
      sts32(sb + R_PACE + lane * 4, 0);
      asm volatile("bar.arrive 1, %0;" :: "n"(NCW * 160) : "memory");
      asm volatile("bar.arrive 6, 128;" ::: "memory");
      if (pw >= ACT) return;
      const uint32_t list = ring + R_LIST;
      uint32_t lt;
      asm("mov.u32 %0, %%lanemask_lt;" : "=r"(lt));
      const uint32_t ln = __shfl_sync(0xffffffffu, lane, lane);
      const uint32_t r4 = (ln >> 3) * 4, c16 = (ln & 7) * 16, l25 = min(ln, 24u);
      const uint32_t pick = ln < 25 ? 0xeca8 : 0x9999;
      uint32_t dst[4];
#pragma unroll
      for (int i = 0; i < 4; i++) dst[i] = ring + (r4 + i) * 128 + (c16 ^ (((r4 + i) & 7) << 4));
      uint64_t pol;
      asm("createpolicy.fractional.L2::evict_first.b64 %0, 1.0;" : "=l"(pol));
      uint32_t sa = ring, phase = 1;
      const uint32_t wrap = (uint32_t)(max(B - NSTATIC * bstep, 0) + bstep - 1);
      auto next_slot = [&]() {
        const bool wrapped = sa == ring + (NSLOT - 1) * SLOT_BYTES;
        const int step = wrapped ? -(NSLOT - 1) * SLOT_BYTES : SLOT_BYTES;
        sa += step;
        phase ^= wrapped;
#pragma unroll
        for (int i = 0; i < 4; i++) dst[i] += step;
      };
      uint32_t claimer = ln;
      uint32_t drawn, started = 0;
      int mean16 = 0;
      auto draw = [&]() {
        drawn = B;
        asm volatile("{\n.reg .pred p;\nsetp.eq.u32 p, %3, 0;\n@p atom.global.inc.u32 %0, [%1], %2;\n}\n"
                     : "+r"(drawn) : "l"(counter), "r"(wrap), "r"(claimer) : "memory");
      };
      if (b >= B) draw();
      while (b < B) {
        const uint32_t e0 = nonzero_as_one(mw.x), e1 = nonzero_as_one(mw.y);
        const uint32_t e2 = nonzero_as_one(mw.z), e3 = nonzero_as_one(mw.w);
        const uint32_t nonbin = (e0 ^ mw.x) | (e1 ^ mw.y) | (e2 ^ mw.z) | (e3 ^ mw.w);
        const uint32_t sA = prmt(e0, e1, pick), sB = prmt(e2, e3, pick);
        const uint32_t pA = (sA & 0x01010101u) * 0x01010101u;
        const uint32_t pB = ((sB & 0x01010101u) + (pA >> 24)) * 0x01010101u;
        uint32_t pos = 0;
        int n = 0;
#pragma unroll
        for (int k = 0; k < 4; k++) {
          const uint32_t bal = ballot_bit(pB, 0x01000000u << k);
          pos += __popc(bal & lt) << k;
          n += __popc(bal) << k;
        }
        const uint32_t general = __any_sync(0xffffffffu, nonbin != 0);
        const uint32_t aA = (pA + pos * 0x01010101u) | ~sA, aB = (pB + pos * 0x01010101u) | ~sB;
#pragma unroll
        for (int i = 0; i < 8; i++) sts8(list - 1 + prmt(i < 4 ? aA : aB, 0, 0x4440 + (i & 3)), 8 * ln + i);
        __syncwarp();

        const uint64_t src = reinterpret_cast<uint64_t>(hist) + (uint64_t)b * (kL * kD * 2);
        const bool no_carry = (uint32_t)src <= 0xffffffffu - kL * kD * 2;
        auto begin_fill = [&](uint32_t h, uint32_t part, int nc, int bt, auto extra) {
          LOGT(0);
          mbar_wait(sa + S_EMPTY, phase);
          if (bt >= B && !part) h |= H_FINAL;
          asm volatile("{\n.reg .pred p;\nsetp.ne.u32 p, %3, 0;\n@p st.shared.v2.u32 [%0], {%1, %2};\n}\n"
                       :: "r"(ring + R_STOP), "r"(sa + (phase ^ 1)), "r"(b * 32), "r"(h & H_FINAL) : "memory");
          extra();
          sts32(sa + S_HDR, h | phase << 31);
          sts32(sa + S_ROW + phase * 4, b | part);
          asm volatile("{\n.reg .pred p;\nsetp.eq.u32 p, %1, 0;\n@p mbarrier.arrive.shared::cta.b64 _, [%0];\n}\n"
                       :: "r"(sa + S_FULL), "r"(ln) : "memory");
          mean16 = mean16 == 0 ? 16 * nc : bn >= slow_from ? mean16 : mean16 + nc - (mean16 >> 4);
          asm volatile("{\n.reg .u32 c;\n"
                       "mov.u32 c, %%globaltimer_lo;\n"
                       "red.shared.max.u32 [%1], c;\n"
                       "atom.shared.add.u32 %0, [%1], %2;\n}\n"
                       : "=r"(started) : "r"(sb + R_PACE + ln * 4),
                         "r"(bn >= slow_from ? mean16 * pace_slow >> 8 : nc * pace >> 4) : "memory");
          started = __shfl_sync(0xffffffffu, started, 0);
          if (!(part & ROW_REST)) mw = load_mask(mask, min(bn, B - 1), l25);
          wait_for(started, pace * (CHUNK / 4));
          LOGT(1);
          if (!(part & ROW_REST)) draw();
          asm volatile("cp.async.ca.shared.global [%0], [%1], 4;"
                       :: "r"(sa + S_TGT + ln * 4), "l"(reinterpret_cast<const uint32_t*>(target) + ((uint32_t)min(bt, B - 1) * 32u + ln)) : "memory");
        };
        auto end_fill = [&](int nc) {
          cp_async_arrive_noinc(sa + S_REST);
          next_slot();
          LOGT(2);
        };
        const uint32_t base = (uint32_t)src + c16;
        uint64_t a[4];
        a[0] = a[1] = a[2] = a[3] = (uint64_t)((uint32_t)(src >> 32) + (ln >> 5)) << 32;
        if (__builtin_expect(no_carry && !general && n >= 80 && n <= CHUNK, 1)) {
          uint32_t idx[7];
#pragma unroll
          for (int t = 0; t < 7; t++) idx[t] = lds32(list + r4 + t * 16);
          uint32_t have;
          asm("bmsk.clamp.b32 %0, 0, %1;" : "=r"(have) : "r"(max(n - 80 - (int)r4, 0)));
          begin_fill(size_bit(n), 0, n, bn, [](){});
          cp_group<0>(dst, a, idx[0], base, pol);
          cp_group<1>(dst, a, idx[1], base, pol);
          cp_group<2>(dst, a, idx[2], base, pol);
          cp_async_arrive_noinc(sa + S_FULL);
          if (bn >= slow_from) wait_for(started + spread, spread);
          cp_group<3>(dst, a, idx[3], base, pol);
          cp_group<4>(dst, a, idx[4], base, pol);
          cp_group_m<5, 0>(dst, a, idx[5], base, have, 1, pol);
          cp_group_m<6, 16>(dst, a, idx[6], base, have, n > 96, pol);
          if (n > 112) cp_group_z<7>(dst, a, lds32(list + r4 + 112), base, n - r4, pol);
          end_fill(n);
        } else if (no_carry && !general) {
          int nc = n <= CHUNK ? n : n <= 160 ? 64 : 96;
          uint32_t la = list + r4, part = n <= CHUNK ? 0 : ROW_MORE;
#pragma unroll 1
          while (true) {
            begin_fill(size_bit(nc), part, nc, part == ROW_MORE ? b : bn, [](){});
            const int left = nc - r4;
            cp_group_z<0>(dst, a, lds32(la), base, left, pol);
            cp_group_z<1>(dst, a, lds32(la + 16), base, left, pol);
            cp_group_z<2>(dst, a, lds32(la + 32), base, left, pol);
            cp_async_arrive_noinc(sa + S_FULL);
            if (bn >= slow_from) wait_for(started + spread, spread);
            cp_group_z<3>(dst, a, lds32(la + 48), base, left, pol);
            cp_group_z<4>(dst, a, lds32(la + 64), base, left, pol);
            cp_group_z<5>(dst, a, lds32(la + 80), base, left, pol);
            cp_group_z<6>(dst, a, lds32(la + 96), base, left, pol);
            cp_group_z<7>(dst, a, lds32(la + 112), base, left, pol);
            end_fill(nc);
            if (part != ROW_MORE) break;
            la += nc;
            nc = n - nc;
            part = ROW_REST;
          }
        } else {
          int r0 = 0;
#pragma unroll 1
          do {
            const int nc = min(n - r0, CHUNK);
            const bool more = r0 + CHUNK < n;
            begin_fill(general ? H_GENERAL : H_16, (more ? ROW_MORE : 0u) | (r0 ? ROW_REST : 0u), nc, more ? b : bn, [&]() {
#pragma unroll 1
              for (int z = ln; general && z < CHUNK; z += 32) {
                uint32_t v = 0;
                if (z < nc) {
                  uint32_t row;
                  asm volatile("ld.shared.u8 %0, [%1];" : "=r"(row) : "r"(list + r0 + z) : "memory");
                  v = __bfloat16_as_ushort(mask[(size_t)b * kL + row]);
                }
                sts16(sa + S_MASK + z * 2, v);
              }
              __syncwarp();
            });
#pragma unroll 1
            for (int z = r4 >> 2; z < CHUNK; z += 4) {
              uint32_t row;
              asm volatile("ld.shared.u8 %0, [%1];" : "=r"(row) : "r"(list + r0 + z) : "memory");
              asm volatile("cp.async.cg.shared.global [%0], [%1], 16, %2;"
                           :: "r"(sa + z * 128 + (c16 ^ ((z & 7) << 4))), "l"(src + c16 + (z < nc ? row : 0) * 128),
                              "r"(z < nc ? 16 : 0) : "memory");
            }
            cp_async_arrive_noinc(sa + S_FULL);
            end_fill(nc);
            r0 += CHUNK;
          } while (r0 < n);
        }
        b = bn;
        bn = __shfl_sync(0xffffffffu, drawn, 0) + NSTATIC * bstep;
        if (bn >= B) claimer = 1;
      }
      STAMP(3);
      if (lds32(ring + R_STOP) == 0) {
        mbar_wait(sa + S_EMPTY, phase);
        sts32(sa + S_HDR, H_STOP | phase << 31);
        sts32(ring + R_STOP, sa + (phase ^ 1));
      }
      asm volatile("cp.async.wait_all;" ::: "memory");
      STAMP(4);
    } else {
      uint32_t due = clock();
      int s0 = NSTATIC * bstep + (PF_EARLY * grid + blockIdx.x) * PF_ROWS;
      auto prefetch = [&]() {
        const int cnt = min(PF_ROWS, B - s0);
        if (lane == 0) {
          prefetch_l2(mask + (size_t)s0 * kL, cnt * kL * 2);
          prefetch_l2(target + (size_t)s0 * kD, cnt * kD * 2);
        }
        s0 += grid * PF_ROWS;
      };
#pragma unroll 1
      for (int j = PF_EARLY; j < PF_FAST && s0 < B; j++) {
        while ((int)(due - (uint32_t)clock()) > 0) {}
        prefetch();
        due += PF_CYCLES;
      }
      due += (PF_FAST - 1) * PF_SLOW - (PF_FAST - PF_EARLY) * PF_CYCLES + (blockIdx.x & 255) * (PF_SLOW / 256);
      asm volatile("bar.sync 6, 128;" ::: "memory");
      const uint32_t ln = __shfl_sync(0xffffffffu, lane, lane);
      const uint32_t home = sb + min(ln, NCW - 1u) * RING_BYTES;
      uint32_t mine = ln < NCW ? home : 0;
      const uint32_t word = __shfl_sync(0xffffffffu, (lane & 4) * 4 + (lane & 3) * 4 + (lane >> 3), lane);
      uint32_t idle = 0, r = 0, at;
      auto poll = [&]() {
        uint32_t ready;
        asm volatile("{\n.reg .pred p;\nsetp.ne.u32 p, %3, 0;\n@p mbarrier.test_wait.parity.shared::cta.b64 p, [%1], %2;\n"
                     "vote.sync.ballot.b32 %0, p, 0xffffffff;\n}\n"
                     : "=r"(ready) : "r"((mine & ~1u) + S_EMPTY), "r"(mine & 1), "r"(mine) : "memory");
        static_assert(NCW == 3, "");
        const uint32_t pick = ((r == 0 ? 0x5a53u : r == 1 ? 0xaa13u : 0x1213u) >> (2 * ready)) & 3;
        at = __shfl_sync(0xffffffffu, mine, pick);
        r = ready ? pick : r;
      };
      poll();
#pragma unroll 1
      while (true) {
        if (at) {
          const uint32_t sa = at & ~1u, carry = sb + r * RING_BYTES + R_CARRY + ln * 8;
          uint32_t f[8][4];
#pragma unroll
          for (int i = 0; i < 8; i++) ldsm_x4_t(sa + S_OUT + ln * 16 + (i >> 2) * 512 + (i & 3) * 1024, f[i][0], f[i][1], f[i][2], f[i][3]);
          const uint32_t row = lds32(sa + S_ROW + 4 - (at & 1) * 4);
          if (ln == r) mine = sa == home + (NSLOT - 1) * SLOT_BYTES ? (at - (NSLOT - 1) * SLOT_BYTES) ^ 1 : at + SLOT_BYTES;
          float c[8][4];
#pragma unroll
          for (int i = 0; i < 8; i++) {
            c[i][0] = c[i][1] = c[i][2] = c[i][3] = 0.f;
            mma_bf16(c[i], f[i], 0x3f803f80u);
          }
          poll();
          asm volatile("{\n.reg .pred p;\nsetp.eq.u32 p, %1, 0;\n@p mbarrier.arrive.shared::cta.b64 _, [%0];\n}\n"
                       :: "r"(sa + S_REST), "r"(ln) : "memory");
          float e[2];
#pragma unroll
          for (int k = 0; k < 2; k++) {
            const float u0 = ln & 1 ? c[1][2 * k] : c[0][2 * k], u1 = ln & 1 ? c[3][2 * k] : c[2][2 * k];
            const float u2 = ln & 1 ? c[5][2 * k] : c[4][2 * k], u3 = ln & 1 ? c[7][2 * k] : c[6][2 * k];
            e[k] = ln & 2 ? u1 + u3 : u0 + u2;
          }
          asm volatile("{\n.reg .pred p, q;\n.reg .f32 a, b;\n.reg .u32 t;\nshr.u32 t, %3, 30;\nsetp.eq.u32 p, t, 1;\nsetp.eq.u32 q, t, 2;\n"
                       "@p ld.shared.v2.f32 {a, b}, [%2];\n@p add.f32 %0, %0, a;\n@p add.f32 %1, %1, b;\n@q st.shared.v2.f32 [%2], {%0, %1};\n}\n"
                       : "+f"(e[0]), "+f"(e[1]) : "r"(carry), "r"(row) : "memory");
          asm volatile("{\n.reg .pred p;\nsetp.ge.s32 p, %2, 0;\n@p st.global.u32 [%0], %1;\n}\n"
                       :: "l"(reinterpret_cast<uint32_t*>(out) + (row * 32u + word)), "r"(pack_bf16(e[0], e[1])), "r"(row) : "memory");
        } else {
          const uint32_t stop = lds32(home + R_STOP);
          poll();
          if (stop == mine) mine = 0;
          if (!__any_sync(0xffffffffu, mine)) break;
          if (s0 < B) {
            if ((int)(due - (uint32_t)clock()) <= 0) { prefetch(); due += PF_SLOW; }
          } else if (++idle > 0x10000000) __trap();
          if (RED_SLEEP) __nanosleep(RED_SLEEP);
        }
      }
      STAMP(4);
    }
  }
}

}

extern "C" void kernel_launch(void* const* d_in, const int* in_sizes, int n_in, void* d_out, int out_size) {
  const __nv_bfloat16* target = (const __nv_bfloat16*)d_in[0];
  const __nv_bfloat16* hist = (const __nv_bfloat16*)d_in[1];
  const __nv_bfloat16* mask = (const __nv_bfloat16*)d_in[2];
  const __nv_bfloat16* w1 = (const __nv_bfloat16*)d_in[3];
  const __nv_bfloat16* b1 = (const __nv_bfloat16*)d_in[4];
  const __nv_bfloat16* w2 = (const __nv_bfloat16*)d_in[5];
  const __nv_bfloat16* b2 = (const __nv_bfloat16*)d_in[6];
  const int B = in_sizes[0] / din::kD;
  if (B <= 0) return;
  static int sms = 0, pace = 0;
  static unsigned int* counter = nullptr;
  if (sms == 0) {
    int dev = 0, khz = 0, bits = 0;
    cudaGetDevice(&dev);
    cudaDeviceGetAttribute(&sms, cudaDevAttrMultiProcessorCount, dev);
    cudaDeviceGetAttribute(&khz, cudaDevAttrMemoryClockRate, dev);
    cudaDeviceGetAttribute(&bits, cudaDevAttrGlobalMemoryBusWidth, dev);
    if (khz > 0 && bits > 0) pace = (int)(16.0 * 128.0 * sms / (khz * 1e-6 * 2.0 * bits / 8.0));
    if (pace > 256) pace = 0;
    cudaGetSymbolAddress((void**)&counter, din::g_next);
    cudaFuncSetAttribute(din::din_kernel, cudaFuncAttributeMaxDynamicSharedMemorySize, din::SMEM_BYTES);
  }
  const long long early = (long long)(din::NSTATIC * NCW + PF_EARLY * PF_ROWS) * sms, line = 128LL * sms;
  long long pf_mask = (early * din::kL * 2 + line - 1) / line, pf_tgt = early * din::kD * 2 / line;
  if (pf_mask > (long long)B * din::kL * 2 / line) pf_mask = (long long)B * din::kL * 2 / line;
  if (pf_tgt > (long long)B * din::kD * 2 / line) pf_tgt = (long long)B * din::kD * 2 / line;
  din::din_kernel<<<sms, din::NTHREADS, din::SMEM_BYTES>>>(mask, target, B, sms, (uint32_t)pf_mask * 128, (uint32_t)pf_tgt * 128,
                                                          w1, hist, b1, w2, b2, (__nv_bfloat16*)d_out, counter, pace,
                                                          B - SLOW_ROUNDS * NCW * sms / 2, pace + (pace * SLOW_BY + 40) / 80,
                                                          pace * SPREAD / 16);
}
```

```cpp
#include <cuda_runtime.h>
#include <cuda_bf16.h>
#include <stdint.h>

namespace din {

constexpr int kL = 200, kD = 64;
#define NCW 3
#define NSLOT 3
constexpr int CHUNK = 128;
constexpr int NTHREADS = NCW * 128 + 128;
#define PREGS 56
#define CREGS 152
constexpr int PROD_REGS = PREGS, CONS_REGS = CREGS;
#define PF_ROWS 8
#define PF_FAST 10
#define PF_SLOW 2000
#define PF_CYCLES 280
#define RED_SLEEP 0
#define KL 2
#define KL14 2
#define K0 3
#define SA 2
#define SB 1
#define TP 3
#define SPREAD 62
#define SLOW_ROUNDS 12
#define SLOW_BY 9
#define PF_EARLY 3
constexpr int NSTATIC = 2;
constexpr int S_TGT = CHUNK * 128;
constexpr int S_HDR = S_TGT + 128;
constexpr int S_FULL = S_HDR + 8;
constexpr int S_EMPTY = S_HDR + 16;
constexpr int S_ROW = S_HDR + 24;
constexpr int S_REST = S_HDR + 32;
constexpr int S_MASK = S_TGT + 256;
constexpr int S_OUT = S_TGT + 1024;
constexpr int SLOT_BYTES = S_OUT + 8192;
constexpr int RING_BYTES_ = NSLOT * SLOT_BYTES;
constexpr int R_PACE = 2 * RING_BYTES_ + S_TGT + 768;
constexpr int R_STOP = S_HDR + 40;
constexpr int R_LIST = S_TGT + 512;
constexpr int R_VEC = S_TGT + 768;
constexpr int R_SEL = S_TGT + 896;
constexpr int R_CARRY = SLOT_BYTES + S_TGT + 512;
constexpr int R_TGT0 = (NSLOT - 1) * SLOT_BYTES + S_OUT;
constexpr int RING_BYTES = NSLOT * SLOT_BYTES;
constexpr int SMEM_BYTES = NCW * RING_BYTES + 1024;
__device__ constexpr int w1_at(int i) { return (i >> 1) * RING_BYTES + (i & 1) * SLOT_BYTES + S_OUT; }
#define LOGT(slot)
static_assert(SMEM_BYTES <= 232448, "shared memory");
constexpr uint32_t H_12 = 2, H_13 = 4, H_14 = 8, H_15 = 16, H_16 = 1u << 16;
constexpr uint32_t H_GENERAL = 1u << 17, H_FINAL = 1u << 18, H_STOP = 1u << 19;
constexpr uint32_t ROW_REST = 1u << 30, ROW_MORE = 1u << 31;

__device__ unsigned int g_next;

#define STAMP(k)

#define STR2(x) #x
#define STR(x) STR2(x)
constexpr int NA = 5;
__device__ __forceinline__ void bias_in(float (&d)[20], const uint32_t (&a)[4], uint32_t lo) {
  asm volatile("{\n.reg .b64 db;\n"
    "cvt.u64.u32 db, %24;\n"
    "wgmma.mma_async.sync.aligned.m64n40k16.f32.bf16.bf16 {%0, %1, %2, %3, %4, %5, %6, %7, %8, %9, %10, %11, %12, %13, %14, %15, %16, %17, %18, %19}, {%20, %21, %22, %23}, db, 0, 1, 1, 0;\n}\n"
    : "=f"(d[0]), "=f"(d[1]), "=f"(d[2]), "=f"(d[3]), "=f"(d[4]), "=f"(d[5]), "=f"(d[6]), "=f"(d[7]), "=f"(d[8]), "=f"(d[9]), "=f"(d[10]), "=f"(d[11]), "=f"(d[12]), "=f"(d[13]), "=f"(d[14]), "=f"(d[15]), "=f"(d[16]), "=f"(d[17]), "=f"(d[18]), "=f"(d[19])
    : "r"(a[0]), "r"(a[1]), "r"(a[2]), "r"(a[3]), "r"(lo)
    : "memory");
}
__device__ __forceinline__ void bias_in(float (&d)[28], const uint32_t (&a)[4], uint32_t lo) {
  asm volatile("{\n.reg .b64 db;\n"
    "cvt.u64.u32 db, %32;\n"
    "wgmma.mma_async.sync.aligned.m64n56k16.f32.bf16.bf16 {%0, %1, %2, %3, %4, %5, %6, %7, %8, %9, %10, %11, %12, %13, %14, %15, %16, %17, %18, %19, %20, %21, %22, %23, %24, %25, %26, %27}, {%28, %29, %30, %31}, db, 0, 1, 1, 0;\n}\n"
    : "=f"(d[0]), "=f"(d[1]), "=f"(d[2]), "=f"(d[3]), "=f"(d[4]), "=f"(d[5]), "=f"(d[6]), "=f"(d[7]), "=f"(d[8]), "=f"(d[9]), "=f"(d[10]), "=f"(d[11]), "=f"(d[12]), "=f"(d[13]), "=f"(d[14]), "=f"(d[15]), "=f"(d[16]), "=f"(d[17]), "=f"(d[18]), "=f"(d[19]), "=f"(d[20]), "=f"(d[21]), "=f"(d[22]), "=f"(d[23]), "=f"(d[24]), "=f"(d[25]), "=f"(d[26]), "=f"(d[27])
    : "r"(a[0]), "r"(a[1]), "r"(a[2]), "r"(a[3]), "r"(lo)
    : "memory");
}
__device__ __forceinline__ void bias_in(float (&d)[32], const uint32_t (&a)[4], uint32_t lo) {
  asm volatile("{\n.reg .b64 db;\n"
    "cvt.u64.u32 db, %36;\n"
    "wgmma.mma_async.sync.aligned.m64n64k16.f32.bf16.bf16 {%0, %1, %2, %3, %4, %5, %6, %7, %8, %9, %10, %11, %12, %13, %14, %15, %16, %17, %18, %19, %20, %21, %22, %23, %24, %25, %26, %27, %28, %29, %30, %31}, {%32, %33, %34, %35}, db, 0, 1, 1, 0;\n}\n"
    : "=f"(d[0]), "=f"(d[1]), "=f"(d[2]), "=f"(d[3]), "=f"(d[4]), "=f"(d[5]), "=f"(d[6]), "=f"(d[7]), "=f"(d[8]), "=f"(d[9]), "=f"(d[10]), "=f"(d[11]), "=f"(d[12]), "=f"(d[13]), "=f"(d[14]), "=f"(d[15]), "=f"(d[16]), "=f"(d[17]), "=f"(d[18]), "=f"(d[19]), "=f"(d[20]), "=f"(d[21]), "=f"(d[22]), "=f"(d[23]), "=f"(d[24]), "=f"(d[25]), "=f"(d[26]), "=f"(d[27]), "=f"(d[28]), "=f"(d[29]), "=f"(d[30]), "=f"(d[31])
    : "r"(a[0]), "r"(a[1]), "r"(a[2]), "r"(a[3]), "r"(lo)
    : "memory");
}
__device__ __forceinline__ void bias_in(float (&d)[36], const uint32_t (&a)[4], uint32_t lo) {
  asm volatile("{\n.reg .b64 db;\n"
    "cvt.u64.u32 db, %40;\n"
    "wgmma.mma_async.sync.aligned.m64n72k16.f32.bf16.bf16 {%0, %1, %2, %3, %4, %5, %6, %7, %8, %9, %10, %11, %12, %13, %14, %15, %16, %17, %18, %19, %20, %21, %22, %23, %24, %25, %26, %27, %28, %29, %30, %31, %32, %33, %34, %35}, {%36, %37, %38, %39}, db, 0, 1, 1, 0;\n}\n"
    : "=f"(d[0]), "=f"(d[1]), "=f"(d[2]), "=f"(d[3]), "=f"(d[4]), "=f"(d[5]), "=f"(d[6]), "=f"(d[7]), "=f"(d[8]), "=f"(d[9]), "=f"(d[10]), "=f"(d[11]), "=f"(d[12]), "=f"(d[13]), "=f"(d[14]), "=f"(d[15]), "=f"(d[16]), "=f"(d[17]), "=f"(d[18]), "=f"(d[19]), "=f"(d[20]), "=f"(d[21]), "=f"(d[22]), "=f"(d[23]), "=f"(d[24]), "=f"(d[25]), "=f"(d[26]), "=f"(d[27]), "=f"(d[28]), "=f"(d[29]), "=f"(d[30]), "=f"(d[31]), "=f"(d[32]), "=f"(d[33]), "=f"(d[34]), "=f"(d[35])
    : "r"(a[0]), "r"(a[1]), "r"(a[2]), "r"(a[3]), "r"(lo)
    : "memory");
}
__device__ __forceinline__ void bias_in(float (&d)[40], const uint32_t (&a)[4], uint32_t lo) {
  asm volatile("{\n.reg .b64 db;\n"
    "cvt.u64.u32 db, %44;\n"
    "wgmma.mma_async.sync.aligned.m64n80k16.f32.bf16.bf16 {%0, %1, %2, %3, %4, %5, %6, %7, %8, %9, %10, %11, %12, %13, %14, %15, %16, %17, %18, %19, %20, %21, %22, %23, %24, %25, %26, %27, %28, %29, %30, %31, %32, %33, %34, %35, %36, %37, %38, %39}, {%40, %41, %42, %43}, db, 0, 1, 1, 0;\n}\n"
    : "=f"(d[0]), "=f"(d[1]), "=f"(d[2]), "=f"(d[3]), "=f"(d[4]), "=f"(d[5]), "=f"(d[6]), "=f"(d[7]), "=f"(d[8]), "=f"(d[9]), "=f"(d[10]), "=f"(d[11]), "=f"(d[12]), "=f"(d[13]), "=f"(d[14]), "=f"(d[15]), "=f"(d[16]), "=f"(d[17]), "=f"(d[18]), "=f"(d[19]), "=f"(d[20]), "=f"(d[21]), "=f"(d[22]), "=f"(d[23]), "=f"(d[24]), "=f"(d[25]), "=f"(d[26]), "=f"(d[27]), "=f"(d[28]), "=f"(d[29]), "=f"(d[30]), "=f"(d[31]), "=f"(d[32]), "=f"(d[33]), "=f"(d[34]), "=f"(d[35]), "=f"(d[36]), "=f"(d[37]), "=f"(d[38]), "=f"(d[39])
    : "r"(a[0]), "r"(a[1]), "r"(a[2]), "r"(a[3]), "r"(lo)
    : "memory");
}
__device__ __forceinline__ void bias_in(float (&d)[44], const uint32_t (&a)[4], uint32_t lo) {
  asm volatile("{\n.reg .b64 db;\n"
    "cvt.u64.u32 db, %48;\n"
    "wgmma.mma_async.sync.aligned.m64n88k16.f32.bf16.bf16 {%0, %1, %2, %3, %4, %5, %6, %7, %8, %9, %10, %11, %12, %13, %14, %15, %16, %17, %18, %19, %20, %21, %22, %23, %24, %25, %26, %27, %28, %29, %30, %31, %32, %33, %34, %35, %36, %37, %38, %39, %40, %41, %42, %43}, {%44, %45, %46, %47}, db, 0, 1, 1, 0;\n}\n"
    : "=f"(d[0]), "=f"(d[1]), "=f"(d[2]), "=f"(d[3]), "=f"(d[4]), "=f"(d[5]), "=f"(d[6]), "=f"(d[7]), "=f"(d[8]), "=f"(d[9]), "=f"(d[10]), "=f"(d[11]), "=f"(d[12]), "=f"(d[13]), "=f"(d[14]), "=f"(d[15]), "=f"(d[16]), "=f"(d[17]), "=f"(d[18]), "=f"(d[19]), "=f"(d[20]), "=f"(d[21]), "=f"(d[22]), "=f"(d[23]), "=f"(d[24]), "=f"(d[25]), "=f"(d[26]), "=f"(d[27]), "=f"(d[28]), "=f"(d[29]), "=f"(d[30]), "=f"(d[31]), "=f"(d[32]), "=f"(d[33]), "=f"(d[34]), "=f"(d[35]), "=f"(d[36]), "=f"(d[37]), "=f"(d[38]), "=f"(d[39]), "=f"(d[40]), "=f"(d[41]), "=f"(d[42]), "=f"(d[43])
    : "r"(a[0]), "r"(a[1]), "r"(a[2]), "r"(a[3]), "r"(lo)
    : "memory");
}
template<int D> __device__ __forceinline__ void gemm1(float (&d)[20], const uint32_t (&a)[16], uint64_t db) {
  asm volatile("{\n.reg .b64 db;\n"
    "add.s64 db, %36, %37 + 0;\n"
    "wgmma.mma_async.sync.aligned.m64n40k16.f32.bf16.bf16 {%0, %1, %2, %3, %4, %5, %6, %7, %8, %9, %10, %11, %12, %13, %14, %15, %16, %17, %18, %19}, {%20, %21, %22, %23}, db, 1, 1, 1, 0;\n"
    "add.s64 db, %36, %37 + 2;\n"
    "wgmma.mma_async.sync.aligned.m64n40k16.f32.bf16.bf16 {%0, %1, %2, %3, %4, %5, %6, %7, %8, %9, %10, %11, %12, %13, %14, %15, %16, %17, %18, %19}, {%24, %25, %26, %27}, db, 1, 1, 1, 0;\n"
    "add.s64 db, %36, %37 + 4;\n"
    "wgmma.mma_async.sync.aligned.m64n40k16.f32.bf16.bf16 {%0, %1, %2, %3, %4, %5, %6, %7, %8, %9, %10, %11, %12, %13, %14, %15, %16, %17, %18, %19}, {%28, %29, %30, %31}, db, 1, 1, 1, 0;\n"
    "add.s64 db, %36, %37 + 6;\n"
    "wgmma.mma_async.sync.aligned.m64n40k16.f32.bf16.bf16 {%0, %1, %2, %3, %4, %5, %6, %7, %8, %9, %10, %11, %12, %13, %14, %15, %16, %17, %18, %19}, {%32, %33, %34, %35}, db, 1, 1, 1, 0;\n"
    "wgmma.commit_group.sync.aligned;\n}\n"
    : "+f"(d[0]), "+f"(d[1]), "+f"(d[2]), "+f"(d[3]), "+f"(d[4]), "+f"(d[5]), "+f"(d[6]), "+f"(d[7]), "+f"(d[8]), "+f"(d[9]), "+f"(d[10]), "+f"(d[11]), "+f"(d[12]), "+f"(d[13]), "+f"(d[14]), "+f"(d[15]), "+f"(d[16]), "+f"(d[17]), "+f"(d[18]), "+f"(d[19])
    : "r"(a[0]), "r"(a[1]), "r"(a[2]), "r"(a[3]), "r"(a[4]), "r"(a[5]), "r"(a[6]), "r"(a[7]), "r"(a[8]), "r"(a[9]), "r"(a[10]), "r"(a[11]), "r"(a[12]), "r"(a[13]), "r"(a[14]), "r"(a[15]), "l"(db), "n"(D)
    : "memory");
}
template<int D> __device__ __forceinline__ void gemm1(float (&d)[28], const uint32_t (&a)[16], uint64_t db) {
  asm volatile("{\n.reg .b64 db;\n"
    "add.s64 db, %44, %45 + 0;\n"
    "wgmma.mma_async.sync.aligned.m64n56k16.f32.bf16.bf16 {%0, %1, %2, %3, %4, %5, %6, %7, %8, %9, %10, %11, %12, %13, %14, %15, %16, %17, %18, %19, %20, %21, %22, %23, %24, %25, %26, %27}, {%28, %29, %30, %31}, db, 1, 1, 1, 0;\n"
    "add.s64 db, %44, %45 + 2;\n"
    "wgmma.mma_async.sync.aligned.m64n56k16.f32.bf16.bf16 {%0, %1, %2, %3, %4, %5, %6, %7, %8, %9, %10, %11, %12, %13, %14, %15, %16, %17, %18, %19, %20, %21, %22, %23, %24, %25, %26, %27}, {%32, %33, %34, %35}, db, 1, 1, 1, 0;\n"
    "add.s64 db, %44, %45 + 4;\n"
    "wgmma.mma_async.sync.aligned.m64n56k16.f32.bf16.bf16 {%0, %1, %2, %3, %4, %5, %6, %7, %8, %9, %10, %11, %12, %13, %14, %15, %16, %17, %18, %19, %20, %21, %22, %23, %24, %25, %26, %27}, {%36, %37, %38, %39}, db, 1, 1, 1, 0;\n"
    "add.s64 db, %44, %45 + 6;\n"
    "wgmma.mma_async.sync.aligned.m64n56k16.f32.bf16.bf16 {%0, %1, %2, %3, %4, %5, %6, %7, %8, %9, %10, %11, %12, %13, %14, %15, %16, %17, %18, %19, %20, %21, %22, %23, %24, %25, %26, %27}, {%40, %41, %42, %43}, db, 1, 1, 1, 0;\n"
    "wgmma.commit_group.sync.aligned;\n}\n"
    : "+f"(d[0]), "+f"(d[1]), "+f"(d[2]), "+f"(d[3]), "+f"(d[4]), "+f"(d[5]), "+f"(d[6]), "+f"(d[7]), "+f"(d[8]), "+f"(d[9]), "+f"(d[10]), "+f"(d[11]), "+f"(d[12]), "+f"(d[13]), "+f"(d[14]), "+f"(d[15]), "+f"(d[16]), "+f"(d[17]), "+f"(d[18]), "+f"(d[19]), "+f"(d[20]), "+f"(d[21]), "+f"(d[22]), "+f"(d[23]), "+f"(d[24]), "+f"(d[25]), "+f"(d[26]), "+f"(d[27])
    : "r"(a[0]), "r"(a[1]), "r"(a[2]), "r"(a[3]), "r"(a[4]), "r"(a[5]), "r"(a[6]), "r"(a[7]), "r"(a[8]), "r"(a[9]), "r"(a[10]), "r"(a[11]), "r"(a[12]), "r"(a[13]), "r"(a[14]), "r"(a[15]), "l"(db), "n"(D)
    : "memory");
}
template<int D> __device__ __forceinline__ void gemm1(float (&d)[32], const uint32_t (&a)[16], uint64_t db) {
  asm volatile("{\n.reg .b64 db;\n"
    "add.s64 db, %48, %49 + 0;\n"
    "wgmma.mma_async.sync.aligned.m64n64k16.f32.bf16.bf16 {%0, %1, %2, %3, %4, %5, %6, %7, %8, %9, %10, %11, %12, %13, %14, %15, %16, %17, %18, %19, %20, %21, %22, %23, %24, %25, %26, %27, %28, %29, %30, %31}, {%32, %33, %34, %35}, db, 1, 1, 1, 0;\n"
    "add.s64 db, %48, %49 + 2;\n"
    "wgmma.mma_async.sync.aligned.m64n64k16.f32.bf16.bf16 {%0, %1, %2, %3, %4, %5, %6, %7, %8, %9, %10, %11, %12, %13, %14, %15, %16, %17, %18, %19, %20, %21, %22, %23, %24, %25, %26, %27, %28, %29, %30, %31}, {%36, %37, %38, %39}, db, 1, 1, 1, 0;\n"
    "add.s64 db, %48, %49 + 4;\n"
    "wgmma.mma_async.sync.aligned.m64n64k16.f32.bf16.bf16 {%0, %1, %2, %3, %4, %5, %6, %7, %8, %9, %10, %11, %12, %13, %14, %15, %16, %17, %18, %19, %20, %21, %22, %23, %24, %25, %26, %27, %28, %29, %30, %31}, {%40, %41, %42, %43}, db, 1, 1, 1, 0;\n"
    "add.s64 db, %48, %49 + 6;\n"
    "wgmma.mma_async.sync.aligned.m64n64k16.f32.bf16.bf16 {%0, %1, %2, %3, %4, %5, %6, %7, %8, %9, %10, %11, %12, %13, %14, %15, %16, %17, %18, %19, %20, %21, %22, %23, %24, %25, %26, %27, %28, %29, %30, %31}, {%44, %45, %46, %47}, db, 1, 1, 1, 0;\n"
    "wgmma.commit_group.sync.aligned;\n}\n"
    : "+f"(d[0]), "+f"(d[1]), "+f"(d[2]), "+f"(d[3]), "+f"(d[4]), "+f"(d[5]), "+f"(d[6]), "+f"(d[7]), "+f"(d[8]), "+f"(d[9]), "+f"(d[10]), "+f"(d[11]), "+f"(d[12]), "+f"(d[13]), "+f"(d[14]), "+f"(d[15]), "+f"(d[16]), "+f"(d[17]), "+f"(d[18]), "+f"(d[19]), "+f"(d[20]), "+f"(d[21]), "+f"(d[22]), "+f"(d[23]), "+f"(d[24]), "+f"(d[25]), "+f"(d[26]), "+f"(d[27]), "+f"(d[28]), "+f"(d[29]), "+f"(d[30]), "+f"(d[31])
    : "r"(a[0]), "r"(a[1]), "r"(a[2]), "r"(a[3]), "r"(a[4]), "r"(a[5]), "r"(a[6]), "r"(a[7]), "r"(a[8]), "r"(a[9]), "r"(a[10]), "r"(a[11]), "r"(a[12]), "r"(a[13]), "r"(a[14]), "r"(a[15]), "l"(db), "n"(D)
    : "memory");
}
template<int D> __device__ __forceinline__ void gemm1(float (&d)[36], const uint32_t (&a)[16], uint64_t db) {
  asm volatile("{\n.reg .b64 db;\n"
    "add.s64 db, %52, %53 + 0;\n"
    "wgmma.mma_async.sync.aligned.m64n72k16.f32.bf16.bf16 {%0, %1, %2, %3, %4, %5, %6, %7, %8, %9, %10, %11, %12, %13, %14, %15, %16, %17, %18, %19, %20, %21, %22, %23, %24, %25, %26, %27, %28, %29, %30, %31, %32, %33, %34, %35}, {%36, %37, %38, %39}, db, 1, 1, 1, 0;\n"
    "add.s64 db, %52, %53 + 2;\n"
    "wgmma.mma_async.sync.aligned.m64n72k16.f32.bf16.bf16 {%0, %1, %2, %3, %4, %5, %6, %7, %8, %9, %10, %11, %12, %13, %14, %15, %16, %17, %18, %19, %20, %21, %22, %23, %24, %25, %26, %27, %28, %29, %30, %31, %32, %33, %34, %35}, {%40, %41, %42, %43}, db, 1, 1, 1, 0;\n"
    "add.s64 db, %52, %53 + 4;\n"
    "wgmma.mma_async.sync.aligned.m64n72k16.f32.bf16.bf16 {%0, %1, %2, %3, %4, %5, %6, %7, %8, %9, %10, %11, %12, %13, %14, %15, %16, %17, %18, %19, %20, %21, %22, %23, %24, %25, %26, %27, %28, %29, %30, %31, %32, %33, %34, %35}, {%44, %45, %46, %47}, db, 1, 1, 1, 0;\n"
    "add.s64 db, %52, %53 + 6;\n"
    "wgmma.mma_async.sync.aligned.m64n72k16.f32.bf16.bf16 {%0, %1, %2, %3, %4, %5, %6, %7, %8, %9, %10, %11, %12, %13, %14, %15, %16, %17, %18, %19, %20, %21, %22, %23, %24, %25, %26, %27, %28, %29, %30, %31, %32, %33, %34, %35}, {%48, %49, %50, %51}, db, 1, 1, 1, 0;\n"
    "wgmma.commit_group.sync.aligned;\n}\n"
    : "+f"(d[0]), "+f"(d[1]), "+f"(d[2]), "+f"(d[3]), "+f"(d[4]), "+f"(d[5]), "+f"(d[6]), "+f"(d[7]), "+f"(d[8]), "+f"(d[9]), "+f"(d[10]), "+f"(d[11]), "+f"(d[12]), "+f"(d[13]), "+f"(d[14]), "+f"(d[15]), "+f"(d[16]), "+f"(d[17]), "+f"(d[18]), "+f"(d[19]), "+f"(d[20]), "+f"(d[21]), "+f"(d[22]), "+f"(d[23]), "+f"(d[24]), "+f"(d[25]), "+f"(d[26]), "+f"(d[27]), "+f"(d[28]), "+f"(d[29]), "+f"(d[30]), "+f"(d[31]), "+f"(d[32]), "+f"(d[33]), "+f"(d[34]), "+f"(d[35])
    : "r"(a[0]), "r"(a[1]), "r"(a[2]), "r"(a[3]), "r"(a[4]), "r"(a[5]), "r"(a[6]), "r"(a[7]), "r"(a[8]), "r"(a[9]), "r"(a[10]), "r"(a[11]), "r"(a[12]), "r"(a[13]), "r"(a[14]), "r"(a[15]), "l"(db), "n"(D)
    : "memory");
}
template<int D> __device__ __forceinline__ void gemm1(float (&d)[40], const uint32_t (&a)[16], uint64_t db) {
  asm volatile("{\n.reg .b64 db;\n"
    "add.s64 db, %56, %57 + 0;\n"
    "wgmma.mma_async.sync.aligned.m64n80k16.f32.bf16.bf16 {%0, %1, %2, %3, %4, %5, %6, %7, %8, %9, %10, %11, %12, %13, %14, %15, %16, %17, %18, %19, %20, %21, %22, %23, %24, %25, %26, %27, %28, %29, %30, %31, %32, %33, %34, %35, %36, %37, %38, %39}, {%40, %41, %42, %43}, db, 1, 1, 1, 0;\n"
    "add.s64 db, %56, %57 + 2;\n"
    "wgmma.mma_async.sync.aligned.m64n80k16.f32.bf16.bf16 {%0, %1, %2, %3, %4, %5, %6, %7, %8, %9, %10, %11, %12, %13, %14, %15, %16, %17, %18, %19, %20, %21, %22, %23, %24, %25, %26, %27, %28, %29, %30, %31, %32, %33, %34, %35, %36, %37, %38, %39}, {%44, %45, %46, %47}, db, 1, 1, 1, 0;\n"
    "add.s64 db, %56, %57 + 4;\n"
    "wgmma.mma_async.sync.aligned.m64n80k16.f32.bf16.bf16 {%0, %1, %2, %3, %4, %5, %6, %7, %8, %9, %10, %11, %12, %13, %14, %15, %16, %17, %18, %19, %20, %21, %22, %23, %24, %25, %26, %27, %28, %29, %30, %31, %32, %33, %34, %35, %36, %37, %38, %39}, {%48, %49, %50, %51}, db, 1, 1, 1, 0;\n"
    "add.s64 db, %56, %57 + 6;\n"
    "wgmma.mma_async.sync.aligned.m64n80k16.f32.bf16.bf16 {%0, %1, %2, %3, %4, %5, %6, %7, %8, %9, %10, %11, %12, %13, %14, %15, %16, %17, %18, %19, %20, %21, %22, %23, %24, %25, %26, %27, %28, %29, %30, %31, %32, %33, %34, %35, %36, %37, %38, %39}, {%52, %53, %54, %55}, db, 1, 1, 1, 0;\n"
    "wgmma.commit_group.sync.aligned;\n}\n"
    : "+f"(d[0]), "+f"(d[1]), "+f"(d[2]), "+f"(d[3]), "+f"(d[4]), "+f"(d[5]), "+f"(d[6]), "+f"(d[7]), "+f"(d[8]), "+f"(d[9]), "+f"(d[10]), "+f"(d[11]), "+f"(d[12]), "+f"(d[13]), "+f"(d[14]), "+f"(d[15]), "+f"(d[16]), "+f"(d[17]), "+f"(d[18]), "+f"(d[19]), "+f"(d[20]), "+f"(d[21]), "+f"(d[22]), "+f"(d[23]), "+f"(d[24]), "+f"(d[25]), "+f"(d[26]), "+f"(d[27]), "+f"(d[28]), "+f"(d[29]), "+f"(d[30]), "+f"(d[31]), "+f"(d[32]), "+f"(d[33]), "+f"(d[34]), "+f"(d[35]), "+f"(d[36]), "+f"(d[37]), "+f"(d[38]), "+f"(d[39])
    : "r"(a[0]), "r"(a[1]), "r"(a[2]), "r"(a[3]), "r"(a[4]), "r"(a[5]), "r"(a[6]), "r"(a[7]), "r"(a[8]), "r"(a[9]), "r"(a[10]), "r"(a[11]), "r"(a[12]), "r"(a[13]), "r"(a[14]), "r"(a[15]), "l"(db), "n"(D)
    : "memory");
}
template<int D> __device__ __forceinline__ void gemm1(float (&d)[44], const uint32_t (&a)[16], uint64_t db) {
  asm volatile("{\n.reg .b64 db;\n"
    "add.s64 db, %60, %61 + 0;\n"
    "wgmma.mma_async.sync.aligned.m64n88k16.f32.bf16.bf16 {%0, %1, %2, %3, %4, %5, %6, %7, %8, %9, %10, %11, %12, %13, %14, %15, %16, %17, %18, %19, %20, %21, %22, %23, %24, %25, %26, %27, %28, %29, %30, %31, %32, %33, %34, %35, %36, %37, %38, %39, %40, %41, %42, %43}, {%44, %45, %46, %47}, db, 1, 1, 1, 0;\n"
    "add.s64 db, %60, %61 + 2;\n"
    "wgmma.mma_async.sync.aligned.m64n88k16.f32.bf16.bf16 {%0, %1, %2, %3, %4, %5, %6, %7, %8, %9, %10, %11, %12, %13, %14, %15, %16, %17, %18, %19, %20, %21, %22, %23, %24, %25, %26, %27, %28, %29, %30, %31, %32, %33, %34, %35, %36, %37, %38, %39, %40, %41, %42, %43}, {%48, %49, %50, %51}, db, 1, 1, 1, 0;\n"
    "add.s64 db, %60, %61 + 4;\n"
    "wgmma.mma_async.sync.aligned.m64n88k16.f32.bf16.bf16 {%0, %1, %2, %3, %4, %5, %6, %7, %8, %9, %10, %11, %12, %13, %14, %15, %16, %17, %18, %19, %20, %21, %22, %23, %24, %25, %26, %27, %28, %29, %30, %31, %32, %33, %34, %35, %36, %37, %38, %39, %40, %41, %42, %43}, {%52, %53, %54, %55}, db, 1, 1, 1, 0;\n"
    "add.s64 db, %60, %61 + 6;\n"
    "wgmma.mma_async.sync.aligned.m64n88k16.f32.bf16.bf16 {%0, %1, %2, %3, %4, %5, %6, %7, %8, %9, %10, %11, %12, %13, %14, %15, %16, %17, %18, %19, %20, %21, %22, %23, %24, %25, %26, %27, %28, %29, %30, %31, %32, %33, %34, %35, %36, %37, %38, %39, %40, %41, %42, %43}, {%56, %57, %58, %59}, db, 1, 1, 1, 0;\n"
    "wgmma.commit_group.sync.aligned;\n}\n"
    : "+f"(d[0]), "+f"(d[1]), "+f"(d[2]), "+f"(d[3]), "+f"(d[4]), "+f"(d[5]), "+f"(d[6]), "+f"(d[7]), "+f"(d[8]), "+f"(d[9]), "+f"(d[10]), "+f"(d[11]), "+f"(d[12]), "+f"(d[13]), "+f"(d[14]), "+f"(d[15]), "+f"(d[16]), "+f"(d[17]), "+f"(d[18]), "+f"(d[19]), "+f"(d[20]), "+f"(d[21]), "+f"(d[22]), "+f"(d[23]), "+f"(d[24]), "+f"(d[25]), "+f"(d[26]), "+f"(d[27]), "+f"(d[28]), "+f"(d[29]), "+f"(d[30]), "+f"(d[31]), "+f"(d[32]), "+f"(d[33]), "+f"(d[34]), "+f"(d[35]), "+f"(d[36]), "+f"(d[37]), "+f"(d[38]), "+f"(d[39]), "+f"(d[40]), "+f"(d[41]), "+f"(d[42]), "+f"(d[43])
    : "r"(a[0]), "r"(a[1]), "r"(a[2]), "r"(a[3]), "r"(a[4]), "r"(a[5]), "r"(a[6]), "r"(a[7]), "r"(a[8]), "r"(a[9]), "r"(a[10]), "r"(a[11]), "r"(a[12]), "r"(a[13]), "r"(a[14]), "r"(a[15]), "l"(db), "n"(D)
    : "memory");
}
template<int D> __device__ __forceinline__ void bias_out(float (&d)[4], const uint32_t (&a)[16], uint64_t db) {
  asm volatile("{\n.reg .b64 db;\n"
    "add.s64 db, %20, %21 + 0;\n"
    "wgmma.mma_async.sync.aligned.m64n8k16.f32.bf16.bf16 {%0, %1, %2, %3}, {%4, %5, %6, %7}, db, 0, 1, 1, 0;\n"
    "add.s64 db, %20, %21 + 2;\n"
    "wgmma.mma_async.sync.aligned.m64n8k16.f32.bf16.bf16 {%0, %1, %2, %3}, {%8, %9, %10, %11}, db, 1, 1, 1, 0;\n"
    "add.s64 db, %20, %21 + 4;\n"
    "wgmma.mma_async.sync.aligned.m64n8k16.f32.bf16.bf16 {%0, %1, %2, %3}, {%12, %13, %14, %15}, db, 1, 1, 1, 0;\n"
    "add.s64 db, %20, %21 + 6;\n"
    "wgmma.mma_async.sync.aligned.m64n8k16.f32.bf16.bf16 {%0, %1, %2, %3}, {%16, %17, %18, %19}, db, 1, 1, 1, 0;\n"
    "wgmma.commit_group.sync.aligned;\n}\n"
    : "=f"(d[0]), "=f"(d[1]), "=f"(d[2]), "=f"(d[3])
    : "r"(a[0]), "r"(a[1]), "r"(a[2]), "r"(a[3]), "r"(a[4]), "r"(a[5]), "r"(a[6]), "r"(a[7]), "r"(a[8]), "r"(a[9]), "r"(a[10]), "r"(a[11]), "r"(a[12]), "r"(a[13]), "r"(a[14]), "r"(a[15]), "l"(db), "n"(D)
    : "memory");
}
template<int D> __device__ __forceinline__ void gemm2_first(float (&d)[16], const uint32_t (&a)[12], uint64_t db, uint32_t meta) {
  asm volatile("{\n.reg .b64 db;\n"
    "wgmma.fence.sync.aligned;\n"
    "add.s64 db, %28, %29 + 0;\n"
    "wgmma.mma_async.sp.sync.aligned.m64n32k32.f32.bf16.bf16 {%0, %1, %2, %3, %4, %5, %6, %7, %8, %9, %10, %11, %12, %13, %14, %15}, {%16, %17, %18, %19}, db, %30, 0, 0, 1, 1, 1;\n"
    "add.s64 db, %28, %29 + 128;\n"
    "wgmma.mma_async.sp.sync.aligned.m64n32k32.f32.bf16.bf16 {%0, %1, %2, %3, %4, %5, %6, %7, %8, %9, %10, %11, %12, %13, %14, %15}, {%20, %21, %22, %23}, db, %30, 0, 1, 1, 1, 1;\n"
    "add.s64 db, %28, %29 + 256;\n"
    "wgmma.mma_async.sp.sync.aligned.m64n32k32.f32.bf16.bf16 {%0, %1, %2, %3, %4, %5, %6, %7, %8, %9, %10, %11, %12, %13, %14, %15}, {%24, %25, %26, %27}, db, %30, 0, 1, 1, 1, 1;\n"
    "wgmma.commit_group.sync.aligned;\n}\n"
    : "=f"(d[0]), "=f"(d[1]), "=f"(d[2]), "=f"(d[3]), "=f"(d[4]), "=f"(d[5]), "=f"(d[6]), "=f"(d[7]), "=f"(d[8]), "=f"(d[9]), "=f"(d[10]), "=f"(d[11]), "=f"(d[12]), "=f"(d[13]), "=f"(d[14]), "=f"(d[15])
    : "r"(a[0]), "r"(a[1]), "r"(a[2]), "r"(a[3]), "r"(a[4]), "r"(a[5]), "r"(a[6]), "r"(a[7]), "r"(a[8]), "r"(a[9]), "r"(a[10]), "r"(a[11]), "l"(db), "n"(D), "r"(meta)
    : "memory");
}
template<int D> __device__ __forceinline__ void gemm2_first(float (&d)[16], const uint32_t (&a)[16], uint64_t db, uint32_t meta) {
  asm volatile("{\n.reg .b64 db;\n"
    "wgmma.fence.sync.aligned;\n"
    "add.s64 db, %32, %33 + 0;\n"
    "wgmma.mma_async.sp.sync.aligned.m64n32k32.f32.bf16.bf16 {%0, %1, %2, %3, %4, %5, %6, %7, %8, %9, %10, %11, %12, %13, %14, %15}, {%16, %17, %18, %19}, db, %34, 0, 0, 1, 1, 1;\n"
    "add.s64 db, %32, %33 + 128;\n"
    "wgmma.mma_async.sp.sync.aligned.m64n32k32.f32.bf16.bf16 {%0, %1, %2, %3, %4, %5, %6, %7, %8, %9, %10, %11, %12, %13, %14, %15}, {%20, %21, %22, %23}, db, %34, 0, 1, 1, 1, 1;\n"
    "add.s64 db, %32, %33 + 256;\n"
    "wgmma.mma_async.sp.sync.aligned.m64n32k32.f32.bf16.bf16 {%0, %1, %2, %3, %4, %5, %6, %7, %8, %9, %10, %11, %12, %13, %14, %15}, {%24, %25, %26, %27}, db, %34, 0, 1, 1, 1, 1;\n"
    "add.s64 db, %32, %33 + 384;\n"
    "wgmma.mma_async.sp.sync.aligned.m64n32k32.f32.bf16.bf16 {%0, %1, %2, %3, %4, %5, %6, %7, %8, %9, %10, %11, %12, %13, %14, %15}, {%28, %29, %30, %31}, db, %34, 0, 1, 1, 1, 1;\n"
    "wgmma.commit_group.sync.aligned;\n}\n"
    : "=f"(d[0]), "=f"(d[1]), "=f"(d[2]), "=f"(d[3]), "=f"(d[4]), "=f"(d[5]), "=f"(d[6]), "=f"(d[7]), "=f"(d[8]), "=f"(d[9]), "=f"(d[10]), "=f"(d[11]), "=f"(d[12]), "=f"(d[13]), "=f"(d[14]), "=f"(d[15])
    : "r"(a[0]), "r"(a[1]), "r"(a[2]), "r"(a[3]), "r"(a[4]), "r"(a[5]), "r"(a[6]), "r"(a[7]), "r"(a[8]), "r"(a[9]), "r"(a[10]), "r"(a[11]), "r"(a[12]), "r"(a[13]), "r"(a[14]), "r"(a[15]), "l"(db), "n"(D), "r"(meta)
    : "memory");
}
template<int D> __device__ __forceinline__ void gemm2_first(float (&d)[16], const uint32_t (&a)[20], uint64_t db, uint32_t meta) {
  asm volatile("{\n.reg .b64 db;\n"
    "wgmma.fence.sync.aligned;\n"
    "add.s64 db, %36, %37 + 0;\n"
    "wgmma.mma_async.sp.sync.aligned.m64n32k32.f32.bf16.bf16 {%0, %1, %2, %3, %4, %5, %6, %7, %8, %9, %10, %11, %12, %13, %14, %15}, {%16, %17, %18, %19}, db, %38, 0, 0, 1, 1, 1;\n"
    "add.s64 db, %36, %37 + 128;\n"
    "wgmma.mma_async.sp.sync.aligned.m64n32k32.f32.bf16.bf16 {%0, %1, %2, %3, %4, %5, %6, %7, %8, %9, %10, %11, %12, %13, %14, %15}, {%20, %21, %22, %23}, db, %38, 0, 1, 1, 1, 1;\n"
    "add.s64 db, %36, %37 + 256;\n"
    "wgmma.mma_async.sp.sync.aligned.m64n32k32.f32.bf16.bf16 {%0, %1, %2, %3, %4, %5, %6, %7, %8, %9, %10, %11, %12, %13, %14, %15}, {%24, %25, %26, %27}, db, %38, 0, 1, 1, 1, 1;\n"
    "add.s64 db, %36, %37 + 384;\n"
    "wgmma.mma_async.sp.sync.aligned.m64n32k32.f32.bf16.bf16 {%0, %1, %2, %3, %4, %5, %6, %7, %8, %9, %10, %11, %12, %13, %14, %15}, {%28, %29, %30, %31}, db, %38, 0, 1, 1, 1, 1;\n"
    "add.s64 db, %36, %37 + 512;\n"
    "wgmma.mma_async.sp.sync.aligned.m64n32k32.f32.bf16.bf16 {%0, %1, %2, %3, %4, %5, %6, %7, %8, %9, %10, %11, %12, %13, %14, %15}, {%32, %33, %34, %35}, db, %38, 0, 1, 1, 1, 1;\n"
    "wgmma.commit_group.sync.aligned;\n}\n"
    : "=f"(d[0]), "=f"(d[1]), "=f"(d[2]), "=f"(d[3]), "=f"(d[4]), "=f"(d[5]), "=f"(d[6]), "=f"(d[7]), "=f"(d[8]), "=f"(d[9]), "=f"(d[10]), "=f"(d[11]), "=f"(d[12]), "=f"(d[13]), "=f"(d[14]), "=f"(d[15])
    : "r"(a[0]), "r"(a[1]), "r"(a[2]), "r"(a[3]), "r"(a[4]), "r"(a[5]), "r"(a[6]), "r"(a[7]), "r"(a[8]), "r"(a[9]), "r"(a[10]), "r"(a[11]), "r"(a[12]), "r"(a[13]), "r"(a[14]), "r"(a[15]), "r"(a[16]), "r"(a[17]), "r"(a[18]), "r"(a[19]), "l"(db), "n"(D), "r"(meta)
    : "memory");
}
template<int D> __device__ __forceinline__ void gemm2_more(float (&d)[16], const uint32_t (&a)[4], uint64_t db, uint32_t meta) {
  asm volatile("{\n.reg .b64 db;\n"
    "wgmma.fence.sync.aligned;\n"
    "add.s64 db, %20, %21 + 0;\n"
    "wgmma.mma_async.sp.sync.aligned.m64n32k32.f32.bf16.bf16 {%0, %1, %2, %3, %4, %5, %6, %7, %8, %9, %10, %11, %12, %13, %14, %15}, {%16, %17, %18, %19}, db, %22, 0, 1, 1, 1, 1;\n"
    "wgmma.commit_group.sync.aligned;\n}\n"
    : "+f"(d[0]), "+f"(d[1]), "+f"(d[2]), "+f"(d[3]), "+f"(d[4]), "+f"(d[5]), "+f"(d[6]), "+f"(d[7]), "+f"(d[8]), "+f"(d[9]), "+f"(d[10]), "+f"(d[11]), "+f"(d[12]), "+f"(d[13]), "+f"(d[14]), "+f"(d[15])
    : "r"(a[0]), "r"(a[1]), "r"(a[2]), "r"(a[3]), "l"(db), "n"(D), "r"(meta)
    : "memory");
}
template<int D> __device__ __forceinline__ void gemm2_more(float (&d)[16], const uint32_t (&a)[8], uint64_t db, uint32_t meta) {
  asm volatile("{\n.reg .b64 db;\n"
    "wgmma.fence.sync.aligned;\n"
    "add.s64 db, %24, %25 + 0;\n"
    "wgmma.mma_async.sp.sync.aligned.m64n32k32.f32.bf16.bf16 {%0, %1, %2, %3, %4, %5, %6, %7, %8, %9, %10, %11, %12, %13, %14, %15}, {%16, %17, %18, %19}, db, %26, 0, 1, 1, 1, 1;\n"
    "add.s64 db, %24, %25 + 128;\n"
    "wgmma.mma_async.sp.sync.aligned.m64n32k32.f32.bf16.bf16 {%0, %1, %2, %3, %4, %5, %6, %7, %8, %9, %10, %11, %12, %13, %14, %15}, {%20, %21, %22, %23}, db, %26, 0, 1, 1, 1, 1;\n"
    "wgmma.commit_group.sync.aligned;\n}\n"
    : "+f"(d[0]), "+f"(d[1]), "+f"(d[2]), "+f"(d[3]), "+f"(d[4]), "+f"(d[5]), "+f"(d[6]), "+f"(d[7]), "+f"(d[8]), "+f"(d[9]), "+f"(d[10]), "+f"(d[11]), "+f"(d[12]), "+f"(d[13]), "+f"(d[14]), "+f"(d[15])
    : "r"(a[0]), "r"(a[1]), "r"(a[2]), "r"(a[3]), "r"(a[4]), "r"(a[5]), "r"(a[6]), "r"(a[7]), "l"(db), "n"(D), "r"(meta)
    : "memory");
}
template<int D> __device__ __forceinline__ void gemm2_more(float (&d)[16], const uint32_t (&a)[12], uint64_t db, uint32_t meta) {
  asm volatile("{\n.reg .b64 db;\n"
    "wgmma.fence.sync.aligned;\n"
    "add.s64 db, %28, %29 + 0;\n"
    "wgmma.mma_async.sp.sync.aligned.m64n32k32.f32.bf16.bf16 {%0, %1, %2, %3, %4, %5, %6, %7, %8, %9, %10, %11, %12, %13, %14, %15}, {%16, %17, %18, %19}, db, %30, 0, 1, 1, 1, 1;\n"
    "add.s64 db, %28, %29 + 128;\n"
    "wgmma.mma_async.sp.sync.aligned.m64n32k32.f32.bf16.bf16 {%0, %1, %2, %3, %4, %5, %6, %7, %8, %9, %10, %11, %12, %13, %14, %15}, {%20, %21, %22, %23}, db, %30, 0, 1, 1, 1, 1;\n"
    "add.s64 db, %28, %29 + 256;\n"
    "wgmma.mma_async.sp.sync.aligned.m64n32k32.f32.bf16.bf16 {%0, %1, %2, %3, %4, %5, %6, %7, %8, %9, %10, %11, %12, %13, %14, %15}, {%24, %25, %26, %27}, db, %30, 0, 1, 1, 1, 1;\n"
    "wgmma.commit_group.sync.aligned;\n}\n"
    : "+f"(d[0]), "+f"(d[1]), "+f"(d[2]), "+f"(d[3]), "+f"(d[4]), "+f"(d[5]), "+f"(d[6]), "+f"(d[7]), "+f"(d[8]), "+f"(d[9]), "+f"(d[10]), "+f"(d[11]), "+f"(d[12]), "+f"(d[13]), "+f"(d[14]), "+f"(d[15])
    : "r"(a[0]), "r"(a[1]), "r"(a[2]), "r"(a[3]), "r"(a[4]), "r"(a[5]), "r"(a[6]), "r"(a[7]), "r"(a[8]), "r"(a[9]), "r"(a[10]), "r"(a[11]), "l"(db), "n"(D), "r"(meta)
    : "memory");
}
template<int D> __device__ __forceinline__ void gemm2_more(float (&d)[16], const uint32_t (&a)[16], uint64_t db, uint32_t meta) {
  asm volatile("{\n.reg .b64 db;\n"
    "wgmma.fence.sync.aligned;\n"
    "add.s64 db, %32, %33 + 0;\n"
    "wgmma.mma_async.sp.sync.aligned.m64n32k32.f32.bf16.bf16 {%0, %1, %2, %3, %4, %5, %6, %7, %8, %9, %10, %11, %12, %13, %14, %15}, {%16, %17, %18, %19}, db, %34, 0, 1, 1, 1, 1;\n"
    "add.s64 db, %32, %33 + 128;\n"
    "wgmma.mma_async.sp.sync.aligned.m64n32k32.f32.bf16.bf16 {%0, %1, %2, %3, %4, %5, %6, %7, %8, %9, %10, %11, %12, %13, %14, %15}, {%20, %21, %22, %23}, db, %34, 0, 1, 1, 1, 1;\n"
    "add.s64 db, %32, %33 + 256;\n"
    "wgmma.mma_async.sp.sync.aligned.m64n32k32.f32.bf16.bf16 {%0, %1, %2, %3, %4, %5, %6, %7, %8, %9, %10, %11, %12, %13, %14, %15}, {%24, %25, %26, %27}, db, %34, 0, 1, 1, 1, 1;\n"
    "add.s64 db, %32, %33 + 384;\n"
    "wgmma.mma_async.sp.sync.aligned.m64n32k32.f32.bf16.bf16 {%0, %1, %2, %3, %4, %5, %6, %7, %8, %9, %10, %11, %12, %13, %14, %15}, {%28, %29, %30, %31}, db, %34, 0, 1, 1, 1, 1;\n"
    "wgmma.commit_group.sync.aligned;\n}\n"
    : "+f"(d[0]), "+f"(d[1]), "+f"(d[2]), "+f"(d[3]), "+f"(d[4]), "+f"(d[5]), "+f"(d[6]), "+f"(d[7]), "+f"(d[8]), "+f"(d[9]), "+f"(d[10]), "+f"(d[11]), "+f"(d[12]), "+f"(d[13]), "+f"(d[14]), "+f"(d[15])
    : "r"(a[0]), "r"(a[1]), "r"(a[2]), "r"(a[3]), "r"(a[4]), "r"(a[5]), "r"(a[6]), "r"(a[7]), "r"(a[8]), "r"(a[9]), "r"(a[10]), "r"(a[11]), "r"(a[12]), "r"(a[13]), "r"(a[14]), "r"(a[15]), "l"(db), "n"(D), "r"(meta)
    : "memory");
}
template<int N> __device__ __forceinline__ void mma_wait(float (&d)[4]) {
  asm volatile("wgmma.wait_group.sync.aligned %4;"
    : "+f"(d[0]), "+f"(d[1]), "+f"(d[2]), "+f"(d[3])
    : "n"(N) : "memory");
}
template<int N> __device__ __forceinline__ void mma_wait(float (&d)[16]) {
  asm volatile("wgmma.wait_group.sync.aligned %16;"
    : "+f"(d[0]), "+f"(d[1]), "+f"(d[2]), "+f"(d[3]), "+f"(d[4]), "+f"(d[5]), "+f"(d[6]), "+f"(d[7]), "+f"(d[8]), "+f"(d[9]), "+f"(d[10]), "+f"(d[11]), "+f"(d[12]), "+f"(d[13]), "+f"(d[14]), "+f"(d[15])
    : "n"(N) : "memory");
}
template<int N> __device__ __forceinline__ void mma_wait(float (&d)[20]) {
  asm volatile("wgmma.wait_group.sync.aligned %20;"
    : "+f"(d[0]), "+f"(d[1]), "+f"(d[2]), "+f"(d[3]), "+f"(d[4]), "+f"(d[5]), "+f"(d[6]), "+f"(d[7]), "+f"(d[8]), "+f"(d[9]), "+f"(d[10]), "+f"(d[11]), "+f"(d[12]), "+f"(d[13]), "+f"(d[14]), "+f"(d[15]), "+f"(d[16]), "+f"(d[17]), "+f"(d[18]), "+f"(d[19])
    : "n"(N) : "memory");
}
template<int N> __device__ __forceinline__ void mma_wait(float (&d)[28]) {
  asm volatile("wgmma.wait_group.sync.aligned %28;"
    : "+f"(d[0]), "+f"(d[1]), "+f"(d[2]), "+f"(d[3]), "+f"(d[4]), "+f"(d[5]), "+f"(d[6]), "+f"(d[7]), "+f"(d[8]), "+f"(d[9]), "+f"(d[10]), "+f"(d[11]), "+f"(d[12]), "+f"(d[13]), "+f"(d[14]), "+f"(d[15]), "+f"(d[16]), "+f"(d[17]), "+f"(d[18]), "+f"(d[19]), "+f"(d[20]), "+f"(d[21]), "+f"(d[22]), "+f"(d[23]), "+f"(d[24]), "+f"(d[25]), "+f"(d[26]), "+f"(d[27])
    : "n"(N) : "memory");
}
template<int N> __device__ __forceinline__ void mma_wait(float (&d)[32]) {
  asm volatile("wgmma.wait_group.sync.aligned %32;"
    : "+f"(d[0]), "+f"(d[1]), "+f"(d[2]), "+f"(d[3]), "+f"(d[4]), "+f"(d[5]), "+f"(d[6]), "+f"(d[7]), "+f"(d[8]), "+f"(d[9]), "+f"(d[10]), "+f"(d[11]), "+f"(d[12]), "+f"(d[13]), "+f"(d[14]), "+f"(d[15]), "+f"(d[16]), "+f"(d[17]), "+f"(d[18]), "+f"(d[19]), "+f"(d[20]), "+f"(d[21]), "+f"(d[22]), "+f"(d[23]), "+f"(d[24]), "+f"(d[25]), "+f"(d[26]), "+f"(d[27]), "+f"(d[28]), "+f"(d[29]), "+f"(d[30]), "+f"(d[31])
    : "n"(N) : "memory");
}
template<int N> __device__ __forceinline__ void mma_wait(float (&d)[36]) {
  asm volatile("wgmma.wait_group.sync.aligned %36;"
    : "+f"(d[0]), "+f"(d[1]), "+f"(d[2]), "+f"(d[3]), "+f"(d[4]), "+f"(d[5]), "+f"(d[6]), "+f"(d[7]), "+f"(d[8]), "+f"(d[9]), "+f"(d[10]), "+f"(d[11]), "+f"(d[12]), "+f"(d[13]), "+f"(d[14]), "+f"(d[15]), "+f"(d[16]), "+f"(d[17]), "+f"(d[18]), "+f"(d[19]), "+f"(d[20]), "+f"(d[21]), "+f"(d[22]), "+f"(d[23]), "+f"(d[24]), "+f"(d[25]), "+f"(d[26]), "+f"(d[27]), "+f"(d[28]), "+f"(d[29]), "+f"(d[30]), "+f"(d[31]), "+f"(d[32]), "+f"(d[33]), "+f"(d[34]), "+f"(d[35])
    : "n"(N) : "memory");
}
template<int N> __device__ __forceinline__ void mma_wait(float (&d)[40]) {
  asm volatile("wgmma.wait_group.sync.aligned %40;"
    : "+f"(d[0]), "+f"(d[1]), "+f"(d[2]), "+f"(d[3]), "+f"(d[4]), "+f"(d[5]), "+f"(d[6]), "+f"(d[7]), "+f"(d[8]), "+f"(d[9]), "+f"(d[10]), "+f"(d[11]), "+f"(d[12]), "+f"(d[13]), "+f"(d[14]), "+f"(d[15]), "+f"(d[16]), "+f"(d[17]), "+f"(d[18]), "+f"(d[19]), "+f"(d[20]), "+f"(d[21]), "+f"(d[22]), "+f"(d[23]), "+f"(d[24]), "+f"(d[25]), "+f"(d[26]), "+f"(d[27]), "+f"(d[28]), "+f"(d[29]), "+f"(d[30]), "+f"(d[31]), "+f"(d[32]), "+f"(d[33]), "+f"(d[34]), "+f"(d[35]), "+f"(d[36]), "+f"(d[37]), "+f"(d[38]), "+f"(d[39])
    : "n"(N) : "memory");
}
template<int N> __device__ __forceinline__ void mma_wait(float (&d)[44]) {
  asm volatile("wgmma.wait_group.sync.aligned %44;"
    : "+f"(d[0]), "+f"(d[1]), "+f"(d[2]), "+f"(d[3]), "+f"(d[4]), "+f"(d[5]), "+f"(d[6]), "+f"(d[7]), "+f"(d[8]), "+f"(d[9]), "+f"(d[10]), "+f"(d[11]), "+f"(d[12]), "+f"(d[13]), "+f"(d[14]), "+f"(d[15]), "+f"(d[16]), "+f"(d[17]), "+f"(d[18]), "+f"(d[19]), "+f"(d[20]), "+f"(d[21]), "+f"(d[22]), "+f"(d[23]), "+f"(d[24]), "+f"(d[25]), "+f"(d[26]), "+f"(d[27]), "+f"(d[28]), "+f"(d[29]), "+f"(d[30]), "+f"(d[31]), "+f"(d[32]), "+f"(d[33]), "+f"(d[34]), "+f"(d[35]), "+f"(d[36]), "+f"(d[37]), "+f"(d[38]), "+f"(d[39]), "+f"(d[40]), "+f"(d[41]), "+f"(d[42]), "+f"(d[43])
    : "n"(N) : "memory");
}
__device__ __forceinline__ void mma_fence() { asm volatile("wgmma.fence.sync.aligned;" ::: "memory"); }

__device__ __forceinline__ uint32_t smem_u32(const void* p) { return (uint32_t)__cvta_generic_to_shared(p); }

__device__ __forceinline__ void mbar_init(uint32_t bar, uint32_t cnt) {
  asm volatile("mbarrier.init.shared::cta.b64 [%0], %1;" :: "r"(bar), "r"(cnt) : "memory");
}
__device__ __forceinline__ void mbar_arrive(uint32_t bar) {
  asm volatile("mbarrier.arrive.shared::cta.b64 _, [%0];" :: "r"(bar) : "memory");
}
__device__ __forceinline__ void mbar_wait(uint32_t bar, uint32_t parity) {
  asm volatile("{\n.reg .pred p;\n.reg .u32 n;\n"
               "mov.u32 n, 0;\n"
               "WAIT_LOOP:\n"
               "mbarrier.try_wait.parity.shared::cta.b64 p, [%0], %1;\n"
               "@p bra.uni WAIT_DONE;\n"
               "add.u32 n, n, 1;\n"
               "setp.lt.u32 p, n, 0x1000000;\n"
               "@p bra.uni WAIT_LOOP;\n"
               "trap;\n"
               "WAIT_DONE:\n}\n"
               :: "r"(bar), "r"(parity) : "memory");
}
__device__ __forceinline__ void mbar_wait_unless(uint32_t ok, uint32_t bar, uint32_t parity) {
  asm volatile("{\n.reg .pred p;\n.reg .u32 n;\n"
               "setp.ne.u32 p, %2, 0;\n"
               "@p bra.uni WAIT_DONE;\n"
               "mov.u32 n, 0;\n"
               "WAIT_LOOP:\n"
               "mbarrier.try_wait.parity.shared::cta.b64 p, [%0], %1;\n"
               "@p bra.uni WAIT_DONE;\n"
               "add.u32 n, n, 1;\n"
               "setp.lt.u32 p, n, 0x1000000;\n"
               "@p bra.uni WAIT_LOOP;\n"
               "trap;\n"
               "WAIT_DONE:\n}\n"
               :: "r"(bar), "r"(parity), "r"(ok) : "memory");
}
__device__ __forceinline__ uint32_t mbar_test(uint32_t bar, uint32_t parity) {
  uint32_t ok;
  asm volatile("{\n.reg .pred p;\nmbarrier.test_wait.parity.shared::cta.b64 p, [%1], %2;\nselp.u32 %0, 1, 0, p;\n}\n"
               : "=r"(ok) : "r"(bar), "r"(parity) : "memory");
  return ok;
}
__device__ __forceinline__ void cp_async16(uint32_t dst, const void* src) {
  asm volatile("cp.async.cg.shared.global [%0], [%1], 16;" :: "r"(dst), "l"(src) : "memory");
}
#define DIN_ADDR4                                                                        \
  "mov.b64 {x, y}, %0;\ndp4a.u32.u32 x, %8, 0x80, %11;\nmov.b64 %0, {x, y};\n"           \
  "mov.b64 {x, y}, %1;\ndp4a.u32.u32 x, %8, 0x8000, %11;\nmov.b64 %1, {x, y};\n"         \
  "mov.b64 {x, y}, %2;\ndp4a.u32.u32 x, %8, 0x800000, %11;\nmov.b64 %2, {x, y};\n"       \
  "mov.b64 {x, y}, %3;\ndp4a.u32.u32 x, %8, 0x80000000, %11;\nmov.b64 %3, {x, y};\n"
template<int T>
__device__ __forceinline__ void cp_group(const uint32_t (&dst)[4], uint64_t (&a)[4], uint32_t rows4, uint32_t base, uint64_t pol) {
  asm volatile("{\n.reg .u32 x, y;\n" DIN_ADDR4
               "cp.async.cg.shared.global.L2::cache_hint [%4 + %10], [%0], 16, %9;\n"
               "cp.async.cg.shared.global.L2::cache_hint [%5 + %10], [%1], 16, %9;\n"
               "cp.async.cg.shared.global.L2::cache_hint [%6 + %10], [%2], 16, %9;\n"
               "cp.async.cg.shared.global.L2::cache_hint [%7 + %10], [%3], 16, %9;\n}\n"
               : "+l"(a[0]), "+l"(a[1]), "+l"(a[2]), "+l"(a[3])
               : "r"(dst[0]), "r"(dst[1]), "r"(dst[2]), "r"(dst[3]), "r"(rows4), "l"(pol), "n"(T * 2048), "r"(base) : "memory");
}
template<int T>
__device__ __forceinline__ void cp_group_z(const uint32_t (&dst)[4], uint64_t (&a)[4], uint32_t rows4, uint32_t base, int left, uint64_t pol) {
  asm volatile("{\n.reg .u32 x, y;\n.reg .pred p0, p1, p2, p3;\n" DIN_ADDR4
               "setp.le.s32 p0, %12, %13;\nsetp.le.s32 p1, %12, %13 + 1;\nsetp.le.s32 p2, %12, %13 + 2;\nsetp.le.s32 p3, %12, %13 + 3;\n"
               "cp.async.cg.shared.global.L2::cache_hint [%4 + %10], [%0], 16, p0, %9;\n"
               "cp.async.cg.shared.global.L2::cache_hint [%5 + %10], [%1], 16, p1, %9;\n"
               "cp.async.cg.shared.global.L2::cache_hint [%6 + %10], [%2], 16, p2, %9;\n"
               "cp.async.cg.shared.global.L2::cache_hint [%7 + %10], [%3], 16, p3, %9;\n}\n"
               : "+l"(a[0]), "+l"(a[1]), "+l"(a[2]), "+l"(a[3])
               : "r"(dst[0]), "r"(dst[1]), "r"(dst[2]), "r"(dst[3]), "r"(rows4), "l"(pol), "n"(T * 2048), "r"(base),
                 "r"(left), "n"(T * 16) : "memory");
}
__device__ __forceinline__ void wait_for(uint32_t t, uint32_t most) {
  asm volatile("{\n.reg .u32 c;\n.reg .pred p;\n"
               "SPIN:\n"
               "mov.u32 c, %%globaltimer_lo;\n"
               "sub.u32 c, c, %0;\n"
               "setp.gt.u32 p, c, %1;\n"
               "@p bra.uni SPIN;\n}\n" :: "r"(t), "r"(~most) : "memory");
}
template<int T, int SH>
__device__ __forceinline__ void cp_group_m(const uint32_t (&dst)[4], uint64_t (&a)[4], uint32_t rows4, uint32_t base, uint32_t have, uint32_t go, uint64_t pol) {
  asm volatile("{\n.reg .u32 x, y;\n.reg .pred p0, p1, p2, p3, g;\n" DIN_ADDR4
               "setp.ne.u32 g, %14, 0;\n"
               "and.b32 x, %12, 1 << %13;\nsetp.eq.u32 p0, x, 0;\nand.b32 x, %12, 2 << %13;\nsetp.eq.u32 p1, x, 0;\n"
               "and.b32 x, %12, 4 << %13;\nsetp.eq.u32 p2, x, 0;\nand.b32 x, %12, 8 << %13;\nsetp.eq.u32 p3, x, 0;\n"
               "@g cp.async.cg.shared.global.L2::cache_hint [%4 + %10], [%0], 16, p0, %9;\n"
               "@g cp.async.cg.shared.global.L2::cache_hint [%5 + %10], [%1], 16, p1, %9;\n"
               "@g cp.async.cg.shared.global.L2::cache_hint [%6 + %10], [%2], 16, p2, %9;\n"
               "@g cp.async.cg.shared.global.L2::cache_hint [%7 + %10], [%3], 16, p3, %9;\n}\n"
               : "+l"(a[0]), "+l"(a[1]), "+l"(a[2]), "+l"(a[3])
               : "r"(dst[0]), "r"(dst[1]), "r"(dst[2]), "r"(dst[3]), "r"(rows4), "l"(pol), "n"(T * 2048), "r"(base),
                 "r"(have), "n"(SH), "r"(go) : "memory");
}
__device__ __forceinline__ uint32_t prmt(uint32_t a, uint32_t b, uint32_t sel) {
  uint32_t d;
  asm("prmt.b32 %0, %1, %2, %3;" : "=r"(d) : "r"(a), "r"(b), "r"(sel));
  return d;
}
__device__ __forceinline__ uint32_t ballot_bit(uint32_t x, uint32_t bit) {
  uint32_t d;
  asm volatile("{\n.reg .pred p;\n.reg .u32 t;\nand.b32 t, %1, %2;\nsetp.ne.u32 p, t, 0;\nvote.sync.ballot.b32 %0, p, 0xffffffff;\n}\n"
               : "=r"(d) : "r"(x), "r"(bit));
  return d;
}
__device__ __forceinline__ uint4 load_mask(const void* mask, uint32_t b, uint32_t i) {
  uint4 m;
  asm volatile("ld.global.nc.L1::no_allocate.v4.u32 {%0,%1,%2,%3}, [%4];"
               : "=r"(m.x), "=r"(m.y), "=r"(m.z), "=r"(m.w) : "l"(reinterpret_cast<const uint4*>(mask) + (b * 25u + i)));
  return m;
}
__device__ __forceinline__ uint32_t nonzero_as_one(uint32_t x) {
  uint32_t d;
  asm("set.neu.bf16x2.bf16x2 %0, %1, %2;" : "=r"(d) : "r"(x), "r"(0u));
  return d;
}
__device__ __forceinline__ void cp_async_arrive_noinc(uint32_t bar) {
  asm volatile("cp.async.mbarrier.arrive.noinc.shared::cta.b64 [%0];" :: "r"(bar) : "memory");
}
__device__ __forceinline__ void ldsm_x4(uint32_t addr, uint32_t& r0, uint32_t& r1, uint32_t& r2, uint32_t& r3) {
  asm volatile("ldmatrix.sync.aligned.m8n8.x4.shared.b16 {%0,%1,%2,%3}, [%4];"
               : "=r"(r0), "=r"(r1), "=r"(r2), "=r"(r3) : "r"(addr) : "memory");
}
__device__ __forceinline__ void ldsm_x4_t(uint32_t addr, uint32_t& r0, uint32_t& r1, uint32_t& r2, uint32_t& r3) {
  asm volatile("ldmatrix.sync.aligned.m8n8.x4.trans.shared.b16 {%0,%1,%2,%3}, [%4];"
               : "=r"(r0), "=r"(r1), "=r"(r2), "=r"(r3) : "r"(addr) : "memory");
}
__device__ __forceinline__ void stsm_x4(uint32_t addr, uint32_t r0, uint32_t r1, uint32_t r2, uint32_t r3) {
  asm volatile("stmatrix.sync.aligned.m8n8.x4.shared.b16 [%0], {%1,%2,%3,%4};"
               :: "r"(addr), "r"(r0), "r"(r1), "r"(r2), "r"(r3) : "memory");
}
__device__ __forceinline__ void stsm_x2(uint32_t addr, uint32_t r0, uint32_t r1) {
  asm volatile("stmatrix.sync.aligned.m8n8.x2.shared.b16 [%0], {%1,%2};"
               :: "r"(addr), "r"(r0), "r"(r1) : "memory");
}
__device__ __forceinline__ void mma_bf16(float (&c)[4], const uint32_t (&a)[4], uint32_t b) {
  asm("mma.sync.aligned.m16n8k16.row.col.f32.bf16.bf16.f32 {%0,%1,%2,%3}, {%4,%5,%6,%7}, {%8,%8}, {%0,%1,%2,%3};"
      : "+f"(c[0]), "+f"(c[1]), "+f"(c[2]), "+f"(c[3]) : "r"(a[0]), "r"(a[1]), "r"(a[2]), "r"(a[3]), "r"(b));
}
__device__ __forceinline__ uint32_t hfma2_bf16(uint32_t a, uint32_t b, uint32_t c) {
  uint32_t d;
  asm volatile("fma.rn.bf16x2 %0, %1, %2, %3;" : "=r"(d) : "r"(a), "r"(b), "r"(c));
  return d;
}
__device__ __forceinline__ uint32_t pack_bf16(float lo, float hi) {
  uint32_t d;
  asm("cvt.rn.bf16x2.f32 %0, %1, %2;" : "=r"(d) : "f"(hi), "f"(lo));
  return d;
}
__device__ __forceinline__ uint32_t lds32(uint32_t a) {
  uint32_t v; asm volatile("ld.shared.u32 %0, [%1];" : "=r"(v) : "r"(a) : "memory"); return v;
}
__device__ __forceinline__ uint32_t lds16(uint32_t a) {
  uint32_t v; asm volatile("ld.shared.u16 %0, [%1];" : "=r"(v) : "r"(a) : "memory"); return v;
}
__device__ __forceinline__ void sts32(uint32_t a, uint32_t v) {
  asm volatile("st.shared.u32 [%0], %1;" :: "r"(a), "r"(v) : "memory");
}
__device__ __forceinline__ void sts16(uint32_t a, uint32_t v) {
  asm volatile("st.shared.u16 [%0], %1;" :: "r"(a), "h"((unsigned short)v) : "memory");
}
__device__ __forceinline__ void sts8(uint32_t a, uint32_t v) {
  asm volatile("st.shared.u8 [%0], %1;" :: "r"(a), "r"(v) : "memory");
}
constexpr uint32_t DESC_ROWS = 0x40000040u, DESC_HALVES = 0x80000020u;
__device__ __forceinline__ uint32_t desc_lo(uint32_t addr) { return ((addr & 0x3FFFF) >> 4) | (1u << 16); }

__device__ __forceinline__ uint4 lds128(uint32_t a) {
  uint4 v;
  asm volatile("ld.shared.v4.u32 {%0,%1,%2,%3}, [%4];" : "=r"(v.x), "=r"(v.y), "=r"(v.z), "=r"(v.w) : "r"(a) : "memory");
  return v;
}
__device__ __forceinline__ void sts128(uint32_t a, uint4 v) {
  asm volatile("st.shared.v4.u32 [%0], {%1,%2,%3,%4};" :: "r"(a), "r"(v.x), "r"(v.y), "r"(v.z), "r"(v.w) : "memory");
}
__device__ __forceinline__ void prefetch_l2(const void* p, uint32_t bytes) {
  asm volatile("cp.async.bulk.prefetch.L2.global [%0], %1;" :: "l"(p), "r"(bytes) : "memory");
}

__device__ __forceinline__ void prefetch_piece(const void* p, uint32_t bytes) {
  asm volatile("{\n.reg .u32 t, c;\n.reg .u64 a;\nmov.u32 t, %%tid.x;\nmov.u32 c, %%ctaid.x;\n"
               "mad.lo.u32 c, c, %2, t;\nmad.wide.u32 a, c, %1, %0;\nprefetch.global.L2 [a];\n}\n"
               :: "l"(p), "r"(bytes), "n"(NTHREADS) : "memory");
}

template<int ND>
__device__ __forceinline__ void tanh_range(float (&d)[ND], int i0, int i1) {
#pragma unroll
  for (int i = i0; i < i1; i++) asm volatile("tanh.approx.f32 %0, %0;" : "+f"(d[i ^ 2]));
}
template<int ND>
__device__ __forceinline__ uint32_t mix(const float (&d)[ND], int i, float w2a, float w2b, float c32) {
  uint32_t p;
  asm volatile("{\n.reg .f32 x, y;\nfma.rn.f32 x, %3, %6, %7;\nfma.rn.f32 y, %4, %6, %7;\n"
               "fma.rn.f32 x, %1, %5, x;\nfma.rn.f32 y, %2, %5, y;\ncvt.rn.bf16x2.f32 %0, y, x;\n}\n"
               : "=r"(p) : "f"(d[4 * i]), "f"(d[4 * i + 1]), "f"(d[4 * i + 2]), "f"(d[4 * i + 3]), "f"(w2a), "f"(w2b), "f"(c32));
  return p;
}
__device__ __forceinline__ uint32_t size_bit(int n) { return n > 120 ? H_16 : H_12 << (max(n - 89, 0) >> 3); }
template<int V> struct Int { static constexpr int value = V; };

__global__ void __launch_bounds__(NTHREADS, 1)
din_kernel(const __nv_bfloat16* __restrict__ mask, const __nv_bfloat16* __restrict__ target, int B, int grid,
           uint32_t pf_mask, uint32_t pf_tgt, const __nv_bfloat16* __restrict__ w1, const __nv_bfloat16* __restrict__ hist,
           const __nv_bfloat16* __restrict__ b1, const __nv_bfloat16* __restrict__ w2,
           const __nv_bfloat16* __restrict__ b2, __nv_bfloat16* __restrict__ out, unsigned int* counter, int pace,
           int slow_from, int pace_slow, int spread) {
  prefetch_piece(mask, pf_mask);
  asm volatile("{\n.reg .pred p;\n.reg .u32 c;\nmov.u32 c, %%clock;\nsetp.eq.u32 p, c, %0;\n@p nanosleep.u32 1;\n}\n" :: "n"(0) : "memory");
  prefetch_piece(target, pf_tgt);
  extern __shared__ unsigned char smem_raw[];
  const uint32_t sb = (smem_u32(smem_raw) + 1023u) & ~1023u;
  const int tid = threadIdx.x, lane = tid & 31;
  const int warp = __shfl_sync(0xffffffffu, tid >> 5, 0);
#define ACT NCW
  const int bstep = ACT * grid;

  STAMP(0);
  if (warp < NCW * 4) {
    const int wg = warp >> 2, w = warp & 3;
    const int g = lane >> 2;
    const uint32_t ring = sb + wg * RING_BYTES;
    const bool active = wg * grid + (int)blockIdx.x < B && wg < ACT;
    {
      const int t = tid & 127;
      const uint32_t dst = sb + ((t ^ ((t >> 3) & 7)) << 4);
      const char* src = reinterpret_cast<const char*>(w1) + t * 16;
#pragma unroll
      for (int i = 0; i < 4; i++) cp_async16(dst + w1_at(i) + wg * 2048, src + i * 8192 + wg * 2048);
      cp_async16(dst + w1_at(0) + (wg >> 1) * RING_BYTES + (wg & 1) * SLOT_BYTES + 6144, src + wg * 8192 + 6144);
      if (wg == 0) cp_async16(dst + w1_at(3) + 6144, src + 3 * 8192 + 6144);
      if (lane < 8) {
        if (w == 0 && active) cp_async16(ring + R_TGT0 + lane * 16, target + (size_t)(wg * grid + blockIdx.x) * kD + lane * 8);
        if (w == 1 && wg < 2) cp_async16(ring + R_VEC + lane * 16, (wg ? w2 : b1) + lane * 8);
      }
    }
    if (w == 2) sts32(ring + R_SEL + lane * 4, 0x3f803f80u);
    uint32_t rb2;
    asm volatile("ld.global.nc.u16 %0, [%1];" : "=r"(rb2) : "l"(b2));
    asm volatile("setmaxnreg.inc.sync.aligned.u32 %0;" :: "n"(CONS_REGS));
    asm volatile("cp.async.wait_all;" ::: "memory");
    STAMP(5);
    asm volatile("bar.sync 1, %0;" :: "n"(NCW * 160) : "memory");
    const uint32_t half2 = 0x3f003f00u, nhalf2 = 0xbf00bf00u, nzero2 = 0x80008000u;
    const uint32_t vec = sb + R_VEC + (16 * w + g) * 2;
    const float w2a = 0.5f * __uint_as_float(lds16(vec + RING_BYTES) << 16);
    const float w2b = 0.5f * __uint_as_float(lds16(vec + RING_BYTES + 16) << 16);
    const uint32_t rw2 = lds32(sb + RING_BYTES + R_VEC + lane * 4);
    float c32 = __uint_as_float(rw2 << 16) + __uint_as_float(rw2 & 0xffff0000u);
#pragma unroll
    for (int o = 16; o; o >>= 1) c32 += __shfl_xor_sync(0xffffffffu, c32, o);
    c32 = (0.5f * c32 + __uint_as_float(rb2 << 16)) * (1.0f / 32.0f);
    uint32_t bq[4];
    bq[2] = hfma2_bf16(lds16(vec), half2, nzero2);
    bq[3] = hfma2_bf16(lds16(vec + 16), half2, nzero2);
    if (lane & 3) bq[2] = bq[3] = 0;
    uint32_t wac[16], wd[16], wbc[16];
    {
      const int mi = lane >> 3, rr = lane & 7;
      const uint32_t a0 = sb + (8 * (mi >> 1) + rr) * 128 + (((2 * w + (mi & 1)) ^ rr) << 4);
#pragma unroll
      for (int ks = 0; ks < 4; ks++) {
        uint32_t A[4], Bm[4], C[4], Dm[4];
        ldsm_x4_t(a0 + ks * 2048 + w1_at(0), A[0], A[1], A[2], A[3]);
        ldsm_x4_t(a0 + ks * 2048 + w1_at(1), Bm[0], Bm[1], Bm[2], Bm[3]);
        ldsm_x4_t(a0 + ks * 2048 + w1_at(2), C[0], C[1], C[2], C[3]);
        ldsm_x4_t(a0 + ks * 2048 + w1_at(3), Dm[0], Dm[1], Dm[2], Dm[3]);
#pragma unroll
        for (int e = 0; e < 4; e++) {
          wac[4 * ks + e] = hfma2_bf16(A[e], half2, hfma2_bf16(C[e], half2, nzero2));
          wbc[4 * ks + e] = hfma2_bf16(Bm[e], half2, hfma2_bf16(C[e], nhalf2, nzero2));
          wd[4 * ks + e] = hfma2_bf16(Dm[e], half2, nzero2);
        }
      }
    }
    asm volatile("fence.proxy.async.shared::cta;" ::: "memory");
    asm volatile("bar.sync 5, %0;" :: "n"(NCW * 128) : "memory");

    const uint32_t ln = __shfl_sync(0xffffffffu, lane, lane);
    const uint32_t q0 = __shfl_sync(0xffffffffu, (lane & 3) ? 0u : 0xffffffffu, lane);
    const uint32_t meta = __shfl_sync(0xffffffffu, 0x88dddd88u + (grid >> 20), lane);
    const uint32_t zr = grid >> 20;
    const uint32_t sel = (ring + R_SEL) >> 4;
    const uint32_t ost = __shfl_sync(0xffffffffu, (lane >> 4) * 1024 + w * 256 + (lane & 15) * 16, lane);
    const uint32_t first = ring;
    const uint32_t last = first + (NSLOT - 1) * SLOT_BYTES;
    uint32_t sa = first, phase = 0;
    uint32_t we[16];
    auto make_weff = [&](uint32_t ta) {
      uint32_t t[8];
      ta += (ln & 24) << 1;
      ldsm_x4(ta, t[0], t[1], t[2], t[3]);
      ldsm_x4(ta + 64, t[4], t[5], t[6], t[7]);
#pragma unroll
      for (int i = 0; i < 16; i++) we[i] = hfma2_bf16(t[i >> 1], wd[i], wac[i]);
    };
    auto make_bq = [&](const float (&bz)[4]) {
#pragma unroll
      for (int e = 0; e < 2; e++) {
        const uint32_t v = __float_as_uint(bz[2 * e]) & q0;
        const float hi = __uint_as_float(v & 0xffff0000u);
        bq[e] = pack_bf16(__uint_as_float(v) - hi, hi);
      }
    };
    if (active) {
      {
        float bz[4];
        uint64_t d0 = (uint64_t)DESC_ROWS << 32 | (ring + R_TGT0) >> 4;
        mma_fence();
        bias_out<0>(bz, wbc, d0);
        make_weff(ring + R_TGT0);
        mma_wait<0>(bz);
        make_bq(bz);
      }
      STAMP(1);
      uint32_t raw = 0, cur, hdr;
      uint32_t full = 0;
      auto finish = [&]() {
        asm volatile("bar.sync %0, 128;" :: "r"(2 + wg) : "memory");
        const uint32_t ra = cur + S_OUT + w * 1024 + ln * 16;
        uint32_t f0[4], f1[4];
        ldsm_x4_t(ra, f0[0], f0[1], f0[2], f0[3]);
        ldsm_x4_t(ra + 512, f1[0], f1[1], f1[2], f1[3]);
        uint32_t* dst = reinterpret_cast<uint32_t*>(out) + (lds32(first + R_STOP + 4) + 4 * w + (ln & 4) * 4 + (ln >> 3));
        float c0[4] = {0.f, 0.f, 0.f, 0.f}, c1[4] = {0.f, 0.f, 0.f, 0.f};
        mma_bf16(c0, f0, 0x3f803f80u);
        mma_bf16(c1, f1, 0x3f803f80u);
        *dst = pack_bf16(c0[0] + c1[0], c0[2] + c1[2]);
      };
      auto chunk = [&](auto groups) {
        constexpr int N8 = decltype(groups)::value, NY = N8 - NA;
        constexpr int KT = (N8 + 1) / 2, E1 = KT - (N8 == 16 ? 3 : N8 == 14 ? KL14 : KL), E0 = N8 < 16 && K0 < E1 ? K0 : E1;
        float x[4 * NA], y[4 * NY], bz[4], o[16];
        uint32_t a[4 * E0], a1[E1 > E0 ? 4 * (E1 - E0) : 4], a2[4 * (KT - E1)];
        auto M = [&](int i0, int i1) {
#pragma unroll
          for (int i = i0; i < i1; i++) {
            uint32_t p = i < NA ? mix(x, i, w2a, w2b, c32) : i < N8 ? mix(y, i - NA, w2a, w2b, c32) : 0;
            if (N8 == 16) {
              uint32_t m = 0x3f803f80u;
              asm volatile("{\n.reg .pred p;\nsetp.ne.u32 p, %1, 0;\n@p ld.shared.u32 %0, [%2];\n}\n"
                           : "+r"(m) : "r"(hdr & H_GENERAL), "r"(cur + S_MASK + i * 16 + (ln & 3) * 4) : "memory");
              p = hfma2_bf16(p, m, 0x80008000u);
            }
            if (i < 2 * E0) a[2 * i] = a[2 * i + 1] = p;
            else if (i < 2 * E1) a1[2 * i - 4 * E0] = a1[2 * i - 4 * E0 + 1] = p;
            else a2[2 * i - 4 * E1] = a2[2 * i - 4 * E1 + 1] = p;
          }
        };
        auto header = [&]() {
          raw = lds32(sa + S_HDR);
          raw = (raw >> 31) == phase ? 0 : raw;
        };
        const uint32_t sta = cur + S_OUT + ost;
        uint64_t db = (uint64_t)(DESC_ROWS + (cur >> 24)) << 32 | cur >> 4;
        const uint32_t par = phase;
        phase ^= sa == last;
        sa = sa == last ? first : sa + SLOT_BYTES;
        mma_fence();
        bias_in(x, bq, sel);
        bias_in(y, bq, sel);
        mbar_wait_unless(full, cur + S_FULL, par);
        LOGT(0);
        mma_fence();
        gemm1<0>(x, we, db);
        bias_out<S_TGT / 16>(bz, wbc, db);
        mma_wait<1>(x);
        const uint32_t there = mbar_test(cur + S_REST, par);
        tanh_range(x, 0, 4 * SA);
        mbar_wait_unless(there, cur + S_REST, par);
        LOGT(2);
        mma_fence();
        gemm1<64 * NA>(y, we, db);
        tanh_range(x, 4 * SA, 4 * (SA + SB));
        if (__builtin_expect(zr != 0, 0)) {
          __nanosleep(zr);
#pragma unroll
          for (int i = 4 * (SA + SB); i < 4 * NA; i++) asm volatile("mov.b32 %0, %1;" : "=f"(x[i]) : "r"(ln));
        }
        tanh_range(x, 4 * (SA + SB), 4 * NA);
        M(0, NA - 1);
        if (__builtin_expect(zr != 0, 0)) {
          __nanosleep(zr);
#pragma unroll
          for (int i = 0; i < NA - 1; i++) sts32(zr + i, a[2 * i]);
#pragma unroll
          for (int i = 4 * NA - 4; i < 4 * NA; i++) sts32(zr + i, __float_as_uint(x[i]));
        }
        mma_wait<0>(y);
        asm volatile("" : "+f"(bz[0]), "+f"(bz[2]) :: "memory");
        header();
        tanh_range(y, 0, 4 * (2 * E0 - NA));
        make_weff(cur + S_TGT);
        M(NA - 1, 2 * E0);
        auto after = [&](uint32_t g, uint32_t u, auto more) {
          asm volatile("{\n.reg .b32 lo, hi, z;\n.reg .pred p;\nand.b32 z, %1, %2;\nsetp.ne.u32 p, z, 0;\nvote.sync.ballot.b32 z, p, 0xffffffff;\n"
                       "and.b32 z, z, %4;\nmov.b64 {lo, hi}, %0;\nadd.u32 hi, hi, %3;\nadd.u32 hi, hi, z;\nmov.b64 %0, {lo, hi};\n}\n"
                       : "+l"(db) : "r"(g), "r"(zr), "n"(decltype(more)::value), "r"(u));
        };
        constexpr int EP = E1 == E0 ? 2 : TP;
        if (EP >= 2) { make_bq(bz); raw = __shfl_sync(0xffffffffu, raw, 0); }
        after(a[4 * E0 - 2] | a[4 * E0 - 4] | (EP == 2 ? bq[0] | bq[1] | sta : 0), EP == 2 ? raw : ~0u, Int<(int)(DESC_HALVES - DESC_ROWS)>());
        gemm2_first<0>(o, a, db, meta);
        if constexpr (E1 > E0) {
          tanh_range(y, 4 * (2 * E0 - NA), 4 * (2 * E1 - NA));
          M(2 * E0, 2 * E1);
          if (EP == 3) after(bq[0] | bq[1] | sta, raw, Int<0>());
          gemm2_more<128 * E0>(o, a1, db, meta);
        }
        tanh_range(y, 4 * (2 * E1 - NA), 4 * NY);
        M(2 * E1, 2 * KT);
        gemm2_more<128 * E1>(o, a2, db, meta);
        full = mbar_test(sa + S_FULL, phase);
        mma_wait<0>(o);
#pragma unroll
        for (int j = 0; j < 2; j++)
          stsm_x4(sta + j * 2048, pack_bf16(o[8 * j], o[8 * j + 2]), pack_bf16(o[8 * j + 1], o[8 * j + 3]),
                  pack_bf16(o[8 * j + 4], o[8 * j + 6]), pack_bf16(o[8 * j + 5], o[8 * j + 7]));
        LOGT(1);
        __syncwarp();
        asm volatile("{\n.reg .pred p;\nsetp.eq.u32 p, %1, 0;\n@p mbarrier.arrive.shared::cta.b64 _, [%0];\n}\n"
                     :: "r"(cur + S_EMPTY), "r"(ln | (hdr & H_FINAL)) : "memory");
      };
      while (true) {
        hdr = __shfl_sync(0xffffffffu, raw, 0);
        cur = sa;
        if (hdr & H_13) { chunk(Int<13>()); if (hdr & H_FINAL) break; }
        else if (hdr & H_12) { chunk(Int<12>()); if (hdr & H_FINAL) break; }
        else if (hdr & H_14) { chunk(Int<14>()); if (hdr & H_FINAL) break; }
        else if (hdr & H_15) { chunk(Int<15>()); if (hdr & H_FINAL) break; }
        else if (hdr & H_STOP) return;
        else if (hdr) { chunk(Int<16>()); if (hdr & H_FINAL) break; }
        else {
          asm volatile("{\n.reg .pred p;\n.reg .u32 n, t;\nmov.u32 n, 0;\n"
                       "AGAIN:\nnanosleep.u32 32;\nld.shared.u32 %0, [%1];\nshfl.sync.idx.b32 %0, %0, 0, 31, 0xffffffff;\n"
                       "shr.u32 t, %0, 31;\nsetp.ne.u32 p, t, %2;\n@p bra.uni THERE;\n"
                       "add.u32 n, n, 1;\nsetp.lt.u32 p, n, 0x1000000;\n@p bra.uni AGAIN;\ntrap;\nTHERE:\n}\n"
                       : "=r"(raw) : "r"(sa + S_HDR), "r"(phase) : "memory");
        }
      }
      finish();
    }
    STAMP(4);
  } else {
    const int pw = warp - NCW * 4;
    const uint32_t ring = sb + pw * RING_BYTES;
    asm volatile("setmaxnreg.dec.sync.aligned.u32 %0;" :: "n"(PROD_REGS));
    if (pw < NCW) {
      int b = pw * grid + blockIdx.x, bn = b + bstep;
      uint4 mw = load_mask(mask, min(b, B - 1), min(lane, 24));
      if (lane == 0) {
#pragma unroll
        for (int i = 0; i < NSLOT; i++) {
          mbar_init(ring + i * SLOT_BYTES + S_FULL, 33);
          mbar_init(ring + i * SLOT_BYTES + S_REST, 33);
          mbar_arrive(ring + i * SLOT_BYTES + S_REST);
          mbar_init(ring + i * SLOT_BYTES + S_EMPTY, 4);
          sts32(ring + i * SLOT_BYTES + S_HDR, 0);
        }
        sts32(ring + R_STOP, b < B && pw < ACT ? 0 : ring);
      }
      sts32(sb + R_PACE + lane * 4, 0);
      asm volatile("bar.arrive 1, %0;" :: "n"(NCW * 160) : "memory");
      asm volatile("bar.arrive 6, 128;" ::: "memory");
      if (pw >= ACT) return;
      const uint32_t list = ring + R_LIST;
      uint32_t lt;
      asm("mov.u32 %0, %%lanemask_lt;" : "=r"(lt));
      const uint32_t ln = __shfl_sync(0xffffffffu, lane, lane);
      const uint32_t r4 = (ln >> 3) * 4, c16 = (ln & 7) * 16, l25 = min(ln, 24u);
      const uint32_t pick = ln < 25 ? 0xeca8 : 0x9999;
      uint32_t dst[4];
#pragma unroll
      for (int i = 0; i < 4; i++) dst[i] = ring + (r4 + i) * 128 + (c16 ^ (((r4 + i) & 7) << 4));
      uint64_t pol;
      asm("createpolicy.fractional.L2::evict_first.b64 %0, 1.0;" : "=l"(pol));
      uint32_t sa = ring, phase = 1;
      const uint32_t wrap = (uint32_t)(max(B - NSTATIC * bstep, 0) + bstep - 1);
      auto next_slot = [&]() {
        const bool wrapped = sa == ring + (NSLOT - 1) * SLOT_BYTES;
        const int step = wrapped ? -(NSLOT - 1) * SLOT_BYTES : SLOT_BYTES;
        sa += step;
        phase ^= wrapped;
#pragma unroll
        for (int i = 0; i < 4; i++) dst[i] += step;
      };
      uint32_t claimer = ln;
      uint32_t drawn, started = 0;
      int mean16 = 0;
      auto draw = [&]() {
        drawn = B;
        asm volatile("{\n.reg .pred p;\nsetp.eq.u32 p, %3, 0;\n@p atom.global.inc.u32 %0, [%1], %2;\n}\n"
                     : "+r"(drawn) : "l"(counter), "r"(wrap), "r"(claimer) : "memory");
      };
      if (b >= B) draw();
      while (b < B) {
        const uint32_t e0 = nonzero_as_one(mw.x), e1 = nonzero_as_one(mw.y);
        const uint32_t e2 = nonzero_as_one(mw.z), e3 = nonzero_as_one(mw.w);
        const uint32_t nonbin = (e0 ^ mw.x) | (e1 ^ mw.y) | (e2 ^ mw.z) | (e3 ^ mw.w);
        const uint32_t sA = prmt(e0, e1, pick), sB = prmt(e2, e3, pick);
        const uint32_t pA = (sA & 0x01010101u) * 0x01010101u;
        const uint32_t pB = ((sB & 0x01010101u) + (pA >> 24)) * 0x01010101u;
        uint32_t pos = 0;
        int n = 0;
#pragma unroll
        for (int k = 0; k < 4; k++) {
          const uint32_t bal = ballot_bit(pB, 0x01000000u << k);
          pos += __popc(bal & lt) << k;
          n += __popc(bal) << k;
        }
        const uint32_t general = __any_sync(0xffffffffu, nonbin != 0);
        const uint32_t aA = (pA + pos * 0x01010101u) | ~sA, aB = (pB + pos * 0x01010101u) | ~sB;
#pragma unroll
        for (int i = 0; i < 8; i++) sts8(list - 1 + prmt(i < 4 ? aA : aB, 0, 0x4440 + (i & 3)), 8 * ln + i);
        __syncwarp();

        const uint64_t src = reinterpret_cast<uint64_t>(hist) + (uint64_t)b * (kL * kD * 2);
        const bool no_carry = (uint32_t)src <= 0xffffffffu - kL * kD * 2;
        auto begin_fill = [&](uint32_t h, uint32_t part, int nc, int bt, auto extra) {
          LOGT(0);
          mbar_wait(sa + S_EMPTY, phase);
          if (bt >= B && !part) h |= H_FINAL;
          asm volatile("{\n.reg .pred p;\nsetp.ne.u32 p, %3, 0;\n@p st.shared.v2.u32 [%0], {%1, %2};\n}\n"
                       :: "r"(ring + R_STOP), "r"(sa + (phase ^ 1)), "r"(b * 32), "r"(h & H_FINAL) : "memory");
          extra();
          sts32(sa + S_HDR, h | phase << 31);
          sts32(sa + S_ROW + phase * 4, b | part);
          asm volatile("{\n.reg .pred p;\nsetp.eq.u32 p, %1, 0;\n@p mbarrier.arrive.shared::cta.b64 _, [%0];\n}\n"
                       :: "r"(sa + S_FULL), "r"(ln) : "memory");
          mean16 = mean16 == 0 ? 16 * nc : bn >= slow_from ? mean16 : mean16 + nc - (mean16 >> 4);
          asm volatile("{\n.reg .u32 c;\n"
                       "mov.u32 c, %%globaltimer_lo;\n"
                       "red.shared.max.u32 [%1], c;\n"
                       "atom.shared.add.u32 %0, [%1], %2;\n}\n"
                       : "=r"(started) : "r"(sb + R_PACE + ln * 4),
                         "r"(bn >= slow_from ? mean16 * pace_slow >> 8 : nc * pace >> 4) : "memory");
          started = __shfl_sync(0xffffffffu, started, 0);
          if (!(part & ROW_REST)) mw = load_mask(mask, min(bn, B - 1), l25);
          wait_for(started, pace * (CHUNK / 4));
          LOGT(1);
          if (!(part & ROW_REST)) draw();
          asm volatile("cp.async.ca.shared.global [%0], [%1], 4;"
                       :: "r"(sa + S_TGT + ln * 4), "l"(reinterpret_cast<const uint32_t*>(target) + ((uint32_t)min(bt, B - 1) * 32u + ln)) : "memory");
        };
        auto end_fill = [&](int nc) {
          cp_async_arrive_noinc(sa + S_REST);
          next_slot();
          LOGT(2);
        };
        const uint32_t base = (uint32_t)src + c16;
        uint64_t a[4];
        a[0] = a[1] = a[2] = a[3] = (uint64_t)((uint32_t)(src >> 32) + (ln >> 5)) << 32;
        if (__builtin_expect(no_carry && !general && n >= 80 && n <= CHUNK, 1)) {
          uint32_t idx[7];
#pragma unroll
          for (int t = 0; t < 7; t++) idx[t] = lds32(list + r4 + t * 16);
          uint32_t have;
          asm("bmsk.clamp.b32 %0, 0, %1;" : "=r"(have) : "r"(max(n - 80 - (int)r4, 0)));
          begin_fill(size_bit(n), 0, n, bn, [](){});
          cp_group<0>(dst, a, idx[0], base, pol);
          cp_group<1>(dst, a, idx[1], base, pol);
          cp_group<2>(dst, a, idx[2], base, pol);
          cp_async_arrive_noinc(sa + S_FULL);
          if (bn >= slow_from) wait_for(started + spread, spread);
          cp_group<3>(dst, a, idx[3], base, pol);
          cp_group<4>(dst, a, idx[4], base, pol);
          cp_group_m<5, 0>(dst, a, idx[5], base, have, 1, pol);
          cp_group_m<6, 16>(dst, a, idx[6], base, have, n > 96, pol);
          if (n > 112) cp_group_z<7>(dst, a, lds32(list + r4 + 112), base, n - r4, pol);
          end_fill(n);
        } else if (no_carry && !general) {
          int nc = n <= CHUNK ? n : n <= 160 ? 64 : 96;
          uint32_t la = list + r4, part = n <= CHUNK ? 0 : ROW_MORE;
#pragma unroll 1
          while (true) {
            begin_fill(size_bit(nc), part, nc, part == ROW_MORE ? b : bn, [](){});
            const int left = nc - r4;
            cp_group_z<0>(dst, a, lds32(la), base, left, pol);
            cp_group_z<1>(dst, a, lds32(la + 16), base, left, pol);
            cp_group_z<2>(dst, a, lds32(la + 32), base, left, pol);
            cp_async_arrive_noinc(sa + S_FULL);
            if (bn >= slow_from) wait_for(started + spread, spread);
            cp_group_z<3>(dst, a, lds32(la + 48), base, left, pol);
            cp_group_z<4>(dst, a, lds32(la + 64), base, left, pol);
            cp_group_z<5>(dst, a, lds32(la + 80), base, left, pol);
            cp_group_z<6>(dst, a, lds32(la + 96), base, left, pol);
            cp_group_z<7>(dst, a, lds32(la + 112), base, left, pol);
            end_fill(nc);
            if (part != ROW_MORE) break;
            la += nc;
            nc = n - nc;
            part = ROW_REST;
          }
        } else {
          int r0 = 0;
#pragma unroll 1
          do {
            const int nc = min(n - r0, CHUNK);
            const bool more = r0 + CHUNK < n;
            begin_fill(general ? H_GENERAL : H_16, (more ? ROW_MORE : 0u) | (r0 ? ROW_REST : 0u), nc, more ? b : bn, [&]() {
#pragma unroll 1
              for (int z = ln; general && z < CHUNK; z += 32) {
                uint32_t v = 0;
                if (z < nc) {
                  uint32_t row;
                  asm volatile("ld.shared.u8 %0, [%1];" : "=r"(row) : "r"(list + r0 + z) : "memory");
                  v = __bfloat16_as_ushort(mask[(size_t)b * kL + row]);
                }
                sts16(sa + S_MASK + z * 2, v);
              }
              __syncwarp();
            });
#pragma unroll 1
            for (int z = r4 >> 2; z < CHUNK; z += 4) {
              uint32_t row;
              asm volatile("ld.shared.u8 %0, [%1];" : "=r"(row) : "r"(list + r0 + z) : "memory");
              asm volatile("cp.async.cg.shared.global [%0], [%1], 16, %2;"
                           :: "r"(sa + z * 128 + (c16 ^ ((z & 7) << 4))), "l"(src + c16 + (z < nc ? row : 0) * 128),
                              "r"(z < nc ? 16 : 0) : "memory");
            }
            cp_async_arrive_noinc(sa + S_FULL);
            end_fill(nc);
            r0 += CHUNK;
          } while (r0 < n);
        }
        b = bn;
        bn = __shfl_sync(0xffffffffu, drawn, 0) + NSTATIC * bstep;
        if (bn >= B) claimer = 1;
      }
      STAMP(3);
      if (lds32(ring + R_STOP) == 0) {
        mbar_wait(sa + S_EMPTY, phase);
        sts32(sa + S_HDR, H_STOP | phase << 31);
        sts32(ring + R_STOP, sa + (phase ^ 1));
      }
      asm volatile("cp.async.wait_all;" ::: "memory");
      STAMP(4);
    } else {
      uint32_t due = clock();
      int s0 = NSTATIC * bstep + (PF_EARLY * grid + blockIdx.x) * PF_ROWS;
      auto prefetch = [&]() {
        const int cnt = min(PF_ROWS, B - s0);
        if (lane == 0) {
          prefetch_l2(mask + (size_t)s0 * kL, cnt * kL * 2);
          prefetch_l2(target + (size_t)s0 * kD, cnt * kD * 2);
        }
        s0 += grid * PF_ROWS;
      };
#pragma unroll 1
      for (int j = PF_EARLY; j < PF_FAST && s0 < B; j++) {
        while ((int)(due - (uint32_t)clock()) > 0) {}
        prefetch();
        due += PF_CYCLES;
      }
      due += (PF_FAST - 1) * PF_SLOW - (PF_FAST - PF_EARLY) * PF_CYCLES + (blockIdx.x & 255) * (PF_SLOW / 256);
      asm volatile("bar.sync 6, 128;" ::: "memory");
      const uint32_t ln = __shfl_sync(0xffffffffu, lane, lane);
      const uint32_t home = sb + min(ln, NCW - 1u) * RING_BYTES;
      uint32_t mine = ln < NCW ? home : 0;
      const uint32_t word = __shfl_sync(0xffffffffu, (lane & 4) * 4 + (lane & 3) * 4 + (lane >> 3), lane);
      uint32_t idle = 0, r = 0, at;
      auto poll = [&]() {
        uint32_t ready;
        asm volatile("{\n.reg .pred p;\nsetp.ne.u32 p, %3, 0;\n@p mbarrier.test_wait.parity.shared::cta.b64 p, [%1], %2;\n"
                     "vote.sync.ballot.b32 %0, p, 0xffffffff;\n}\n"
                     : "=r"(ready) : "r"((mine & ~1u) + S_EMPTY), "r"(mine & 1), "r"(mine) : "memory");
        static_assert(NCW == 3, "");
        const uint32_t pick = ((r == 0 ? 0x5a53u : r == 1 ? 0xaa13u : 0x1213u) >> (2 * ready)) & 3;
        at = __shfl_sync(0xffffffffu, mine, pick);
        r = ready ? pick : r;
      };
      poll();
#pragma unroll 1
      while (true) {
        if (at) {
          const uint32_t sa = at & ~1u, carry = sb + r * RING_BYTES + R_CARRY + ln * 8;
          uint32_t f[8][4];
#pragma unroll
          for (int i = 0; i < 8; i++) ldsm_x4_t(sa + S_OUT + ln * 16 + (i >> 2) * 512 + (i & 3) * 1024, f[i][0], f[i][1], f[i][2], f[i][3]);
          const uint32_t row = lds32(sa + S_ROW + 4 - (at & 1) * 4);
          if (ln == r) mine = sa == home + (NSLOT - 1) * SLOT_BYTES ? (at - (NSLOT - 1) * SLOT_BYTES) ^ 1 : at + SLOT_BYTES;
          float c[8][4];
#pragma unroll
          for (int i = 0; i < 8; i++) {
            c[i][0] = c[i][1] = c[i][2] = c[i][3] = 0.f;
            mma_bf16(c[i], f[i], 0x3f803f80u);
          }
          poll();
          asm volatile("{\n.reg .pred p;\nsetp.eq.u32 p, %1, 0;\n@p mbarrier.arrive.shared::cta.b64 _, [%0];\n}\n"
                       :: "r"(sa + S_REST), "r"(ln) : "memory");
          float e[2];
#pragma unroll
          for (int k = 0; k < 2; k++) {
            const float u0 = ln & 1 ? c[1][2 * k] : c[0][2 * k], u1 = ln & 1 ? c[3][2 * k] : c[2][2 * k];
            const float u2 = ln & 1 ? c[5][2 * k] : c[4][2 * k], u3 = ln & 1 ? c[7][2 * k] : c[6][2 * k];
            e[k] = ln & 2 ? u1 + u3 : u0 + u2;
          }
          asm volatile("{\n.reg .pred p, q;\n.reg .f32 a, b;\n.reg .u32 t;\nshr.u32 t, %3, 30;\nsetp.eq.u32 p, t, 1;\nsetp.eq.u32 q, t, 2;\n"
                       "@p ld.shared.v2.f32 {a, b}, [%2];\n@p add.f32 %0, %0, a;\n@p add.f32 %1, %1, b;\n@q st.shared.v2.f32 [%2], {%0, %1};\n}\n"
                       : "+f"(e[0]), "+f"(e[1]) : "r"(carry), "r"(row) : "memory");
          asm volatile("{\n.reg .pred p;\nsetp.ge.s32 p, %2, 0;\n@p st.global.u32 [%0], %1;\n}\n"
                       :: "l"(reinterpret_cast<uint32_t*>(out) + (row * 32u + word)), "r"(pack_bf16(e[0], e[1])), "r"(row) : "memory");
        } else {
          const uint32_t stop = lds32(home + R_STOP);
          poll();
          if (stop == mine) mine = 0;
          if (!__any_sync(0xffffffffu, mine)) break;
          if (s0 < B) {
            if ((int)(due - (uint32_t)clock()) <= 0) { prefetch(); due += PF_SLOW; }
          } else if (++idle > 0x10000000) __trap();
          if (RED_SLEEP) __nanosleep(RED_SLEEP);
        }
      }
      STAMP(4);
    }
  }
}

}

extern "C" void kernel_launch(void* const* d_in, const int* in_sizes, int n_in, void* d_out, int out_size) {
  const __nv_bfloat16* target = (const __nv_bfloat16*)d_in[0];
  const __nv_bfloat16* hist = (const __nv_bfloat16*)d_in[1];
  const __nv_bfloat16* mask = (const __nv_bfloat16*)d_in[2];
  const __nv_bfloat16* w1 = (const __nv_bfloat16*)d_in[3];
  const __nv_bfloat16* b1 = (const __nv_bfloat16*)d_in[4];
  const __nv_bfloat16* w2 = (const __nv_bfloat16*)d_in[5];
  const __nv_bfloat16* b2 = (const __nv_bfloat16*)d_in[6];
  const int B = in_sizes[0] / din::kD;
  if (B <= 0) return;
  static int sms = 0, pace = 0;
  static unsigned int* counter = nullptr;
  if (sms == 0) {
    int dev = 0, khz = 0, bits = 0;
    cudaGetDevice(&dev);
    cudaDeviceGetAttribute(&sms, cudaDevAttrMultiProcessorCount, dev);
    cudaDeviceGetAttribute(&khz, cudaDevAttrMemoryClockRate, dev);
    cudaDeviceGetAttribute(&bits, cudaDevAttrGlobalMemoryBusWidth, dev);
    if (khz > 0 && bits > 0) pace = (int)(16.0 * 128.0 * sms / (khz * 1e-6 * 2.0 * bits / 8.0));
    if (pace > 256) pace = 0;
    cudaGetSymbolAddress((void**)&counter, din::g_next);
    cudaFuncSetAttribute(din::din_kernel, cudaFuncAttributeMaxDynamicSharedMemorySize, din::SMEM_BYTES);
  }
  const long long early = (long long)(din::NSTATIC * NCW + PF_EARLY * PF_ROWS) * sms, threads = (long long)din::NTHREADS * sms;
  long long pf_mask = (early * din::kL * 2 + threads - 1) / threads, pf_tgt = (early * din::kD * 2 + threads - 1) / threads;
  if (pf_mask > (long long)B * din::kL * 2 / threads) pf_mask = (long long)B * din::kL * 2 / threads;
  if (pf_tgt > (long long)B * din::kD * 2 / threads) pf_tgt = (long long)B * din::kD * 2 / threads;
  din::din_kernel<<<sms, din::NTHREADS, din::SMEM_BYTES>>>(mask, target, B, sms, (uint32_t)pf_mask, (uint32_t)pf_tgt,
                                                          w1, hist, b1, w2, b2, (__nv_bfloat16*)d_out, counter, pace,
                                                          B - SLOW_ROUNDS * NCW * sms / 2, pace + (pace * SLOW_BY + 40) / 80,
                                                          pace * SPREAD / 16);
}
```

```cpp
#include <cuda_runtime.h>
#include <cuda_bf16.h>
#include <stdint.h>

namespace din {

constexpr int kL = 200, kD = 64;
#define NCW 3
#define NSLOT 3
constexpr int CHUNK = 128;
constexpr int NTHREADS = NCW * 128 + 128;
constexpr int PROD_REGS = 56, CONS_REGS = 152;
#define PF_ROWS 8
#define PF_EARLY 3
#define PF_FAST 10
#define PF_CYCLES 280
#define PF_SLOW 2000
#define SLOW_ROUNDS 12
#define SLOW_BY 9
#define SPREAD 62
#define SA 2
#define SB 1
#define K0 3
#define KL 2
constexpr int NSTATIC = 2;
constexpr int S_TGT = CHUNK * 128;
constexpr int S_HDR = S_TGT + 128;
constexpr int S_FULL = S_HDR + 8;
constexpr int S_EMPTY = S_HDR + 16;
constexpr int S_ROW = S_HDR + 24;
constexpr int S_REST = S_HDR + 32;
constexpr int S_MASK = S_TGT + 256;
constexpr int S_OUT = S_TGT + 1024;
constexpr int SLOT_BYTES = S_OUT + 8192;
constexpr int RING_BYTES_ = NSLOT * SLOT_BYTES;
constexpr int R_PACE = 2 * RING_BYTES_ + S_TGT + 768;
constexpr int R_STOP = S_HDR + 40;
constexpr int R_LIST = S_TGT + 512;
constexpr int R_VEC = S_TGT + 768;
constexpr int R_SEL = S_TGT + 896;
constexpr int R_CARRY = SLOT_BYTES + S_TGT + 512;
constexpr int R_TGT0 = (NSLOT - 1) * SLOT_BYTES + S_OUT;
constexpr int RING_BYTES = NSLOT * SLOT_BYTES;
constexpr int SMEM_BYTES = NCW * RING_BYTES + 1024;
__device__ constexpr int w1_at(int i) { return (i >> 1) * RING_BYTES + (i & 1) * SLOT_BYTES + S_OUT; }
static_assert(SMEM_BYTES <= 232448, "shared memory");
constexpr uint32_t H_12 = 2, H_13 = 4, H_14 = 8, H_15 = 16, H_16 = 1u << 16;
constexpr uint32_t H_GENERAL = 1u << 17, H_FINAL = 1u << 18, H_STOP = 1u << 19;
constexpr uint32_t ROW_REST = 1u << 30, ROW_MORE = 1u << 31;

__device__ unsigned int g_next;


constexpr int NA = 5;
__device__ __forceinline__ void bias_in(float (&d)[20], const uint32_t (&a)[4], uint32_t lo) {
  asm volatile("{\n.reg .b64 db;\n"
    "cvt.u64.u32 db, %24;\n"
    "wgmma.mma_async.sync.aligned.m64n40k16.f32.bf16.bf16 {%0, %1, %2, %3, %4, %5, %6, %7, %8, %9, %10, %11, %12, %13, %14, %15, %16, %17, %18, %19}, {%20, %21, %22, %23}, db, 0, 1, 1, 0;\n}\n"
    : "=f"(d[0]), "=f"(d[1]), "=f"(d[2]), "=f"(d[3]), "=f"(d[4]), "=f"(d[5]), "=f"(d[6]), "=f"(d[7]), "=f"(d[8]), "=f"(d[9]), "=f"(d[10]), "=f"(d[11]), "=f"(d[12]), "=f"(d[13]), "=f"(d[14]), "=f"(d[15]), "=f"(d[16]), "=f"(d[17]), "=f"(d[18]), "=f"(d[19])
    : "r"(a[0]), "r"(a[1]), "r"(a[2]), "r"(a[3]), "r"(lo)
    : "memory");
}
__device__ __forceinline__ void bias_in(float (&d)[28], const uint32_t (&a)[4], uint32_t lo) {
  asm volatile("{\n.reg .b64 db;\n"
    "cvt.u64.u32 db, %32;\n"
    "wgmma.mma_async.sync.aligned.m64n56k16.f32.bf16.bf16 {%0, %1, %2, %3, %4, %5, %6, %7, %8, %9, %10, %11, %12, %13, %14, %15, %16, %17, %18, %19, %20, %21, %22, %23, %24, %25, %26, %27}, {%28, %29, %30, %31}, db, 0, 1, 1, 0;\n}\n"
    : "=f"(d[0]), "=f"(d[1]), "=f"(d[2]), "=f"(d[3]), "=f"(d[4]), "=f"(d[5]), "=f"(d[6]), "=f"(d[7]), "=f"(d[8]), "=f"(d[9]), "=f"(d[10]), "=f"(d[11]), "=f"(d[12]), "=f"(d[13]), "=f"(d[14]), "=f"(d[15]), "=f"(d[16]), "=f"(d[17]), "=f"(d[18]), "=f"(d[19]), "=f"(d[20]), "=f"(d[21]), "=f"(d[22]), "=f"(d[23]), "=f"(d[24]), "=f"(d[25]), "=f"(d[26]), "=f"(d[27])
    : "r"(a[0]), "r"(a[1]), "r"(a[2]), "r"(a[3]), "r"(lo)
    : "memory");
}
__device__ __forceinline__ void bias_in(float (&d)[32], const uint32_t (&a)[4], uint32_t lo) {
  asm volatile("{\n.reg .b64 db;\n"
    "cvt.u64.u32 db, %36;\n"
    "wgmma.mma_async.sync.aligned.m64n64k16.f32.bf16.bf16 {%0, %1, %2, %3, %4, %5, %6, %7, %8, %9, %10, %11, %12, %13, %14, %15, %16, %17, %18, %19, %20, %21, %22, %23, %24, %25, %26, %27, %28, %29, %30, %31}, {%32, %33, %34, %35}, db, 0, 1, 1, 0;\n}\n"
    : "=f"(d[0]), "=f"(d[1]), "=f"(d[2]), "=f"(d[3]), "=f"(d[4]), "=f"(d[5]), "=f"(d[6]), "=f"(d[7]), "=f"(d[8]), "=f"(d[9]), "=f"(d[10]), "=f"(d[11]), "=f"(d[12]), "=f"(d[13]), "=f"(d[14]), "=f"(d[15]), "=f"(d[16]), "=f"(d[17]), "=f"(d[18]), "=f"(d[19]), "=f"(d[20]), "=f"(d[21]), "=f"(d[22]), "=f"(d[23]), "=f"(d[24]), "=f"(d[25]), "=f"(d[26]), "=f"(d[27]), "=f"(d[28]), "=f"(d[29]), "=f"(d[30]), "=f"(d[31])
    : "r"(a[0]), "r"(a[1]), "r"(a[2]), "r"(a[3]), "r"(lo)
    : "memory");
}
__device__ __forceinline__ void bias_in(float (&d)[36], const uint32_t (&a)[4], uint32_t lo) {
  asm volatile("{\n.reg .b64 db;\n"
    "cvt.u64.u32 db, %40;\n"
    "wgmma.mma_async.sync.aligned.m64n72k16.f32.bf16.bf16 {%0, %1, %2, %3, %4, %5, %6, %7, %8, %9, %10, %11, %12, %13, %14, %15, %16, %17, %18, %19, %20, %21, %22, %23, %24, %25, %26, %27, %28, %29, %30, %31, %32, %33, %34, %35}, {%36, %37, %38, %39}, db, 0, 1, 1, 0;\n}\n"
    : "=f"(d[0]), "=f"(d[1]), "=f"(d[2]), "=f"(d[3]), "=f"(d[4]), "=f"(d[5]), "=f"(d[6]), "=f"(d[7]), "=f"(d[8]), "=f"(d[9]), "=f"(d[10]), "=f"(d[11]), "=f"(d[12]), "=f"(d[13]), "=f"(d[14]), "=f"(d[15]), "=f"(d[16]), "=f"(d[17]), "=f"(d[18]), "=f"(d[19]), "=f"(d[20]), "=f"(d[21]), "=f"(d[22]), "=f"(d[23]), "=f"(d[24]), "=f"(d[25]), "=f"(d[26]), "=f"(d[27]), "=f"(d[28]), "=f"(d[29]), "=f"(d[30]), "=f"(d[31]), "=f"(d[32]), "=f"(d[33]), "=f"(d[34]), "=f"(d[35])
    : "r"(a[0]), "r"(a[1]), "r"(a[2]), "r"(a[3]), "r"(lo)
    : "memory");
}
__device__ __forceinline__ void bias_in(float (&d)[40], const uint32_t (&a)[4], uint32_t lo) {
  asm volatile("{\n.reg .b64 db;\n"
    "cvt.u64.u32 db, %44;\n"
    "wgmma.mma_async.sync.aligned.m64n80k16.f32.bf16.bf16 {%0, %1, %2, %3, %4, %5, %6, %7, %8, %9, %10, %11, %12, %13, %14, %15, %16, %17, %18, %19, %20, %21, %22, %23, %24, %25, %26, %27, %28, %29, %30, %31, %32, %33, %34, %35, %36, %37, %38, %39}, {%40, %41, %42, %43}, db, 0, 1, 1, 0;\n}\n"
    : "=f"(d[0]), "=f"(d[1]), "=f"(d[2]), "=f"(d[3]), "=f"(d[4]), "=f"(d[5]), "=f"(d[6]), "=f"(d[7]), "=f"(d[8]), "=f"(d[9]), "=f"(d[10]), "=f"(d[11]), "=f"(d[12]), "=f"(d[13]), "=f"(d[14]), "=f"(d[15]), "=f"(d[16]), "=f"(d[17]), "=f"(d[18]), "=f"(d[19]), "=f"(d[20]), "=f"(d[21]), "=f"(d[22]), "=f"(d[23]), "=f"(d[24]), "=f"(d[25]), "=f"(d[26]), "=f"(d[27]), "=f"(d[28]), "=f"(d[29]), "=f"(d[30]), "=f"(d[31]), "=f"(d[32]), "=f"(d[33]), "=f"(d[34]), "=f"(d[35]), "=f"(d[36]), "=f"(d[37]), "=f"(d[38]), "=f"(d[39])
    : "r"(a[0]), "r"(a[1]), "r"(a[2]), "r"(a[3]), "r"(lo)
    : "memory");
}
__device__ __forceinline__ void bias_in(float (&d)[44], const uint32_t (&a)[4], uint32_t lo) {
  asm volatile("{\n.reg .b64 db;\n"
    "cvt.u64.u32 db, %48;\n"
    "wgmma.mma_async.sync.aligned.m64n88k16.f32.bf16.bf16 {%0, %1, %2, %3, %4, %5, %6, %7, %8, %9, %10, %11, %12, %13, %14, %15, %16, %17, %18, %19, %20, %21, %22, %23, %24, %25, %26, %27, %28, %29, %30, %31, %32, %33, %34, %35, %36, %37, %38, %39, %40, %41, %42, %43}, {%44, %45, %46, %47}, db, 0, 1, 1, 0;\n}\n"
    : "=f"(d[0]), "=f"(d[1]), "=f"(d[2]), "=f"(d[3]), "=f"(d[4]), "=f"(d[5]), "=f"(d[6]), "=f"(d[7]), "=f"(d[8]), "=f"(d[9]), "=f"(d[10]), "=f"(d[11]), "=f"(d[12]), "=f"(d[13]), "=f"(d[14]), "=f"(d[15]), "=f"(d[16]), "=f"(d[17]), "=f"(d[18]), "=f"(d[19]), "=f"(d[20]), "=f"(d[21]), "=f"(d[22]), "=f"(d[23]), "=f"(d[24]), "=f"(d[25]), "=f"(d[26]), "=f"(d[27]), "=f"(d[28]), "=f"(d[29]), "=f"(d[30]), "=f"(d[31]), "=f"(d[32]), "=f"(d[33]), "=f"(d[34]), "=f"(d[35]), "=f"(d[36]), "=f"(d[37]), "=f"(d[38]), "=f"(d[39]), "=f"(d[40]), "=f"(d[41]), "=f"(d[42]), "=f"(d[43])
    : "r"(a[0]), "r"(a[1]), "r"(a[2]), "r"(a[3]), "r"(lo)
    : "memory");
}
template<int D> __device__ __forceinline__ void gemm1(float (&d)[20], const uint32_t (&a)[16], uint64_t db) {
  asm volatile("{\n.reg .b64 db;\n"
    "add.s64 db, %36, %37 + 0;\n"
    "wgmma.mma_async.sync.aligned.m64n40k16.f32.bf16.bf16 {%0, %1, %2, %3, %4, %5, %6, %7, %8, %9, %10, %11, %12, %13, %14, %15, %16, %17, %18, %19}, {%20, %21, %22, %23}, db, 1, 1, 1, 0;\n"
    "add.s64 db, %36, %37 + 2;\n"
    "wgmma.mma_async.sync.aligned.m64n40k16.f32.bf16.bf16 {%0, %1, %2, %3, %4, %5, %6, %7, %8, %9, %10, %11, %12, %13, %14, %15, %16, %17, %18, %19}, {%24, %25, %26, %27}, db, 1, 1, 1, 0;\n"
    "add.s64 db, %36, %37 + 4;\n"
    "wgmma.mma_async.sync.aligned.m64n40k16.f32.bf16.bf16 {%0, %1, %2, %3, %4, %5, %6, %7, %8, %9, %10, %11, %12, %13, %14, %15, %16, %17, %18, %19}, {%28, %29, %30, %31}, db, 1, 1, 1, 0;\n"
    "add.s64 db, %36, %37 + 6;\n"
    "wgmma.mma_async.sync.aligned.m64n40k16.f32.bf16.bf16 {%0, %1, %2, %3, %4, %5, %6, %7, %8, %9, %10, %11, %12, %13, %14, %15, %16, %17, %18, %19}, {%32, %33, %34, %35}, db, 1, 1, 1, 0;\n"
    "wgmma.commit_group.sync.aligned;\n}\n"
    : "+f"(d[0]), "+f"(d[1]), "+f"(d[2]), "+f"(d[3]), "+f"(d[4]), "+f"(d[5]), "+f"(d[6]), "+f"(d[7]), "+f"(d[8]), "+f"(d[9]), "+f"(d[10]), "+f"(d[11]), "+f"(d[12]), "+f"(d[13]), "+f"(d[14]), "+f"(d[15]), "+f"(d[16]), "+f"(d[17]), "+f"(d[18]), "+f"(d[19])
    : "r"(a[0]), "r"(a[1]), "r"(a[2]), "r"(a[3]), "r"(a[4]), "r"(a[5]), "r"(a[6]), "r"(a[7]), "r"(a[8]), "r"(a[9]), "r"(a[10]), "r"(a[11]), "r"(a[12]), "r"(a[13]), "r"(a[14]), "r"(a[15]), "l"(db), "n"(D)
    : "memory");
}
template<int D> __device__ __forceinline__ void gemm1(float (&d)[28], const uint32_t (&a)[16], uint64_t db) {
  asm volatile("{\n.reg .b64 db;\n"
    "add.s64 db, %44, %45 + 0;\n"
    "wgmma.mma_async.sync.aligned.m64n56k16.f32.bf16.bf16 {%0, %1, %2, %3, %4, %5, %6, %7, %8, %9, %10, %11, %12, %13, %14, %15, %16, %17, %18, %19, %20, %21, %22, %23, %24, %25, %26, %27}, {%28, %29, %30, %31}, db, 1, 1, 1, 0;\n"
    "add.s64 db, %44, %45 + 2;\n"
    "wgmma.mma_async.sync.aligned.m64n56k16.f32.bf16.bf16 {%0, %1, %2, %3, %4, %5, %6, %7, %8, %9, %10, %11, %12, %13, %14, %15, %16, %17, %18, %19, %20, %21, %22, %23, %24, %25, %26, %27}, {%32, %33, %34, %35}, db, 1, 1, 1, 0;\n"
    "add.s64 db, %44, %45 + 4;\n"
    "wgmma.mma_async.sync.aligned.m64n56k16.f32.bf16.bf16 {%0, %1, %2, %3, %4, %5, %6, %7, %8, %9, %10, %11, %12, %13, %14, %15, %16, %17, %18, %19, %20, %21, %22, %23, %24, %25, %26, %27}, {%36, %37, %38, %39}, db, 1, 1, 1, 0;\n"
    "add.s64 db, %44, %45 + 6;\n"
    "wgmma.mma_async.sync.aligned.m64n56k16.f32.bf16.bf16 {%0, %1, %2, %3, %4, %5, %6, %7, %8, %9, %10, %11, %12, %13, %14, %15, %16, %17, %18, %19, %20, %21, %22, %23, %24, %25, %26, %27}, {%40, %41, %42, %43}, db, 1, 1, 1, 0;\n"
    "wgmma.commit_group.sync.aligned;\n}\n"
    : "+f"(d[0]), "+f"(d[1]), "+f"(d[2]), "+f"(d[3]), "+f"(d[4]), "+f"(d[5]), "+f"(d[6]), "+f"(d[7]), "+f"(d[8]), "+f"(d[9]), "+f"(d[10]), "+f"(d[11]), "+f"(d[12]), "+f"(d[13]), "+f"(d[14]), "+f"(d[15]), "+f"(d[16]), "+f"(d[17]), "+f"(d[18]), "+f"(d[19]), "+f"(d[20]), "+f"(d[21]), "+f"(d[22]), "+f"(d[23]), "+f"(d[24]), "+f"(d[25]), "+f"(d[26]), "+f"(d[27])
    : "r"(a[0]), "r"(a[1]), "r"(a[2]), "r"(a[3]), "r"(a[4]), "r"(a[5]), "r"(a[6]), "r"(a[7]), "r"(a[8]), "r"(a[9]), "r"(a[10]), "r"(a[11]), "r"(a[12]), "r"(a[13]), "r"(a[14]), "r"(a[15]), "l"(db), "n"(D)
    : "memory");
}
template<int D> __device__ __forceinline__ void gemm1(float (&d)[32], const uint32_t (&a)[16], uint64_t db) {
  asm volatile("{\n.reg .b64 db;\n"
    "add.s64 db, %48, %49 + 0;\n"
    "wgmma.mma_async.sync.aligned.m64n64k16.f32.bf16.bf16 {%0, %1, %2, %3, %4, %5, %6, %7, %8, %9, %10, %11, %12, %13, %14, %15, %16, %17, %18, %19, %20, %21, %22, %23, %24, %25, %26, %27, %28, %29, %30, %31}, {%32, %33, %34, %35}, db, 1, 1, 1, 0;\n"
    "add.s64 db, %48, %49 + 2;\n"
    "wgmma.mma_async.sync.aligned.m64n64k16.f32.bf16.bf16 {%0, %1, %2, %3, %4, %5, %6, %7, %8, %9, %10, %11, %12, %13, %14, %15, %16, %17, %18, %19, %20, %21, %22, %23, %24, %25, %26, %27, %28, %29, %30, %31}, {%36, %37, %38, %39}, db, 1, 1, 1, 0;\n"
    "add.s64 db, %48, %49 + 4;\n"
    "wgmma.mma_async.sync.aligned.m64n64k16.f32.bf16.bf16 {%0, %1, %2, %3, %4, %5, %6, %7, %8, %9, %10, %11, %12, %13, %14, %15, %16, %17, %18, %19, %20, %21, %22, %23, %24, %25, %26, %27, %28, %29, %30, %31}, {%40, %41, %42, %43}, db, 1, 1, 1, 0;\n"
    "add.s64 db, %48, %49 + 6;\n"
    "wgmma.mma_async.sync.aligned.m64n64k16.f32.bf16.bf16 {%0, %1, %2, %3, %4, %5, %6, %7, %8, %9, %10, %11, %12, %13, %14, %15, %16, %17, %18, %19, %20, %21, %22, %23, %24, %25, %26, %27, %28, %29, %30, %31}, {%44, %45, %46, %47}, db, 1, 1, 1, 0;\n"
    "wgmma.commit_group.sync.aligned;\n}\n"
    : "+f"(d[0]), "+f"(d[1]), "+f"(d[2]), "+f"(d[3]), "+f"(d[4]), "+f"(d[5]), "+f"(d[6]), "+f"(d[7]), "+f"(d[8]), "+f"(d[9]), "+f"(d[10]), "+f"(d[11]), "+f"(d[12]), "+f"(d[13]), "+f"(d[14]), "+f"(d[15]), "+f"(d[16]), "+f"(d[17]), "+f"(d[18]), "+f"(d[19]), "+f"(d[20]), "+f"(d[21]), "+f"(d[22]), "+f"(d[23]), "+f"(d[24]), "+f"(d[25]), "+f"(d[26]), "+f"(d[27]), "+f"(d[28]), "+f"(d[29]), "+f"(d[30]), "+f"(d[31])
    : "r"(a[0]), "r"(a[1]), "r"(a[2]), "r"(a[3]), "r"(a[4]), "r"(a[5]), "r"(a[6]), "r"(a[7]), "r"(a[8]), "r"(a[9]), "r"(a[10]), "r"(a[11]), "r"(a[12]), "r"(a[13]), "r"(a[14]), "r"(a[15]), "l"(db), "n"(D)
    : "memory");
}
template<int D> __device__ __forceinline__ void gemm1(float (&d)[36], const uint32_t (&a)[16], uint64_t db) {
  asm volatile("{\n.reg .b64 db;\n"
    "add.s64 db, %52, %53 + 0;\n"
    "wgmma.mma_async.sync.aligned.m64n72k16.f32.bf16.bf16 {%0, %1, %2, %3, %4, %5, %6, %7, %8, %9, %10, %11, %12, %13, %14, %15, %16, %17, %18, %19, %20, %21, %22, %23, %24, %25, %26, %27, %28, %29, %30, %31, %32, %33, %34, %35}, {%36, %37, %38, %39}, db, 1, 1, 1, 0;\n"
    "add.s64 db, %52, %53 + 2;\n"
    "wgmma.mma_async.sync.aligned.m64n72k16.f32.bf16.bf16 {%0, %1, %2, %3, %4, %5, %6, %7, %8, %9, %10, %11, %12, %13, %14, %15, %16, %17, %18, %19, %20, %21, %22, %23, %24, %25, %26, %27, %28, %29, %30, %31, %32, %33, %34, %35}, {%40, %41, %42, %43}, db, 1, 1, 1, 0;\n"
    "add.s64 db, %52, %53 + 4;\n"
    "wgmma.mma_async.sync.aligned.m64n72k16.f32.bf16.bf16 {%0, %1, %2, %3, %4, %5, %6, %7, %8, %9, %10, %11, %12, %13, %14, %15, %16, %17, %18, %19, %20, %21, %22, %23, %24, %25, %26, %27, %28, %29, %30, %31, %32, %33, %34, %35}, {%44, %45, %46, %47}, db, 1, 1, 1, 0;\n"
    "add.s64 db, %52, %53 + 6;\n"
    "wgmma.mma_async.sync.aligned.m64n72k16.f32.bf16.bf16 {%0, %1, %2, %3, %4, %5, %6, %7, %8, %9, %10, %11, %12, %13, %14, %15, %16, %17, %18, %19, %20, %21, %22, %23, %24, %25, %26, %27, %28, %29, %30, %31, %32, %33, %34, %35}, {%48, %49, %50, %51}, db, 1, 1, 1, 0;\n"
    "wgmma.commit_group.sync.aligned;\n}\n"
    : "+f"(d[0]), "+f"(d[1]), "+f"(d[2]), "+f"(d[3]), "+f"(d[4]), "+f"(d[5]), "+f"(d[6]), "+f"(d[7]), "+f"(d[8]), "+f"(d[9]), "+f"(d[10]), "+f"(d[11]), "+f"(d[12]), "+f"(d[13]), "+f"(d[14]), "+f"(d[15]), "+f"(d[16]), "+f"(d[17]), "+f"(d[18]), "+f"(d[19]), "+f"(d[20]), "+f"(d[21]), "+f"(d[22]), "+f"(d[23]), "+f"(d[24]), "+f"(d[25]), "+f"(d[26]), "+f"(d[27]), "+f"(d[28]), "+f"(d[29]), "+f"(d[30]), "+f"(d[31]), "+f"(d[32]), "+f"(d[33]), "+f"(d[34]), "+f"(d[35])
    : "r"(a[0]), "r"(a[1]), "r"(a[2]), "r"(a[3]), "r"(a[4]), "r"(a[5]), "r"(a[6]), "r"(a[7]), "r"(a[8]), "r"(a[9]), "r"(a[10]), "r"(a[11]), "r"(a[12]), "r"(a[13]), "r"(a[14]), "r"(a[15]), "l"(db), "n"(D)
    : "memory");
}
template<int D> __device__ __forceinline__ void gemm1(float (&d)[40], const uint32_t (&a)[16], uint64_t db) {
  asm volatile("{\n.reg .b64 db;\n"
    "add.s64 db, %56, %57 + 0;\n"
    "wgmma.mma_async.sync.aligned.m64n80k16.f32.bf16.bf16 {%0, %1, %2, %3, %4, %5, %6, %7, %8, %9, %10, %11, %12, %13, %14, %15, %16, %17, %18, %19, %20, %21, %22, %23, %24, %25, %26, %27, %28, %29, %30, %31, %32, %33, %34, %35, %36, %37, %38, %39}, {%40, %41, %42, %43}, db, 1, 1, 1, 0;\n"
    "add.s64 db, %56, %57 + 2;\n"
    "wgmma.mma_async.sync.aligned.m64n80k16.f32.bf16.bf16 {%0, %1, %2, %3, %4, %5, %6, %7, %8, %9, %10, %11, %12, %13, %14, %15, %16, %17, %18, %19, %20, %21, %22, %23, %24, %25, %26, %27, %28, %29, %30, %31, %32, %33, %34, %35, %36, %37, %38, %39}, {%44, %45, %46, %47}, db, 1, 1, 1, 0;\n"
    "add.s64 db, %56, %57 + 4;\n"
    "wgmma.mma_async.sync.aligned.m64n80k16.f32.bf16.bf16 {%0, %1, %2, %3, %4, %5, %6, %7, %8, %9, %10, %11, %12, %13, %14, %15, %16, %17, %18, %19, %20, %21, %22, %23, %24, %25, %26, %27, %28, %29, %30, %31, %32, %33, %34, %35, %36, %37, %38, %39}, {%48, %49, %50, %51}, db, 1, 1, 1, 0;\n"
    "add.s64 db, %56, %57 + 6;\n"
    "wgmma.mma_async.sync.aligned.m64n80k16.f32.bf16.bf16 {%0, %1, %2, %3, %4, %5, %6, %7, %8, %9, %10, %11, %12, %13, %14, %15, %16, %17, %18, %19, %20, %21, %22, %23, %24, %25, %26, %27, %28, %29, %30, %31, %32, %33, %34, %35, %36, %37, %38, %39}, {%52, %53, %54, %55}, db, 1, 1, 1, 0;\n"
    "wgmma.commit_group.sync.aligned;\n}\n"
    : "+f"(d[0]), "+f"(d[1]), "+f"(d[2]), "+f"(d[3]), "+f"(d[4]), "+f"(d[5]), "+f"(d[6]), "+f"(d[7]), "+f"(d[8]), "+f"(d[9]), "+f"(d[10]), "+f"(d[11]), "+f"(d[12]), "+f"(d[13]), "+f"(d[14]), "+f"(d[15]), "+f"(d[16]), "+f"(d[17]), "+f"(d[18]), "+f"(d[19]), "+f"(d[20]), "+f"(d[21]), "+f"(d[22]), "+f"(d[23]), "+f"(d[24]), "+f"(d[25]), "+f"(d[26]), "+f"(d[27]), "+f"(d[28]), "+f"(d[29]), "+f"(d[30]), "+f"(d[31]), "+f"(d[32]), "+f"(d[33]), "+f"(d[34]), "+f"(d[35]), "+f"(d[36]), "+f"(d[37]), "+f"(d[38]), "+f"(d[39])
    : "r"(a[0]), "r"(a[1]), "r"(a[2]), "r"(a[3]), "r"(a[4]), "r"(a[5]), "r"(a[6]), "r"(a[7]), "r"(a[8]), "r"(a[9]), "r"(a[10]), "r"(a[11]), "r"(a[12]), "r"(a[13]), "r"(a[14]), "r"(a[15]), "l"(db), "n"(D)
    : "memory");
}
template<int D> __device__ __forceinline__ void gemm1(float (&d)[44], const uint32_t (&a)[16], uint64_t db) {
  asm volatile("{\n.reg .b64 db;\n"
    "add.s64 db, %60, %61 + 0;\n"
    "wgmma.mma_async.sync.aligned.m64n88k16.f32.bf16.bf16 {%0, %1, %2, %3, %4, %5, %6, %7, %8, %9, %10, %11, %12, %13, %14, %15, %16, %17, %18, %19, %20, %21, %22, %23, %24, %25, %26, %27, %28, %29, %30, %31, %32, %33, %34, %35, %36, %37, %38, %39, %40, %41, %42, %43}, {%44, %45, %46, %47}, db, 1, 1, 1, 0;\n"
    "add.s64 db, %60, %61 + 2;\n"
    "wgmma.mma_async.sync.aligned.m64n88k16.f32.bf16.bf16 {%0, %1, %2, %3, %4, %5, %6, %7, %8, %9, %10, %11, %12, %13, %14, %15, %16, %17, %18, %19, %20, %21, %22, %23, %24, %25, %26, %27, %28, %29, %30, %31, %32, %33, %34, %35, %36, %37, %38, %39, %40, %41, %42, %43}, {%48, %49, %50, %51}, db, 1, 1, 1, 0;\n"
    "add.s64 db, %60, %61 + 4;\n"
    "wgmma.mma_async.sync.aligned.m64n88k16.f32.bf16.bf16 {%0, %1, %2, %3, %4, %5, %6, %7, %8, %9, %10, %11, %12, %13, %14, %15, %16, %17, %18, %19, %20, %21, %22, %23, %24, %25, %26, %27, %28, %29, %30, %31, %32, %33, %34, %35, %36, %37, %38, %39, %40, %41, %42, %43}, {%52, %53, %54, %55}, db, 1, 1, 1, 0;\n"
    "add.s64 db, %60, %61 + 6;\n"
    "wgmma.mma_async.sync.aligned.m64n88k16.f32.bf16.bf16 {%0, %1, %2, %3, %4, %5, %6, %7, %8, %9, %10, %11, %12, %13, %14, %15, %16, %17, %18, %19, %20, %21, %22, %23, %24, %25, %26, %27, %28, %29, %30, %31, %32, %33, %34, %35, %36, %37, %38, %39, %40, %41, %42, %43}, {%56, %57, %58, %59}, db, 1, 1, 1, 0;\n"
    "wgmma.commit_group.sync.aligned;\n}\n"
    : "+f"(d[0]), "+f"(d[1]), "+f"(d[2]), "+f"(d[3]), "+f"(d[4]), "+f"(d[5]), "+f"(d[6]), "+f"(d[7]), "+f"(d[8]), "+f"(d[9]), "+f"(d[10]), "+f"(d[11]), "+f"(d[12]), "+f"(d[13]), "+f"(d[14]), "+f"(d[15]), "+f"(d[16]), "+f"(d[17]), "+f"(d[18]), "+f"(d[19]), "+f"(d[20]), "+f"(d[21]), "+f"(d[22]), "+f"(d[23]), "+f"(d[24]), "+f"(d[25]), "+f"(d[26]), "+f"(d[27]), "+f"(d[28]), "+f"(d[29]), "+f"(d[30]), "+f"(d[31]), "+f"(d[32]), "+f"(d[33]), "+f"(d[34]), "+f"(d[35]), "+f"(d[36]), "+f"(d[37]), "+f"(d[38]), "+f"(d[39]), "+f"(d[40]), "+f"(d[41]), "+f"(d[42]), "+f"(d[43])
    : "r"(a[0]), "r"(a[1]), "r"(a[2]), "r"(a[3]), "r"(a[4]), "r"(a[5]), "r"(a[6]), "r"(a[7]), "r"(a[8]), "r"(a[9]), "r"(a[10]), "r"(a[11]), "r"(a[12]), "r"(a[13]), "r"(a[14]), "r"(a[15]), "l"(db), "n"(D)
    : "memory");
}
template<int D> __device__ __forceinline__ void bias_out(float (&d)[4], const uint32_t (&a)[16], uint64_t db) {
  asm volatile("{\n.reg .b64 db;\n"
    "add.s64 db, %20, %21 + 0;\n"
    "wgmma.mma_async.sync.aligned.m64n8k16.f32.bf16.bf16 {%0, %1, %2, %3}, {%4, %5, %6, %7}, db, 0, 1, 1, 0;\n"
    "add.s64 db, %20, %21 + 2;\n"
    "wgmma.mma_async.sync.aligned.m64n8k16.f32.bf16.bf16 {%0, %1, %2, %3}, {%8, %9, %10, %11}, db, 1, 1, 1, 0;\n"
    "add.s64 db, %20, %21 + 4;\n"
    "wgmma.mma_async.sync.aligned.m64n8k16.f32.bf16.bf16 {%0, %1, %2, %3}, {%12, %13, %14, %15}, db, 1, 1, 1, 0;\n"
    "add.s64 db, %20, %21 + 6;\n"
    "wgmma.mma_async.sync.aligned.m64n8k16.f32.bf16.bf16 {%0, %1, %2, %3}, {%16, %17, %18, %19}, db, 1, 1, 1, 0;\n"
    "wgmma.commit_group.sync.aligned;\n}\n"
    : "=f"(d[0]), "=f"(d[1]), "=f"(d[2]), "=f"(d[3])
    : "r"(a[0]), "r"(a[1]), "r"(a[2]), "r"(a[3]), "r"(a[4]), "r"(a[5]), "r"(a[6]), "r"(a[7]), "r"(a[8]), "r"(a[9]), "r"(a[10]), "r"(a[11]), "r"(a[12]), "r"(a[13]), "r"(a[14]), "r"(a[15]), "l"(db), "n"(D)
    : "memory");
}
template<int D> __device__ __forceinline__ void gemm2_first(float (&d)[16], const uint32_t (&a)[12], uint64_t db, uint32_t meta) {
  asm volatile("{\n.reg .b64 db;\n"
    "wgmma.fence.sync.aligned;\n"
    "add.s64 db, %28, %29 + 0;\n"
    "wgmma.mma_async.sp.sync.aligned.m64n32k32.f32.bf16.bf16 {%0, %1, %2, %3, %4, %5, %6, %7, %8, %9, %10, %11, %12, %13, %14, %15}, {%16, %17, %18, %19}, db, %30, 0, 0, 1, 1, 1;\n"
    "add.s64 db, %28, %29 + 128;\n"
    "wgmma.mma_async.sp.sync.aligned.m64n32k32.f32.bf16.bf16 {%0, %1, %2, %3, %4, %5, %6, %7, %8, %9, %10, %11, %12, %13, %14, %15}, {%20, %21, %22, %23}, db, %30, 0, 1, 1, 1, 1;\n"
    "add.s64 db, %28, %29 + 256;\n"
    "wgmma.mma_async.sp.sync.aligned.m64n32k32.f32.bf16.bf16 {%0, %1, %2, %3, %4, %5, %6, %7, %8, %9, %10, %11, %12, %13, %14, %15}, {%24, %25, %26, %27}, db, %30, 0, 1, 1, 1, 1;\n"
    "wgmma.commit_group.sync.aligned;\n}\n"
    : "=f"(d[0]), "=f"(d[1]), "=f"(d[2]), "=f"(d[3]), "=f"(d[4]), "=f"(d[5]), "=f"(d[6]), "=f"(d[7]), "=f"(d[8]), "=f"(d[9]), "=f"(d[10]), "=f"(d[11]), "=f"(d[12]), "=f"(d[13]), "=f"(d[14]), "=f"(d[15])
    : "r"(a[0]), "r"(a[1]), "r"(a[2]), "r"(a[3]), "r"(a[4]), "r"(a[5]), "r"(a[6]), "r"(a[7]), "r"(a[8]), "r"(a[9]), "r"(a[10]), "r"(a[11]), "l"(db), "n"(D), "r"(meta)
    : "memory");
}
template<int D> __device__ __forceinline__ void gemm2_first(float (&d)[16], const uint32_t (&a)[16], uint64_t db, uint32_t meta) {
  asm volatile("{\n.reg .b64 db;\n"
    "wgmma.fence.sync.aligned;\n"
    "add.s64 db, %32, %33 + 0;\n"
    "wgmma.mma_async.sp.sync.aligned.m64n32k32.f32.bf16.bf16 {%0, %1, %2, %3, %4, %5, %6, %7, %8, %9, %10, %11, %12, %13, %14, %15}, {%16, %17, %18, %19}, db, %34, 0, 0, 1, 1, 1;\n"
    "add.s64 db, %32, %33 + 128;\n"
    "wgmma.mma_async.sp.sync.aligned.m64n32k32.f32.bf16.bf16 {%0, %1, %2, %3, %4, %5, %6, %7, %8, %9, %10, %11, %12, %13, %14, %15}, {%20, %21, %22, %23}, db, %34, 0, 1, 1, 1, 1;\n"
    "add.s64 db, %32, %33 + 256;\n"
    "wgmma.mma_async.sp.sync.aligned.m64n32k32.f32.bf16.bf16 {%0, %1, %2, %3, %4, %5, %6, %7, %8, %9, %10, %11, %12, %13, %14, %15}, {%24, %25, %26, %27}, db, %34, 0, 1, 1, 1, 1;\n"
    "add.s64 db, %32, %33 + 384;\n"
    "wgmma.mma_async.sp.sync.aligned.m64n32k32.f32.bf16.bf16 {%0, %1, %2, %3, %4, %5, %6, %7, %8, %9, %10, %11, %12, %13, %14, %15}, {%28, %29, %30, %31}, db, %34, 0, 1, 1, 1, 1;\n"
    "wgmma.commit_group.sync.aligned;\n}\n"
    : "=f"(d[0]), "=f"(d[1]), "=f"(d[2]), "=f"(d[3]), "=f"(d[4]), "=f"(d[5]), "=f"(d[6]), "=f"(d[7]), "=f"(d[8]), "=f"(d[9]), "=f"(d[10]), "=f"(d[11]), "=f"(d[12]), "=f"(d[13]), "=f"(d[14]), "=f"(d[15])
    : "r"(a[0]), "r"(a[1]), "r"(a[2]), "r"(a[3]), "r"(a[4]), "r"(a[5]), "r"(a[6]), "r"(a[7]), "r"(a[8]), "r"(a[9]), "r"(a[10]), "r"(a[11]), "r"(a[12]), "r"(a[13]), "r"(a[14]), "r"(a[15]), "l"(db), "n"(D), "r"(meta)
    : "memory");
}
template<int D> __device__ __forceinline__ void gemm2_first(float (&d)[16], const uint32_t (&a)[20], uint64_t db, uint32_t meta) {
  asm volatile("{\n.reg .b64 db;\n"
    "wgmma.fence.sync.aligned;\n"
    "add.s64 db, %36, %37 + 0;\n"
    "wgmma.mma_async.sp.sync.aligned.m64n32k32.f32.bf16.bf16 {%0, %1, %2, %3, %4, %5, %6, %7, %8, %9, %10, %11, %12, %13, %14, %15}, {%16, %17, %18, %19}, db, %38, 0, 0, 1, 1, 1;\n"
    "add.s64 db, %36, %37 + 128;\n"
    "wgmma.mma_async.sp.sync.aligned.m64n32k32.f32.bf16.bf16 {%0, %1, %2, %3, %4, %5, %6, %7, %8, %9, %10, %11, %12, %13, %14, %15}, {%20, %21, %22, %23}, db, %38, 0, 1, 1, 1, 1;\n"
    "add.s64 db, %36, %37 + 256;\n"
    "wgmma.mma_async.sp.sync.aligned.m64n32k32.f32.bf16.bf16 {%0, %1, %2, %3, %4, %5, %6, %7, %8, %9, %10, %11, %12, %13, %14, %15}, {%24, %25, %26, %27}, db, %38, 0, 1, 1, 1, 1;\n"
    "add.s64 db, %36, %37 + 384;\n"
    "wgmma.mma_async.sp.sync.aligned.m64n32k32.f32.bf16.bf16 {%0, %1, %2, %3, %4, %5, %6, %7, %8, %9, %10, %11, %12, %13, %14, %15}, {%28, %29, %30, %31}, db, %38, 0, 1, 1, 1, 1;\n"
    "add.s64 db, %36, %37 + 512;\n"
    "wgmma.mma_async.sp.sync.aligned.m64n32k32.f32.bf16.bf16 {%0, %1, %2, %3, %4, %5, %6, %7, %8, %9, %10, %11, %12, %13, %14, %15}, {%32, %33, %34, %35}, db, %38, 0, 1, 1, 1, 1;\n"
    "wgmma.commit_group.sync.aligned;\n}\n"
    : "=f"(d[0]), "=f"(d[1]), "=f"(d[2]), "=f"(d[3]), "=f"(d[4]), "=f"(d[5]), "=f"(d[6]), "=f"(d[7]), "=f"(d[8]), "=f"(d[9]), "=f"(d[10]), "=f"(d[11]), "=f"(d[12]), "=f"(d[13]), "=f"(d[14]), "=f"(d[15])
    : "r"(a[0]), "r"(a[1]), "r"(a[2]), "r"(a[3]), "r"(a[4]), "r"(a[5]), "r"(a[6]), "r"(a[7]), "r"(a[8]), "r"(a[9]), "r"(a[10]), "r"(a[11]), "r"(a[12]), "r"(a[13]), "r"(a[14]), "r"(a[15]), "r"(a[16]), "r"(a[17]), "r"(a[18]), "r"(a[19]), "l"(db), "n"(D), "r"(meta)
    : "memory");
}
template<int D> __device__ __forceinline__ void gemm2_more(float (&d)[16], const uint32_t (&a)[4], uint64_t db, uint32_t meta) {
  asm volatile("{\n.reg .b64 db;\n"
    "wgmma.fence.sync.aligned;\n"
    "add.s64 db, %20, %21 + 0;\n"
    "wgmma.mma_async.sp.sync.aligned.m64n32k32.f32.bf16.bf16 {%0, %1, %2, %3, %4, %5, %6, %7, %8, %9, %10, %11, %12, %13, %14, %15}, {%16, %17, %18, %19}, db, %22, 0, 1, 1, 1, 1;\n"
    "wgmma.commit_group.sync.aligned;\n}\n"
    : "+f"(d[0]), "+f"(d[1]), "+f"(d[2]), "+f"(d[3]), "+f"(d[4]), "+f"(d[5]), "+f"(d[6]), "+f"(d[7]), "+f"(d[8]), "+f"(d[9]), "+f"(d[10]), "+f"(d[11]), "+f"(d[12]), "+f"(d[13]), "+f"(d[14]), "+f"(d[15])
    : "r"(a[0]), "r"(a[1]), "r"(a[2]), "r"(a[3]), "l"(db), "n"(D), "r"(meta)
    : "memory");
}
template<int D> __device__ __forceinline__ void gemm2_more(float (&d)[16], const uint32_t (&a)[8], uint64_t db, uint32_t meta) {
  asm volatile("{\n.reg .b64 db;\n"
    "wgmma.fence.sync.aligned;\n"
    "add.s64 db, %24, %25 + 0;\n"
    "wgmma.mma_async.sp.sync.aligned.m64n32k32.f32.bf16.bf16 {%0, %1, %2, %3, %4, %5, %6, %7, %8, %9, %10, %11, %12, %13, %14, %15}, {%16, %17, %18, %19}, db, %26, 0, 1, 1, 1, 1;\n"
    "add.s64 db, %24, %25 + 128;\n"
    "wgmma.mma_async.sp.sync.aligned.m64n32k32.f32.bf16.bf16 {%0, %1, %2, %3, %4, %5, %6, %7, %8, %9, %10, %11, %12, %13, %14, %15}, {%20, %21, %22, %23}, db, %26, 0, 1, 1, 1, 1;\n"
    "wgmma.commit_group.sync.aligned;\n}\n"
    : "+f"(d[0]), "+f"(d[1]), "+f"(d[2]), "+f"(d[3]), "+f"(d[4]), "+f"(d[5]), "+f"(d[6]), "+f"(d[7]), "+f"(d[8]), "+f"(d[9]), "+f"(d[10]), "+f"(d[11]), "+f"(d[12]), "+f"(d[13]), "+f"(d[14]), "+f"(d[15])
    : "r"(a[0]), "r"(a[1]), "r"(a[2]), "r"(a[3]), "r"(a[4]), "r"(a[5]), "r"(a[6]), "r"(a[7]), "l"(db), "n"(D), "r"(meta)
    : "memory");
}
template<int D> __device__ __forceinline__ void gemm2_more(float (&d)[16], const uint32_t (&a)[12], uint64_t db, uint32_t meta) {
  asm volatile("{\n.reg .b64 db;\n"
    "wgmma.fence.sync.aligned;\n"
    "add.s64 db, %28, %29 + 0;\n"
    "wgmma.mma_async.sp.sync.aligned.m64n32k32.f32.bf16.bf16 {%0, %1, %2, %3, %4, %5, %6, %7, %8, %9, %10, %11, %12, %13, %14, %15}, {%16, %17, %18, %19}, db, %30, 0, 1, 1, 1, 1;\n"
    "add.s64 db, %28, %29 + 128;\n"
    "wgmma.mma_async.sp.sync.aligned.m64n32k32.f32.bf16.bf16 {%0, %1, %2, %3, %4, %5, %6, %7, %8, %9, %10, %11, %12, %13, %14, %15}, {%20, %21, %22, %23}, db, %30, 0, 1, 1, 1, 1;\n"
    "add.s64 db, %28, %29 + 256;\n"
    "wgmma.mma_async.sp.sync.aligned.m64n32k32.f32.bf16.bf16 {%0, %1, %2, %3, %4, %5, %6, %7, %8, %9, %10, %11, %12, %13, %14, %15}, {%24, %25, %26, %27}, db, %30, 0, 1, 1, 1, 1;\n"
    "wgmma.commit_group.sync.aligned;\n}\n"
    : "+f"(d[0]), "+f"(d[1]), "+f"(d[2]), "+f"(d[3]), "+f"(d[4]), "+f"(d[5]), "+f"(d[6]), "+f"(d[7]), "+f"(d[8]), "+f"(d[9]), "+f"(d[10]), "+f"(d[11]), "+f"(d[12]), "+f"(d[13]), "+f"(d[14]), "+f"(d[15])
    : "r"(a[0]), "r"(a[1]), "r"(a[2]), "r"(a[3]), "r"(a[4]), "r"(a[5]), "r"(a[6]), "r"(a[7]), "r"(a[8]), "r"(a[9]), "r"(a[10]), "r"(a[11]), "l"(db), "n"(D), "r"(meta)
    : "memory");
}
template<int D> __device__ __forceinline__ void gemm2_more(float (&d)[16], const uint32_t (&a)[16], uint64_t db, uint32_t meta) {
  asm volatile("{\n.reg .b64 db;\n"
    "wgmma.fence.sync.aligned;\n"
    "add.s64 db, %32, %33 + 0;\n"
    "wgmma.mma_async.sp.sync.aligned.m64n32k32.f32.bf16.bf16 {%0, %1, %2, %3, %4, %5, %6, %7, %8, %9, %10, %11, %12, %13, %14, %15}, {%16, %17, %18, %19}, db, %34, 0, 1, 1, 1, 1;\n"
    "add.s64 db, %32, %33 + 128;\n"
    "wgmma.mma_async.sp.sync.aligned.m64n32k32.f32.bf16.bf16 {%0, %1, %2, %3, %4, %5, %6, %7, %8, %9, %10, %11, %12, %13, %14, %15}, {%20, %21, %22, %23}, db, %34, 0, 1, 1, 1, 1;\n"
    "add.s64 db, %32, %33 + 256;\n"
    "wgmma.mma_async.sp.sync.aligned.m64n32k32.f32.bf16.bf16 {%0, %1, %2, %3, %4, %5, %6, %7, %8, %9, %10, %11, %12, %13, %14, %15}, {%24, %25, %26, %27}, db, %34, 0, 1, 1, 1, 1;\n"
    "add.s64 db, %32, %33 + 384;\n"
    "wgmma.mma_async.sp.sync.aligned.m64n32k32.f32.bf16.bf16 {%0, %1, %2, %3, %4, %5, %6, %7, %8, %9, %10, %11, %12, %13, %14, %15}, {%28, %29, %30, %31}, db, %34, 0, 1, 1, 1, 1;\n"
    "wgmma.commit_group.sync.aligned;\n}\n"
    : "+f"(d[0]), "+f"(d[1]), "+f"(d[2]), "+f"(d[3]), "+f"(d[4]), "+f"(d[5]), "+f"(d[6]), "+f"(d[7]), "+f"(d[8]), "+f"(d[9]), "+f"(d[10]), "+f"(d[11]), "+f"(d[12]), "+f"(d[13]), "+f"(d[14]), "+f"(d[15])
    : "r"(a[0]), "r"(a[1]), "r"(a[2]), "r"(a[3]), "r"(a[4]), "r"(a[5]), "r"(a[6]), "r"(a[7]), "r"(a[8]), "r"(a[9]), "r"(a[10]), "r"(a[11]), "r"(a[12]), "r"(a[13]), "r"(a[14]), "r"(a[15]), "l"(db), "n"(D), "r"(meta)
    : "memory");
}
template<int N> __device__ __forceinline__ void mma_wait(float (&d)[4]) {
  asm volatile("wgmma.wait_group.sync.aligned %4;"
    : "+f"(d[0]), "+f"(d[1]), "+f"(d[2]), "+f"(d[3])
    : "n"(N) : "memory");
}
template<int N> __device__ __forceinline__ void mma_wait(float (&d)[16]) {
  asm volatile("wgmma.wait_group.sync.aligned %16;"
    : "+f"(d[0]), "+f"(d[1]), "+f"(d[2]), "+f"(d[3]), "+f"(d[4]), "+f"(d[5]), "+f"(d[6]), "+f"(d[7]), "+f"(d[8]), "+f"(d[9]), "+f"(d[10]), "+f"(d[11]), "+f"(d[12]), "+f"(d[13]), "+f"(d[14]), "+f"(d[15])
    : "n"(N) : "memory");
}
template<int N> __device__ __forceinline__ void mma_wait(float (&d)[20]) {
  asm volatile("wgmma.wait_group.sync.aligned %20;"
    : "+f"(d[0]), "+f"(d[1]), "+f"(d[2]), "+f"(d[3]), "+f"(d[4]), "+f"(d[5]), "+f"(d[6]), "+f"(d[7]), "+f"(d[8]), "+f"(d[9]), "+f"(d[10]), "+f"(d[11]), "+f"(d[12]), "+f"(d[13]), "+f"(d[14]), "+f"(d[15]), "+f"(d[16]), "+f"(d[17]), "+f"(d[18]), "+f"(d[19])
    : "n"(N) : "memory");
}
template<int N> __device__ __forceinline__ void mma_wait(float (&d)[28]) {
  asm volatile("wgmma.wait_group.sync.aligned %28;"
    : "+f"(d[0]), "+f"(d[1]), "+f"(d[2]), "+f"(d[3]), "+f"(d[4]), "+f"(d[5]), "+f"(d[6]), "+f"(d[7]), "+f"(d[8]), "+f"(d[9]), "+f"(d[10]), "+f"(d[11]), "+f"(d[12]), "+f"(d[13]), "+f"(d[14]), "+f"(d[15]), "+f"(d[16]), "+f"(d[17]), "+f"(d[18]), "+f"(d[19]), "+f"(d[20]), "+f"(d[21]), "+f"(d[22]), "+f"(d[23]), "+f"(d[24]), "+f"(d[25]), "+f"(d[26]), "+f"(d[27])
    : "n"(N) : "memory");
}
template<int N> __device__ __forceinline__ void mma_wait(float (&d)[32]) {
  asm volatile("wgmma.wait_group.sync.aligned %32;"
    : "+f"(d[0]), "+f"(d[1]), "+f"(d[2]), "+f"(d[3]), "+f"(d[4]), "+f"(d[5]), "+f"(d[6]), "+f"(d[7]), "+f"(d[8]), "+f"(d[9]), "+f"(d[10]), "+f"(d[11]), "+f"(d[12]), "+f"(d[13]), "+f"(d[14]), "+f"(d[15]), "+f"(d[16]), "+f"(d[17]), "+f"(d[18]), "+f"(d[19]), "+f"(d[20]), "+f"(d[21]), "+f"(d[22]), "+f"(d[23]), "+f"(d[24]), "+f"(d[25]), "+f"(d[26]), "+f"(d[27]), "+f"(d[28]), "+f"(d[29]), "+f"(d[30]), "+f"(d[31])
    : "n"(N) : "memory");
}
template<int N> __device__ __forceinline__ void mma_wait(float (&d)[36]) {
  asm volatile("wgmma.wait_group.sync.aligned %36;"
    : "+f"(d[0]), "+f"(d[1]), "+f"(d[2]), "+f"(d[3]), "+f"(d[4]), "+f"(d[5]), "+f"(d[6]), "+f"(d[7]), "+f"(d[8]), "+f"(d[9]), "+f"(d[10]), "+f"(d[11]), "+f"(d[12]), "+f"(d[13]), "+f"(d[14]), "+f"(d[15]), "+f"(d[16]), "+f"(d[17]), "+f"(d[18]), "+f"(d[19]), "+f"(d[20]), "+f"(d[21]), "+f"(d[22]), "+f"(d[23]), "+f"(d[24]), "+f"(d[25]), "+f"(d[26]), "+f"(d[27]), "+f"(d[28]), "+f"(d[29]), "+f"(d[30]), "+f"(d[31]), "+f"(d[32]), "+f"(d[33]), "+f"(d[34]), "+f"(d[35])
    : "n"(N) : "memory");
}
template<int N> __device__ __forceinline__ void mma_wait(float (&d)[40]) {
  asm volatile("wgmma.wait_group.sync.aligned %40;"
    : "+f"(d[0]), "+f"(d[1]), "+f"(d[2]), "+f"(d[3]), "+f"(d[4]), "+f"(d[5]), "+f"(d[6]), "+f"(d[7]), "+f"(d[8]), "+f"(d[9]), "+f"(d[10]), "+f"(d[11]), "+f"(d[12]), "+f"(d[13]), "+f"(d[14]), "+f"(d[15]), "+f"(d[16]), "+f"(d[17]), "+f"(d[18]), "+f"(d[19]), "+f"(d[20]), "+f"(d[21]), "+f"(d[22]), "+f"(d[23]), "+f"(d[24]), "+f"(d[25]), "+f"(d[26]), "+f"(d[27]), "+f"(d[28]), "+f"(d[29]), "+f"(d[30]), "+f"(d[31]), "+f"(d[32]), "+f"(d[33]), "+f"(d[34]), "+f"(d[35]), "+f"(d[36]), "+f"(d[37]), "+f"(d[38]), "+f"(d[39])
    : "n"(N) : "memory");
}
template<int N> __device__ __forceinline__ void mma_wait(float (&d)[44]) {
  asm volatile("wgmma.wait_group.sync.aligned %44;"
    : "+f"(d[0]), "+f"(d[1]), "+f"(d[2]), "+f"(d[3]), "+f"(d[4]), "+f"(d[5]), "+f"(d[6]), "+f"(d[7]), "+f"(d[8]), "+f"(d[9]), "+f"(d[10]), "+f"(d[11]), "+f"(d[12]), "+f"(d[13]), "+f"(d[14]), "+f"(d[15]), "+f"(d[16]), "+f"(d[17]), "+f"(d[18]), "+f"(d[19]), "+f"(d[20]), "+f"(d[21]), "+f"(d[22]), "+f"(d[23]), "+f"(d[24]), "+f"(d[25]), "+f"(d[26]), "+f"(d[27]), "+f"(d[28]), "+f"(d[29]), "+f"(d[30]), "+f"(d[31]), "+f"(d[32]), "+f"(d[33]), "+f"(d[34]), "+f"(d[35]), "+f"(d[36]), "+f"(d[37]), "+f"(d[38]), "+f"(d[39]), "+f"(d[40]), "+f"(d[41]), "+f"(d[42]), "+f"(d[43])
    : "n"(N) : "memory");
}
__device__ __forceinline__ void mma_fence() { asm volatile("wgmma.fence.sync.aligned;" ::: "memory"); }


__device__ __forceinline__ uint32_t smem_u32(const void* p) { return (uint32_t)__cvta_generic_to_shared(p); }

__device__ __forceinline__ void mbar_init(uint32_t bar, uint32_t cnt) {
  asm volatile("mbarrier.init.shared::cta.b64 [%0], %1;" :: "r"(bar), "r"(cnt) : "memory");
}
__device__ __forceinline__ void mbar_arrive(uint32_t bar) {
  asm volatile("mbarrier.arrive.shared::cta.b64 _, [%0];" :: "r"(bar) : "memory");
}
__device__ __forceinline__ void mbar_wait(uint32_t bar, uint32_t parity) {
  asm volatile("{\n.reg .pred p;\n.reg .u32 n;\n"
               "mov.u32 n, 0;\n"
               "WAIT_LOOP:\n"
               "mbarrier.try_wait.parity.shared::cta.b64 p, [%0], %1;\n"
               "@p bra.uni WAIT_DONE;\n"
               "add.u32 n, n, 1;\n"
               "setp.lt.u32 p, n, 0x1000000;\n"
               "@p bra.uni WAIT_LOOP;\n"
               "trap;\n"
               "WAIT_DONE:\n}\n"
               :: "r"(bar), "r"(parity) : "memory");
}
__device__ __forceinline__ void mbar_wait_unless(uint32_t ok, uint32_t bar, uint32_t parity) {
  asm volatile("{\n.reg .pred p;\n.reg .u32 n;\n"
               "setp.ne.u32 p, %2, 0;\n"
               "@p bra.uni WAIT_DONE;\n"
               "mov.u32 n, 0;\n"
               "WAIT_LOOP:\n"
               "mbarrier.try_wait.parity.shared::cta.b64 p, [%0], %1;\n"
               "@p bra.uni WAIT_DONE;\n"
               "add.u32 n, n, 1;\n"
               "setp.lt.u32 p, n, 0x1000000;\n"
               "@p bra.uni WAIT_LOOP;\n"
               "trap;\n"
               "WAIT_DONE:\n}\n"
               :: "r"(bar), "r"(parity), "r"(ok) : "memory");
}
__device__ __forceinline__ uint32_t mbar_test(uint32_t bar, uint32_t parity) {
  uint32_t ok;
  asm volatile("{\n.reg .pred p;\nmbarrier.test_wait.parity.shared::cta.b64 p, [%1], %2;\nselp.u32 %0, 1, 0, p;\n}\n"
               : "=r"(ok) : "r"(bar), "r"(parity) : "memory");
  return ok;
}
__device__ __forceinline__ void cp_async16(uint32_t dst, const void* src) {
  asm volatile("cp.async.cg.shared.global [%0], [%1], 16;" :: "r"(dst), "l"(src) : "memory");
}
#define DIN_ADDR4                                                                        \
  "mov.b64 {x, y}, %0;\ndp4a.u32.u32 x, %8, 0x80, %11;\nmov.b64 %0, {x, y};\n"           \
  "mov.b64 {x, y}, %1;\ndp4a.u32.u32 x, %8, 0x8000, %11;\nmov.b64 %1, {x, y};\n"         \
  "mov.b64 {x, y}, %2;\ndp4a.u32.u32 x, %8, 0x800000, %11;\nmov.b64 %2, {x, y};\n"       \
  "mov.b64 {x, y}, %3;\ndp4a.u32.u32 x, %8, 0x80000000, %11;\nmov.b64 %3, {x, y};\n"
template<int T>
__device__ __forceinline__ void cp_group(const uint32_t (&dst)[4], uint64_t (&a)[4], uint32_t rows4, uint32_t base, uint64_t pol) {
  asm volatile("{\n.reg .u32 x, y;\n" DIN_ADDR4
               "cp.async.cg.shared.global.L2::cache_hint [%4 + %10], [%0], 16, %9;\n"
               "cp.async.cg.shared.global.L2::cache_hint [%5 + %10], [%1], 16, %9;\n"
               "cp.async.cg.shared.global.L2::cache_hint [%6 + %10], [%2], 16, %9;\n"
               "cp.async.cg.shared.global.L2::cache_hint [%7 + %10], [%3], 16, %9;\n}\n"
               : "+l"(a[0]), "+l"(a[1]), "+l"(a[2]), "+l"(a[3])
               : "r"(dst[0]), "r"(dst[1]), "r"(dst[2]), "r"(dst[3]), "r"(rows4), "l"(pol), "n"(T * 2048), "r"(base) : "memory");
}
template<int T>
__device__ __forceinline__ void cp_group_z(const uint32_t (&dst)[4], uint64_t (&a)[4], uint32_t rows4, uint32_t base, int left, uint64_t pol) {
  asm volatile("{\n.reg .u32 x, y;\n.reg .pred p0, p1, p2, p3;\n" DIN_ADDR4
               "setp.le.s32 p0, %12, %13;\nsetp.le.s32 p1, %12, %13 + 1;\nsetp.le.s32 p2, %12, %13 + 2;\nsetp.le.s32 p3, %12, %13 + 3;\n"
               "cp.async.cg.shared.global.L2::cache_hint [%4 + %10], [%0], 16, p0, %9;\n"
               "cp.async.cg.shared.global.L2::cache_hint [%5 + %10], [%1], 16, p1, %9;\n"
               "cp.async.cg.shared.global.L2::cache_hint [%6 + %10], [%2], 16, p2, %9;\n"
               "cp.async.cg.shared.global.L2::cache_hint [%7 + %10], [%3], 16, p3, %9;\n}\n"
               : "+l"(a[0]), "+l"(a[1]), "+l"(a[2]), "+l"(a[3])
               : "r"(dst[0]), "r"(dst[1]), "r"(dst[2]), "r"(dst[3]), "r"(rows4), "l"(pol), "n"(T * 2048), "r"(base),
                 "r"(left), "n"(T * 16) : "memory");
}
__device__ __forceinline__ void wait_for(uint32_t t, uint32_t most) {
  asm volatile("{\n.reg .u32 c;\n.reg .pred p;\n"
               "SPIN:\n"
               "mov.u32 c, %%globaltimer_lo;\n"
               "sub.u32 c, c, %0;\n"
               "setp.gt.u32 p, c, %1;\n"
               "@p bra.uni SPIN;\n}\n" :: "r"(t), "r"(~most) : "memory");
}
template<int T, int SH>
__device__ __forceinline__ void cp_group_m(const uint32_t (&dst)[4], uint64_t (&a)[4], uint32_t rows4, uint32_t base, uint32_t have, uint32_t go, uint64_t pol) {
  asm volatile("{\n.reg .u32 x, y;\n.reg .pred p0, p1, p2, p3, g;\n" DIN_ADDR4
               "setp.ne.u32 g, %14, 0;\n"
               "and.b32 x, %12, 1 << %13;\nsetp.eq.u32 p0, x, 0;\nand.b32 x, %12, 2 << %13;\nsetp.eq.u32 p1, x, 0;\n"
               "and.b32 x, %12, 4 << %13;\nsetp.eq.u32 p2, x, 0;\nand.b32 x, %12, 8 << %13;\nsetp.eq.u32 p3, x, 0;\n"
               "@g cp.async.cg.shared.global.L2::cache_hint [%4 + %10], [%0], 16, p0, %9;\n"
               "@g cp.async.cg.shared.global.L2::cache_hint [%5 + %10], [%1], 16, p1, %9;\n"
               "@g cp.async.cg.shared.global.L2::cache_hint [%6 + %10], [%2], 16, p2, %9;\n"
               "@g cp.async.cg.shared.global.L2::cache_hint [%7 + %10], [%3], 16, p3, %9;\n}\n"
               : "+l"(a[0]), "+l"(a[1]), "+l"(a[2]), "+l"(a[3])
               : "r"(dst[0]), "r"(dst[1]), "r"(dst[2]), "r"(dst[3]), "r"(rows4), "l"(pol), "n"(T * 2048), "r"(base),
                 "r"(have), "n"(SH), "r"(go) : "memory");
}
__device__ __forceinline__ uint32_t prmt(uint32_t a, uint32_t b, uint32_t sel) {
  uint32_t d;
  asm("prmt.b32 %0, %1, %2, %3;" : "=r"(d) : "r"(a), "r"(b), "r"(sel));
  return d;
}
__device__ __forceinline__ uint32_t ballot_bit(uint32_t x, uint32_t bit) {
  uint32_t d;
  asm volatile("{\n.reg .pred p;\n.reg .u32 t;\nand.b32 t, %1, %2;\nsetp.ne.u32 p, t, 0;\nvote.sync.ballot.b32 %0, p, 0xffffffff;\n}\n"
               : "=r"(d) : "r"(x), "r"(bit));
  return d;
}
__device__ __forceinline__ uint4 load_mask(const void* mask, uint32_t b, uint32_t i) {
  uint4 m;
  asm volatile("ld.global.nc.L1::no_allocate.v4.u32 {%0,%1,%2,%3}, [%4];"
               : "=r"(m.x), "=r"(m.y), "=r"(m.z), "=r"(m.w) : "l"(reinterpret_cast<const uint4*>(mask) + (b * 25u + i)));
  return m;
}
__device__ __forceinline__ uint32_t nonzero_as_one(uint32_t x) {
  uint32_t d;
  asm("set.neu.bf16x2.bf16x2 %0, %1, %2;" : "=r"(d) : "r"(x), "r"(0u));
  return d;
}
__device__ __forceinline__ void cp_async_arrive_noinc(uint32_t bar) {
  asm volatile("cp.async.mbarrier.arrive.noinc.shared::cta.b64 [%0];" :: "r"(bar) : "memory");
}
__device__ __forceinline__ void ldsm_x4(uint32_t addr, uint32_t& r0, uint32_t& r1, uint32_t& r2, uint32_t& r3) {
  asm volatile("ldmatrix.sync.aligned.m8n8.x4.shared.b16 {%0,%1,%2,%3}, [%4];"
               : "=r"(r0), "=r"(r1), "=r"(r2), "=r"(r3) : "r"(addr) : "memory");
}
__device__ __forceinline__ void ldsm_x4_t(uint32_t addr, uint32_t& r0, uint32_t& r1, uint32_t& r2, uint32_t& r3) {
  asm volatile("ldmatrix.sync.aligned.m8n8.x4.trans.shared.b16 {%0,%1,%2,%3}, [%4];"
               : "=r"(r0), "=r"(r1), "=r"(r2), "=r"(r3) : "r"(addr) : "memory");
}
__device__ __forceinline__ void stsm_x4(uint32_t addr, uint32_t r0, uint32_t r1, uint32_t r2, uint32_t r3) {
  asm volatile("stmatrix.sync.aligned.m8n8.x4.shared.b16 [%0], {%1,%2,%3,%4};"
               :: "r"(addr), "r"(r0), "r"(r1), "r"(r2), "r"(r3) : "memory");
}
__device__ __forceinline__ void stsm_x2(uint32_t addr, uint32_t r0, uint32_t r1) {
  asm volatile("stmatrix.sync.aligned.m8n8.x2.shared.b16 [%0], {%1,%2};"
               :: "r"(addr), "r"(r0), "r"(r1) : "memory");
}
__device__ __forceinline__ void mma_bf16(float (&c)[4], const uint32_t (&a)[4], uint32_t b) {
  asm("mma.sync.aligned.m16n8k16.row.col.f32.bf16.bf16.f32 {%0,%1,%2,%3}, {%4,%5,%6,%7}, {%8,%8}, {%0,%1,%2,%3};"
      : "+f"(c[0]), "+f"(c[1]), "+f"(c[2]), "+f"(c[3]) : "r"(a[0]), "r"(a[1]), "r"(a[2]), "r"(a[3]), "r"(b));
}
__device__ __forceinline__ uint32_t hfma2_bf16(uint32_t a, uint32_t b, uint32_t c) {
  uint32_t d;
  asm volatile("fma.rn.bf16x2 %0, %1, %2, %3;" : "=r"(d) : "r"(a), "r"(b), "r"(c));
  return d;
}
__device__ __forceinline__ uint32_t pack_bf16(float lo, float hi) {
  uint32_t d;
  asm("cvt.rn.bf16x2.f32 %0, %1, %2;" : "=r"(d) : "f"(hi), "f"(lo));
  return d;
}
__device__ __forceinline__ uint32_t lds32(uint32_t a) {
  uint32_t v; asm volatile("ld.shared.u32 %0, [%1];" : "=r"(v) : "r"(a) : "memory"); return v;
}
__device__ __forceinline__ uint32_t lds16(uint32_t a) {
  uint32_t v; asm volatile("ld.shared.u16 %0, [%1];" : "=r"(v) : "r"(a) : "memory"); return v;
}
__device__ __forceinline__ void sts32(uint32_t a, uint32_t v) {
  asm volatile("st.shared.u32 [%0], %1;" :: "r"(a), "r"(v) : "memory");
}
__device__ __forceinline__ void sts16(uint32_t a, uint32_t v) {
  asm volatile("st.shared.u16 [%0], %1;" :: "r"(a), "h"((unsigned short)v) : "memory");
}
__device__ __forceinline__ void sts8(uint32_t a, uint32_t v) {
  asm volatile("st.shared.u8 [%0], %1;" :: "r"(a), "r"(v) : "memory");
}
constexpr uint32_t DESC_ROWS = 0x40000040u, DESC_HALVES = 0x80000020u;
__device__ __forceinline__ uint32_t desc_lo(uint32_t addr) { return ((addr & 0x3FFFF) >> 4) | (1u << 16); }

__device__ __forceinline__ uint4 lds128(uint32_t a) {
  uint4 v;
  asm volatile("ld.shared.v4.u32 {%0,%1,%2,%3}, [%4];" : "=r"(v.x), "=r"(v.y), "=r"(v.z), "=r"(v.w) : "r"(a) : "memory");
  return v;
}
__device__ __forceinline__ void sts128(uint32_t a, uint4 v) {
  asm volatile("st.shared.v4.u32 [%0], {%1,%2,%3,%4};" :: "r"(a), "r"(v.x), "r"(v.y), "r"(v.z), "r"(v.w) : "memory");
}
__device__ __forceinline__ void prefetch_l2(const void* p, uint32_t bytes) {
  asm volatile("cp.async.bulk.prefetch.L2.global [%0], %1;" :: "l"(p), "r"(bytes) : "memory");
}

__device__ __forceinline__ void prefetch_piece(const void* p, uint32_t bytes) {
  asm volatile("{\n.reg .u32 t, c;\n.reg .u64 a;\nmov.u32 t, %%tid.x;\nmov.u32 c, %%ctaid.x;\n"
               "mad.lo.u32 c, c, %2, t;\nmad.wide.u32 a, c, %1, %0;\nprefetch.global.L2 [a];\n}\n"
               :: "l"(p), "r"(bytes), "n"(NTHREADS) : "memory");
}

template<int ND>
__device__ __forceinline__ void tanh_range(float (&d)[ND], int i0, int i1) {
#pragma unroll
  for (int i = i0; i < i1; i++) asm volatile("tanh.approx.f32 %0, %0;" : "+f"(d[i ^ 2]));
}
template<int ND>
__device__ __forceinline__ uint32_t mix(const float (&d)[ND], int i, float w2a, float w2b, float c32) {
  uint32_t p;
  asm volatile("{\n.reg .f32 x, y;\nfma.rn.f32 x, %3, %6, %7;\nfma.rn.f32 y, %4, %6, %7;\n"
               "fma.rn.f32 x, %1, %5, x;\nfma.rn.f32 y, %2, %5, y;\ncvt.rn.bf16x2.f32 %0, y, x;\n}\n"
               : "=r"(p) : "f"(d[4 * i]), "f"(d[4 * i + 1]), "f"(d[4 * i + 2]), "f"(d[4 * i + 3]), "f"(w2a), "f"(w2b), "f"(c32));
  return p;
}
__device__ __forceinline__ uint32_t size_bit(int n) { return n > 120 ? H_16 : H_12 << (max(n - 89, 0) >> 3); }
template<int V> struct Int { static constexpr int value = V; };

__global__ void __launch_bounds__(NTHREADS, 1)
din_kernel(const __nv_bfloat16* __restrict__ mask, const __nv_bfloat16* __restrict__ target, int B, int grid,
           uint32_t pf_mask, uint32_t pf_tgt, const __nv_bfloat16* __restrict__ w1, const __nv_bfloat16* __restrict__ hist,
           const __nv_bfloat16* __restrict__ b1, const __nv_bfloat16* __restrict__ w2,
           const __nv_bfloat16* __restrict__ b2, __nv_bfloat16* __restrict__ out, unsigned int* counter, int pace,
           int slow_from, int pace_slow, int spread) {
  prefetch_piece(mask, pf_mask);
  asm volatile("{\n.reg .pred p;\n.reg .u32 c;\nmov.u32 c, %%clock;\nsetp.eq.u32 p, c, %0;\n@p nanosleep.u32 1;\n}\n" :: "n"(0) : "memory");
  prefetch_piece(target, pf_tgt);
  extern __shared__ unsigned char smem_raw[];
  const uint32_t sb = (smem_u32(smem_raw) + 1023u) & ~1023u;
  const int tid = threadIdx.x, lane = tid & 31;
  const int warp = __shfl_sync(0xffffffffu, tid >> 5, 0);
#define ACT NCW
  const int bstep = ACT * grid;

  if (warp < NCW * 4) {
    const int wg = warp >> 2, w = warp & 3;
    const int g = lane >> 2;
    const uint32_t ring = sb + wg * RING_BYTES;
    const bool active = wg * grid + (int)blockIdx.x < B && wg < ACT;
    {
      const int t = tid & 127;
      const uint32_t dst = sb + ((t ^ ((t >> 3) & 7)) << 4);
      const char* src = reinterpret_cast<const char*>(w1) + t * 16;
#pragma unroll
      for (int i = 0; i < 4; i++) cp_async16(dst + w1_at(i) + wg * 2048, src + i * 8192 + wg * 2048);
      cp_async16(dst + w1_at(0) + (wg >> 1) * RING_BYTES + (wg & 1) * SLOT_BYTES + 6144, src + wg * 8192 + 6144);
      if (wg == 0) cp_async16(dst + w1_at(3) + 6144, src + 3 * 8192 + 6144);
      if (lane < 8) {
        if (w == 0 && active) cp_async16(ring + R_TGT0 + lane * 16, target + (size_t)(wg * grid + blockIdx.x) * kD + lane * 8);
        if (w == 1 && wg < 2) cp_async16(ring + R_VEC + lane * 16, (wg ? w2 : b1) + lane * 8);
      }
    }
    if (w == 2) sts32(ring + R_SEL + lane * 4, 0x3f803f80u);
    uint32_t rb2;
    asm volatile("ld.global.nc.u16 %0, [%1];" : "=r"(rb2) : "l"(b2));
    asm volatile("setmaxnreg.inc.sync.aligned.u32 %0;" :: "n"(CONS_REGS));
    asm volatile("cp.async.wait_all;" ::: "memory");
    asm volatile("bar.sync 1, %0;" :: "n"(NCW * 160) : "memory");
    const uint32_t half2 = 0x3f003f00u, nhalf2 = 0xbf00bf00u, nzero2 = 0x80008000u;
    const uint32_t vec = sb + R_VEC + (16 * w + g) * 2;
    const float w2a = 0.5f * __uint_as_float(lds16(vec + RING_BYTES) << 16);
    const float w2b = 0.5f * __uint_as_float(lds16(vec + RING_BYTES + 16) << 16);
    const uint32_t rw2 = lds32(sb + RING_BYTES + R_VEC + lane * 4);
    float c32 = __uint_as_float(rw2 << 16) + __uint_as_float(rw2 & 0xffff0000u);
#pragma unroll
    for (int o = 16; o; o >>= 1) c32 += __shfl_xor_sync(0xffffffffu, c32, o);
    c32 = (0.5f * c32 + __uint_as_float(rb2 << 16)) * (1.0f / 32.0f);
    uint32_t bq[4];
    bq[2] = hfma2_bf16(lds16(vec), half2, nzero2);
    bq[3] = hfma2_bf16(lds16(vec + 16), half2, nzero2);
    if (lane & 3) bq[2] = bq[3] = 0;
    uint32_t wac[16], wd[16], wbc[16];
    {
      const int mi = lane >> 3, rr = lane & 7;
      const uint32_t a0 = sb + (8 * (mi >> 1) + rr) * 128 + (((2 * w + (mi & 1)) ^ rr) << 4);
#pragma unroll
      for (int ks = 0; ks < 4; ks++) {
        uint32_t A[4], Bm[4], C[4], Dm[4];
        ldsm_x4_t(a0 + ks * 2048 + w1_at(0), A[0], A[1], A[2], A[3]);
        ldsm_x4_t(a0 + ks * 2048 + w1_at(1), Bm[0], Bm[1], Bm[2], Bm[3]);
        ldsm_x4_t(a0 + ks * 2048 + w1_at(2), C[0], C[1], C[2], C[3]);
        ldsm_x4_t(a0 + ks * 2048 + w1_at(3), Dm[0], Dm[1], Dm[2], Dm[3]);
#pragma unroll
        for (int e = 0; e < 4; e++) {
          wac[4 * ks + e] = hfma2_bf16(A[e], half2, hfma2_bf16(C[e], half2, nzero2));
          wbc[4 * ks + e] = hfma2_bf16(Bm[e], half2, hfma2_bf16(C[e], nhalf2, nzero2));
          wd[4 * ks + e] = hfma2_bf16(Dm[e], half2, nzero2);
        }
      }
    }
    asm volatile("fence.proxy.async.shared::cta;" ::: "memory");
    asm volatile("bar.sync 5, %0;" :: "n"(NCW * 128) : "memory");

    const uint32_t ln = __shfl_sync(0xffffffffu, lane, lane);
    const uint32_t q0 = __shfl_sync(0xffffffffu, (lane & 3) ? 0u : 0xffffffffu, lane);
    const uint32_t meta = __shfl_sync(0xffffffffu, 0x88dddd88u + (grid >> 20), lane);
    const uint32_t zr = grid >> 20;
    const uint32_t sel = (ring + R_SEL) >> 4;
    const uint32_t ost = __shfl_sync(0xffffffffu, (lane >> 4) * 1024 + w * 256 + (lane & 15) * 16, lane);
    const uint32_t first = ring;
    const uint32_t last = first + (NSLOT - 1) * SLOT_BYTES;
    uint32_t sa = first, phase = 0;
    uint32_t we[16];
    auto make_weff = [&](uint32_t ta) {
      uint32_t t[8];
      ta += (ln & 24) << 1;
      ldsm_x4(ta, t[0], t[1], t[2], t[3]);
      ldsm_x4(ta + 64, t[4], t[5], t[6], t[7]);
#pragma unroll
      for (int i = 0; i < 16; i++) we[i] = hfma2_bf16(t[i >> 1], wd[i], wac[i]);
    };
    auto make_bq = [&](const float (&bz)[4]) {
#pragma unroll
      for (int e = 0; e < 2; e++) {
        const uint32_t v = __float_as_uint(bz[2 * e]) & q0;
        const float hi = __uint_as_float(v & 0xffff0000u);
        bq[e] = pack_bf16(__uint_as_float(v) - hi, hi);
      }
    };
    if (active) {
      {
        float bz[4];
        uint64_t d0 = (uint64_t)DESC_ROWS << 32 | (ring + R_TGT0) >> 4;
        mma_fence();
        bias_out<0>(bz, wbc, d0);
        make_weff(ring + R_TGT0);
        mma_wait<0>(bz);
        make_bq(bz);
      }
      uint32_t raw = 0, cur, hdr;
      uint32_t full = 0;
      auto finish = [&]() {
        asm volatile("bar.sync %0, 128;" :: "r"(2 + wg) : "memory");
        const uint32_t ra = cur + S_OUT + w * 1024 + ln * 16;
        uint32_t f0[4], f1[4];
        ldsm_x4_t(ra, f0[0], f0[1], f0[2], f0[3]);
        ldsm_x4_t(ra + 512, f1[0], f1[1], f1[2], f1[3]);
        uint32_t* dst = reinterpret_cast<uint32_t*>(out) + (lds32(first + R_STOP + 4) + 4 * w + (ln & 4) * 4 + (ln >> 3));
        float c0[4] = {0.f, 0.f, 0.f, 0.f}, c1[4] = {0.f, 0.f, 0.f, 0.f};
        mma_bf16(c0, f0, 0x3f803f80u);
        mma_bf16(c1, f1, 0x3f803f80u);
        *dst = pack_bf16(c0[0] + c1[0], c0[2] + c1[2]);
      };
      auto chunk = [&](auto groups) {
        constexpr int N8 = decltype(groups)::value, NY = N8 - NA;
        constexpr int KT = (N8 + 1) / 2, E1 = KT - (N8 == 16 ? 3 : KL), E0 = N8 < 16 && K0 < E1 ? K0 : E1;
        float x[4 * NA], y[4 * NY], bz[4], o[16];
        uint32_t a[4 * E0], a1[E1 > E0 ? 4 * (E1 - E0) : 4], a2[4 * (KT - E1)];
        auto M = [&](int i0, int i1) {
#pragma unroll
          for (int i = i0; i < i1; i++) {
            uint32_t p = i < NA ? mix(x, i, w2a, w2b, c32) : i < N8 ? mix(y, i - NA, w2a, w2b, c32) : 0;
            if (N8 == 16) {
              uint32_t m = 0x3f803f80u;
              asm volatile("{\n.reg .pred p;\nsetp.ne.u32 p, %1, 0;\n@p ld.shared.u32 %0, [%2];\n}\n"
                           : "+r"(m) : "r"(hdr & H_GENERAL), "r"(cur + S_MASK + i * 16 + (ln & 3) * 4) : "memory");
              p = hfma2_bf16(p, m, 0x80008000u);
            }
            if (i < 2 * E0) a[2 * i] = a[2 * i + 1] = p;
            else if (i < 2 * E1) a1[2 * i - 4 * E0] = a1[2 * i - 4 * E0 + 1] = p;
            else a2[2 * i - 4 * E1] = a2[2 * i - 4 * E1 + 1] = p;
          }
        };
        auto header = [&]() {
          raw = lds32(sa + S_HDR);
          raw = (raw >> 31) == phase ? 0 : raw;
        };
        const uint32_t sta = cur + S_OUT + ost;
        uint64_t db = (uint64_t)(DESC_ROWS + (cur >> 24)) << 32 | cur >> 4;
        const uint32_t par = phase;
        phase ^= sa == last;
        sa = sa == last ? first : sa + SLOT_BYTES;
        mma_fence();
        bias_in(x, bq, sel);
        bias_in(y, bq, sel);
        mbar_wait_unless(full, cur + S_FULL, par);
        mma_fence();
        gemm1<0>(x, we, db);
        bias_out<S_TGT / 16>(bz, wbc, db);
        mma_wait<1>(x);
        const uint32_t there = mbar_test(cur + S_REST, par);
        tanh_range(x, 0, 4 * SA);
        mbar_wait_unless(there, cur + S_REST, par);
        mma_fence();
        gemm1<64 * NA>(y, we, db);
        tanh_range(x, 4 * SA, 4 * (SA + SB));
        if (__builtin_expect(zr != 0, 0)) {
          __nanosleep(zr);
#pragma unroll
          for (int i = 4 * (SA + SB); i < 4 * NA; i++) asm volatile("mov.b32 %0, %1;" : "=f"(x[i]) : "r"(ln));
        }
        tanh_range(x, 4 * (SA + SB), 4 * NA);
        M(0, NA - 1);
        if (__builtin_expect(zr != 0, 0)) {
          __nanosleep(zr);
#pragma unroll
          for (int i = 0; i < NA - 1; i++) sts32(zr + i, a[2 * i]);
#pragma unroll
          for (int i = 4 * NA - 4; i < 4 * NA; i++) sts32(zr + i, __float_as_uint(x[i]));
        }
        mma_wait<0>(y);
        asm volatile("" : "+f"(bz[0]), "+f"(bz[2]) :: "memory");
        header();
        tanh_range(y, 0, 4 * (2 * E0 - NA));
        make_weff(cur + S_TGT);
        M(NA - 1, 2 * E0);
        auto after = [&](uint32_t g, uint32_t u, auto more) {
          asm volatile("{\n.reg .b32 lo, hi, z;\n.reg .pred p;\nand.b32 z, %1, %2;\nsetp.ne.u32 p, z, 0;\nvote.sync.ballot.b32 z, p, 0xffffffff;\n"
                       "and.b32 z, z, %4;\nmov.b64 {lo, hi}, %0;\nadd.u32 hi, hi, %3;\nadd.u32 hi, hi, z;\nmov.b64 %0, {lo, hi};\n}\n"
                       : "+l"(db) : "r"(g), "r"(zr), "n"(decltype(more)::value), "r"(u));
        };
        constexpr bool TWO = E1 == E0;
        make_bq(bz);
        raw = __shfl_sync(0xffffffffu, raw, 0);
        after(a[4 * E0 - 2] | a[4 * E0 - 4] | (TWO ? bq[0] | bq[1] | sta : 0), TWO ? raw : ~0u, Int<(int)(DESC_HALVES - DESC_ROWS)>());
        gemm2_first<0>(o, a, db, meta);
        if constexpr (E1 > E0) {
          tanh_range(y, 4 * (2 * E0 - NA), 4 * (2 * E1 - NA));
          M(2 * E0, 2 * E1);
          after(bq[0] | bq[1] | sta, raw, Int<0>());
          gemm2_more<128 * E0>(o, a1, db, meta);
        }
        tanh_range(y, 4 * (2 * E1 - NA), 4 * NY);
        M(2 * E1, 2 * KT);
        gemm2_more<128 * E1>(o, a2, db, meta);
        full = mbar_test(sa + S_FULL, phase);
        mma_wait<0>(o);
#pragma unroll
        for (int j = 0; j < 2; j++)
          stsm_x4(sta + j * 2048, pack_bf16(o[8 * j], o[8 * j + 2]), pack_bf16(o[8 * j + 1], o[8 * j + 3]),
                  pack_bf16(o[8 * j + 4], o[8 * j + 6]), pack_bf16(o[8 * j + 5], o[8 * j + 7]));
        __syncwarp();
        asm volatile("{\n.reg .pred p;\nsetp.eq.u32 p, %1, 0;\n@p mbarrier.arrive.shared::cta.b64 _, [%0];\n}\n"
                     :: "r"(cur + S_EMPTY), "r"(ln | (hdr & H_FINAL)) : "memory");
      };
      while (true) {
        hdr = __shfl_sync(0xffffffffu, raw, 0);
        cur = sa;
        if (hdr & H_13) { chunk(Int<13>()); if (hdr & H_FINAL) break; }
        else if (hdr & H_12) { chunk(Int<12>()); if (hdr & H_FINAL) break; }
        else if (hdr & H_14) { chunk(Int<14>()); if (hdr & H_FINAL) break; }
        else if (hdr & H_15) { chunk(Int<15>()); if (hdr & H_FINAL) break; }
        else if (hdr & H_STOP) return;
        else if (hdr) { chunk(Int<16>()); if (hdr & H_FINAL) break; }
        else {
          asm volatile("{\n.reg .pred p;\n.reg .u32 n, t;\nmov.u32 n, 0;\n"
                       "AGAIN:\nnanosleep.u32 32;\nld.shared.u32 %0, [%1];\nshfl.sync.idx.b32 %0, %0, 0, 31, 0xffffffff;\n"
                       "shr.u32 t, %0, 31;\nsetp.ne.u32 p, t, %2;\n@p bra.uni THERE;\n"
                       "add.u32 n, n, 1;\nsetp.lt.u32 p, n, 0x1000000;\n@p bra.uni AGAIN;\ntrap;\nTHERE:\n}\n"
                       : "=r"(raw) : "r"(sa + S_HDR), "r"(phase) : "memory");
        }
      }
      finish();
    }
  } else {
    const int pw = warp - NCW * 4;
    const uint32_t ring = sb + pw * RING_BYTES;
    asm volatile("setmaxnreg.dec.sync.aligned.u32 %0;" :: "n"(PROD_REGS));
    if (pw < NCW) {
      int b = pw * grid + blockIdx.x, bn = b + bstep;
      uint4 mw = load_mask(mask, min(b, B - 1), min(lane, 24));
      if (lane == 0) {
#pragma unroll
        for (int i = 0; i < NSLOT; i++) {
          mbar_init(ring + i * SLOT_BYTES + S_FULL, 33);
          mbar_init(ring + i * SLOT_BYTES + S_REST, 33);
          mbar_arrive(ring + i * SLOT_BYTES + S_REST);
          mbar_init(ring + i * SLOT_BYTES + S_EMPTY, 4);
          sts32(ring + i * SLOT_BYTES + S_HDR, 0);
        }
        sts32(ring + R_STOP, b < B && pw < ACT ? 0 : ring);
      }
      sts32(sb + R_PACE + lane * 4, 0);
      asm volatile("bar.arrive 1, %0;" :: "n"(NCW * 160) : "memory");
      asm volatile("bar.arrive 6, 128;" ::: "memory");
      if (pw >= ACT) return;
      const uint32_t list = ring + R_LIST;
      uint32_t lt;
      asm("mov.u32 %0, %%lanemask_lt;" : "=r"(lt));
      const uint32_t ln = __shfl_sync(0xffffffffu, lane, lane);
      const uint32_t r4 = (ln >> 3) * 4, c16 = (ln & 7) * 16, l25 = min(ln, 24u);
      const uint32_t pick = ln < 25 ? 0xeca8 : 0x9999;
      uint32_t dst[4];
#pragma unroll
      for (int i = 0; i < 4; i++) dst[i] = ring + (r4 + i) * 128 + (c16 ^ (((r4 + i) & 7) << 4));
      uint64_t pol;
      asm("createpolicy.fractional.L2::evict_first.b64 %0, 1.0;" : "=l"(pol));
      uint32_t sa = ring, phase = 1;
      const uint32_t wrap = (uint32_t)(max(B - NSTATIC * bstep, 0) + bstep - 1);
      auto next_slot = [&]() {
        const bool wrapped = sa == ring + (NSLOT - 1) * SLOT_BYTES;
        const int step = wrapped ? -(NSLOT - 1) * SLOT_BYTES : SLOT_BYTES;
        sa += step;
        phase ^= wrapped;
#pragma unroll
        for (int i = 0; i < 4; i++) dst[i] += step;
      };
      uint32_t claimer = ln;
      uint32_t drawn, started = 0;
      int mean16 = 0;
      auto draw = [&]() {
        drawn = B;
        asm volatile("{\n.reg .pred p;\nsetp.eq.u32 p, %3, 0;\n@p atom.global.inc.u32 %0, [%1], %2;\n}\n"
                     : "+r"(drawn) : "l"(counter), "r"(wrap), "r"(claimer) : "memory");
      };
      if (b >= B) draw();
      while (b < B) {
        const uint32_t e0 = nonzero_as_one(mw.x), e1 = nonzero_as_one(mw.y);
        const uint32_t e2 = nonzero_as_one(mw.z), e3 = nonzero_as_one(mw.w);
        const uint32_t nonbin = (e0 ^ mw.x) | (e1 ^ mw.y) | (e2 ^ mw.z) | (e3 ^ mw.w);
        const uint32_t sA = prmt(e0, e1, pick), sB = prmt(e2, e3, pick);
        const uint32_t pA = (sA & 0x01010101u) * 0x01010101u;
        const uint32_t pB = ((sB & 0x01010101u) + (pA >> 24)) * 0x01010101u;
        uint32_t pos = 0;
        int n = 0;
#pragma unroll
        for (int k = 0; k < 4; k++) {
          const uint32_t bal = ballot_bit(pB, 0x01000000u << k);
          pos += __popc(bal & lt) << k;
          n += __popc(bal) << k;
        }
        const uint32_t general = __any_sync(0xffffffffu, nonbin != 0);
        const uint32_t aA = (pA + pos * 0x01010101u) | ~sA, aB = (pB + pos * 0x01010101u) | ~sB;
#pragma unroll
        for (int i = 0; i < 8; i++) sts8(list - 1 + prmt(i < 4 ? aA : aB, 0, 0x4440 + (i & 3)), 8 * ln + i);
        __syncwarp();

        const uint64_t src = reinterpret_cast<uint64_t>(hist) + (uint64_t)b * (kL * kD * 2);
        const bool no_carry = (uint32_t)src <= 0xffffffffu - kL * kD * 2;
        auto begin_fill = [&](uint32_t h, uint32_t part, int nc, int bt, auto extra) {
          mbar_wait(sa + S_EMPTY, phase);
          if (bt >= B && !part) h |= H_FINAL;
          asm volatile("{\n.reg .pred p;\nsetp.ne.u32 p, %3, 0;\n@p st.shared.v2.u32 [%0], {%1, %2};\n}\n"
                       :: "r"(ring + R_STOP), "r"(sa + (phase ^ 1)), "r"(b * 32), "r"(h & H_FINAL) : "memory");
          extra();
          sts32(sa + S_HDR, h | phase << 31);
          sts32(sa + S_ROW + phase * 4, b | part);
          asm volatile("{\n.reg .pred p;\nsetp.eq.u32 p, %1, 0;\n@p mbarrier.arrive.shared::cta.b64 _, [%0];\n}\n"
                       :: "r"(sa + S_FULL), "r"(ln) : "memory");
          mean16 = mean16 == 0 ? 16 * nc : bn >= slow_from ? mean16 : mean16 + nc - (mean16 >> 4);
          asm volatile("{\n.reg .u32 c;\n"
                       "mov.u32 c, %%globaltimer_lo;\n"
                       "red.shared.max.u32 [%1], c;\n"
                       "atom.shared.add.u32 %0, [%1], %2;\n}\n"
                       : "=r"(started) : "r"(sb + R_PACE + ln * 4),
                         "r"(bn >= slow_from ? mean16 * pace_slow >> 8 : nc * pace >> 4) : "memory");
          started = __shfl_sync(0xffffffffu, started, 0);
          if (!(part & ROW_REST)) mw = load_mask(mask, min(bn, B - 1), l25);
          wait_for(started, pace * (CHUNK / 4));
          if (!(part & ROW_REST)) draw();
          asm volatile("cp.async.ca.shared.global [%0], [%1], 4;"
                       :: "r"(sa + S_TGT + ln * 4), "l"(reinterpret_cast<const uint32_t*>(target) + ((uint32_t)min(bt, B - 1) * 32u + ln)) : "memory");
        };
        auto end_fill = [&](int nc) {
          cp_async_arrive_noinc(sa + S_REST);
          next_slot();
        };
        const uint32_t base = (uint32_t)src + c16;
        uint64_t a[4];
        a[0] = a[1] = a[2] = a[3] = (uint64_t)((uint32_t)(src >> 32) + (ln >> 5)) << 32;
        if (__builtin_expect(no_carry && !general && n >= 80 && n <= CHUNK, 1)) {
          uint32_t idx[7];
#pragma unroll
          for (int t = 0; t < 7; t++) idx[t] = lds32(list + r4 + t * 16);
          uint32_t have;
          asm("bmsk.clamp.b32 %0, 0, %1;" : "=r"(have) : "r"(max(n - 80 - (int)r4, 0)));
          begin_fill(size_bit(n), 0, n, bn, [](){});
          cp_group<0>(dst, a, idx[0], base, pol);
          cp_group<1>(dst, a, idx[1], base, pol);
          cp_group<2>(dst, a, idx[2], base, pol);
          cp_async_arrive_noinc(sa + S_FULL);
          if (bn >= slow_from) wait_for(started + spread, spread);
          cp_group<3>(dst, a, idx[3], base, pol);
          cp_group<4>(dst, a, idx[4], base, pol);
          cp_group_m<5, 0>(dst, a, idx[5], base, have, 1, pol);
          cp_group_m<6, 16>(dst, a, idx[6], base, have, n > 96, pol);
          if (n > 112) cp_group_z<7>(dst, a, lds32(list + r4 + 112), base, n - r4, pol);
          end_fill(n);
        } else if (no_carry && !general) {
          int nc = n <= CHUNK ? n : n <= 160 ? 64 : 96;
          uint32_t la = list + r4, part = n <= CHUNK ? 0 : ROW_MORE;
#pragma unroll 1
          while (true) {
            begin_fill(size_bit(nc), part, nc, part == ROW_MORE ? b : bn, [](){});
            const int left = nc - r4;
            cp_group_z<0>(dst, a, lds32(la), base, left, pol);
            cp_group_z<1>(dst, a, lds32(la + 16), base, left, pol);
            cp_group_z<2>(dst, a, lds32(la + 32), base, left, pol);
            cp_async_arrive_noinc(sa + S_FULL);
            if (bn >= slow_from) wait_for(started + spread, spread);
            cp_group_z<3>(dst, a, lds32(la + 48), base, left, pol);
            cp_group_z<4>(dst, a, lds32(la + 64), base, left, pol);
            cp_group_z<5>(dst, a, lds32(la + 80), base, left, pol);
            cp_group_z<6>(dst, a, lds32(la + 96), base, left, pol);
            cp_group_z<7>(dst, a, lds32(la + 112), base, left, pol);
            end_fill(nc);
            if (part != ROW_MORE) break;
            la += nc;
            nc = n - nc;
            part = ROW_REST;
          }
        } else {
          int r0 = 0;
#pragma unroll 1
          do {
            const int nc = min(n - r0, CHUNK);
            const bool more = r0 + CHUNK < n;
            begin_fill(general ? H_GENERAL : H_16, (more ? ROW_MORE : 0u) | (r0 ? ROW_REST : 0u), nc, more ? b : bn, [&]() {
#pragma unroll 1
              for (int z = ln; general && z < CHUNK; z += 32) {
                uint32_t v = 0;
                if (z < nc) {
                  uint32_t row;
                  asm volatile("ld.shared.u8 %0, [%1];" : "=r"(row) : "r"(list + r0 + z) : "memory");
                  v = __bfloat16_as_ushort(mask[(size_t)b * kL + row]);
                }
                sts16(sa + S_MASK + z * 2, v);
              }
              __syncwarp();
            });
#pragma unroll 1
            for (int z = r4 >> 2; z < CHUNK; z += 4) {
              uint32_t row;
              asm volatile("ld.shared.u8 %0, [%1];" : "=r"(row) : "r"(list + r0 + z) : "memory");
              asm volatile("cp.async.cg.shared.global [%0], [%1], 16, %2;"
                           :: "r"(sa + z * 128 + (c16 ^ ((z & 7) << 4))), "l"(src + c16 + (z < nc ? row : 0) * 128),
                              "r"(z < nc ? 16 : 0) : "memory");
            }
            cp_async_arrive_noinc(sa + S_FULL);
            end_fill(nc);
            r0 += CHUNK;
          } while (r0 < n);
        }
        b = bn;
        bn = __shfl_sync(0xffffffffu, drawn, 0) + NSTATIC * bstep;
        if (bn >= B) claimer = 1;
      }
      if (lds32(ring + R_STOP) == 0) {
        mbar_wait(sa + S_EMPTY, phase);
        sts32(sa + S_HDR, H_STOP | phase << 31);
        sts32(ring + R_STOP, sa + (phase ^ 1));
      }
      asm volatile("cp.async.wait_all;" ::: "memory");
    } else {
      uint32_t due = clock();
      int s0 = NSTATIC * bstep + (PF_EARLY * grid + blockIdx.x) * PF_ROWS;
      auto prefetch = [&]() {
        const int cnt = min(PF_ROWS, B - s0);
        if (lane == 0) {
          prefetch_l2(mask + (size_t)s0 * kL, cnt * kL * 2);
          prefetch_l2(target + (size_t)s0 * kD, cnt * kD * 2);
        }
        s0 += grid * PF_ROWS;
      };
#pragma unroll 1
      for (int j = PF_EARLY; j < PF_FAST && s0 < B; j++) {
        while ((int)(due - (uint32_t)clock()) > 0) {}
        prefetch();
        due += PF_CYCLES;
      }
      due += (PF_FAST - 1) * PF_SLOW - (PF_FAST - PF_EARLY) * PF_CYCLES + (blockIdx.x & 255) * (PF_SLOW / 256);
      asm volatile("bar.sync 6, 128;" ::: "memory");
      const uint32_t ln = __shfl_sync(0xffffffffu, lane, lane);
      const uint32_t home = sb + min(ln, NCW - 1u) * RING_BYTES;
      uint32_t mine = ln < NCW ? home : 0;
      const uint32_t word = __shfl_sync(0xffffffffu, (lane & 4) * 4 + (lane & 3) * 4 + (lane >> 3), lane);
      uint32_t idle = 0, r = 0, at;
      auto poll = [&]() {
        uint32_t ready;
        asm volatile("{\n.reg .pred p;\nsetp.ne.u32 p, %3, 0;\n@p mbarrier.test_wait.parity.shared::cta.b64 p, [%1], %2;\n"
                     "vote.sync.ballot.b32 %0, p, 0xffffffff;\n}\n"
                     : "=r"(ready) : "r"((mine & ~1u) + S_EMPTY), "r"(mine & 1), "r"(mine) : "memory");
        static_assert(NCW == 3, "");
        const uint32_t pick = ((r == 0 ? 0x5a53u : r == 1 ? 0xaa13u : 0x1213u) >> (2 * ready)) & 3;
        at = __shfl_sync(0xffffffffu, mine, pick);
        r = ready ? pick : r;
      };
      poll();
#pragma unroll 1
      while (true) {
        if (at) {
          const uint32_t sa = at & ~1u, carry = sb + r * RING_BYTES + R_CARRY + ln * 8;
          uint32_t f[8][4];
#pragma unroll
          for (int i = 0; i < 8; i++) ldsm_x4_t(sa + S_OUT + ln * 16 + (i >> 2) * 512 + (i & 3) * 1024, f[i][0], f[i][1], f[i][2], f[i][3]);
          const uint32_t row = lds32(sa + S_ROW + 4 - (at & 1) * 4);
          if (ln == r) mine = sa == home + (NSLOT - 1) * SLOT_BYTES ? (at - (NSLOT - 1) * SLOT_BYTES) ^ 1 : at + SLOT_BYTES;
          float c[8][4];
#pragma unroll
          for (int i = 0; i < 8; i++) {
            c[i][0] = c[i][1] = c[i][2] = c[i][3] = 0.f;
            mma_bf16(c[i], f[i], 0x3f803f80u);
          }
          poll();
          asm volatile("{\n.reg .pred p;\nsetp.eq.u32 p, %1, 0;\n@p mbarrier.arrive.shared::cta.b64 _, [%0];\n}\n"
                       :: "r"(sa + S_REST), "r"(ln) : "memory");
          float e[2];
#pragma unroll
          for (int k = 0; k < 2; k++) {
            const float u0 = ln & 1 ? c[1][2 * k] : c[0][2 * k], u1 = ln & 1 ? c[3][2 * k] : c[2][2 * k];
            const float u2 = ln & 1 ? c[5][2 * k] : c[4][2 * k], u3 = ln & 1 ? c[7][2 * k] : c[6][2 * k];
            e[k] = ln & 2 ? u1 + u3 : u0 + u2;
          }
          asm volatile("{\n.reg .pred p, q;\n.reg .f32 a, b;\n.reg .u32 t;\nshr.u32 t, %3, 30;\nsetp.eq.u32 p, t, 1;\nsetp.eq.u32 q, t, 2;\n"
                       "@p ld.shared.v2.f32 {a, b}, [%2];\n@p add.f32 %0, %0, a;\n@p add.f32 %1, %1, b;\n@q st.shared.v2.f32 [%2], {%0, %1};\n}\n"
                       : "+f"(e[0]), "+f"(e[1]) : "r"(carry), "r"(row) : "memory");
          asm volatile("{\n.reg .pred p;\nsetp.ge.s32 p, %2, 0;\n@p st.global.u32 [%0], %1;\n}\n"
                       :: "l"(reinterpret_cast<uint32_t*>(out) + (row * 32u + word)), "r"(pack_bf16(e[0], e[1])), "r"(row) : "memory");
        } else {
          const uint32_t stop = lds32(home + R_STOP);
          poll();
          if (stop == mine) mine = 0;
          if (!__any_sync(0xffffffffu, mine)) break;
          if (s0 < B) {
            if ((int)(due - (uint32_t)clock()) <= 0) { prefetch(); due += PF_SLOW; }
          } else if (++idle > 0x10000000) __trap();
        }
      }
    }
  }
}

}

extern "C" void kernel_launch(void* const* d_in, const int* in_sizes, int n_in, void* d_out, int out_size) {
  const __nv_bfloat16* target = (const __nv_bfloat16*)d_in[0];
  const __nv_bfloat16* hist = (const __nv_bfloat16*)d_in[1];
  const __nv_bfloat16* mask = (const __nv_bfloat16*)d_in[2];
  const __nv_bfloat16* w1 = (const __nv_bfloat16*)d_in[3];
  const __nv_bfloat16* b1 = (const __nv_bfloat16*)d_in[4];
  const __nv_bfloat16* w2 = (const __nv_bfloat16*)d_in[5];
  const __nv_bfloat16* b2 = (const __nv_bfloat16*)d_in[6];
  const int B = in_sizes[0] / din::kD;
  if (B <= 0) return;
  static int sms = 0, pace = 0;
  static unsigned int* counter = nullptr;
  if (sms == 0) {
    int dev = 0, khz = 0, bits = 0;
    cudaGetDevice(&dev);
    cudaDeviceGetAttribute(&sms, cudaDevAttrMultiProcessorCount, dev);
    cudaDeviceGetAttribute(&khz, cudaDevAttrMemoryClockRate, dev);
    cudaDeviceGetAttribute(&bits, cudaDevAttrGlobalMemoryBusWidth, dev);
    if (khz > 0 && bits > 0) pace = (int)(16.0 * 128.0 * sms / (khz * 1e-6 * 2.0 * bits / 8.0));
    if (pace > 256) pace = 0;
    cudaGetSymbolAddress((void**)&counter, din::g_next);
    cudaFuncSetAttribute(din::din_kernel, cudaFuncAttributeMaxDynamicSharedMemorySize, din::SMEM_BYTES);
  }
  const long long early = (long long)(din::NSTATIC * NCW + PF_EARLY * PF_ROWS) * sms, threads = (long long)din::NTHREADS * sms;
  long long pf_mask = (early * din::kL * 2 + threads - 1) / threads, pf_tgt = (early * din::kD * 2 + threads - 1) / threads;
  if (pf_mask > (long long)B * din::kL * 2 / threads) pf_mask = (long long)B * din::kL * 2 / threads;
  if (pf_tgt > (long long)B * din::kD * 2 / threads) pf_tgt = (long long)B * din::kD * 2 / threads;
  din::din_kernel<<<sms, din::NTHREADS, din::SMEM_BYTES>>>(mask, target, B, sms, (uint32_t)pf_mask, (uint32_t)pf_tgt,
                                                          w1, hist, b1, w2, b2, (__nv_bfloat16*)d_out, counter, pace,
                                                          B - SLOW_ROUNDS * NCW * sms / 2, pace + (pace * SLOW_BY + 40) / 80,
                                                          pace * SPREAD / 16);
}
```

```cpp
#include <cuda_runtime.h>
#include <cuda_bf16.h>
#include <stdint.h>

namespace din {

constexpr int kL = 200, kD = 64;
#define NCW 3
#define NSLOT 3
constexpr int CHUNK = 128;
constexpr int NTHREADS = NCW * 128 + 128;
constexpr int PROD_REGS = 56, CONS_REGS = 152;
#define PF_ROWS 8
#define PF_EARLY 3
#define PF_FAST 10
#define PF_CYCLES 280
#define PF_SLOW 2000
#define SLOW_ROUNDS 12
#define SLOW_BY 17
#define SPREAD 55
#define ALIGN 30
#define SA 2
#define SB 1
#define K0 3
#define KL 2
constexpr int NSTATIC = 2;
constexpr int S_TGT = CHUNK * 128;
constexpr int S_HDR = S_TGT + 128;
constexpr int S_FULL = S_HDR + 8;
constexpr int S_EMPTY = S_HDR + 16;
constexpr int S_ROW = S_HDR + 24;
constexpr int S_REST = S_HDR + 32;
constexpr int S_MASK = S_TGT + 256;
constexpr int S_OUT = S_TGT + 1024;
constexpr int SLOT_BYTES = S_OUT + 8192;
constexpr int RING_BYTES_ = NSLOT * SLOT_BYTES;
constexpr int R_PACE = 2 * RING_BYTES_ + S_TGT + 768;
constexpr int R_STOP = S_HDR + 40;
constexpr int R_ADJ = S_HDR + 48;
constexpr int R_LIST = S_TGT + 512;
constexpr int R_VEC = S_TGT + 768;
constexpr int R_SEL = S_TGT + 896;
constexpr int R_CARRY = SLOT_BYTES + S_TGT + 512;
constexpr int R_TGT0 = (NSLOT - 1) * SLOT_BYTES + S_OUT;
constexpr int RING_BYTES = NSLOT * SLOT_BYTES;
constexpr int SMEM_BYTES = NCW * RING_BYTES + 1024;
__device__ constexpr int w1_at(int i) { return (i >> 1) * RING_BYTES + (i & 1) * SLOT_BYTES + S_OUT; }
static_assert(SMEM_BYTES <= 232448, "shared memory");
constexpr uint32_t H_12 = 2, H_13 = 4, H_14 = 8, H_15 = 16, H_16 = 1u << 16;
constexpr uint32_t H_GENERAL = 1u << 17, H_FINAL = 1u << 18, H_STOP = 1u << 19;
constexpr uint32_t ROW_REST = 1u << 30, ROW_MORE = 1u << 31;

__device__ unsigned int g_next;


constexpr int NA = 5;
__device__ __forceinline__ void bias_in(float (&d)[20], const uint32_t (&a)[4], uint32_t lo) {
  asm volatile("{\n.reg .b64 db;\n"
    "cvt.u64.u32 db, %24;\n"
    "wgmma.mma_async.sync.aligned.m64n40k16.f32.bf16.bf16 {%0, %1, %2, %3, %4, %5, %6, %7, %8, %9, %10, %11, %12, %13, %14, %15, %16, %17, %18, %19}, {%20, %21, %22, %23}, db, 0, 1, 1, 0;\n}\n"
    : "=f"(d[0]), "=f"(d[1]), "=f"(d[2]), "=f"(d[3]), "=f"(d[4]), "=f"(d[5]), "=f"(d[6]), "=f"(d[7]), "=f"(d[8]), "=f"(d[9]), "=f"(d[10]), "=f"(d[11]), "=f"(d[12]), "=f"(d[13]), "=f"(d[14]), "=f"(d[15]), "=f"(d[16]), "=f"(d[17]), "=f"(d[18]), "=f"(d[19])
    : "r"(a[0]), "r"(a[1]), "r"(a[2]), "r"(a[3]), "r"(lo)
    : "memory");
}
__device__ __forceinline__ void bias_in(float (&d)[28], const uint32_t (&a)[4], uint32_t lo) {
  asm volatile("{\n.reg .b64 db;\n"
    "cvt.u64.u32 db, %32;\n"
    "wgmma.mma_async.sync.aligned.m64n56k16.f32.bf16.bf16 {%0, %1, %2, %3, %4, %5, %6, %7, %8, %9, %10, %11, %12, %13, %14, %15, %16, %17, %18, %19, %20, %21, %22, %23, %24, %25, %26, %27}, {%28, %29, %30, %31}, db, 0, 1, 1, 0;\n}\n"
    : "=f"(d[0]), "=f"(d[1]), "=f"(d[2]), "=f"(d[3]), "=f"(d[4]), "=f"(d[5]), "=f"(d[6]), "=f"(d[7]), "=f"(d[8]), "=f"(d[9]), "=f"(d[10]), "=f"(d[11]), "=f"(d[12]), "=f"(d[13]), "=f"(d[14]), "=f"(d[15]), "=f"(d[16]), "=f"(d[17]), "=f"(d[18]), "=f"(d[19]), "=f"(d[20]), "=f"(d[21]), "=f"(d[22]), "=f"(d[23]), "=f"(d[24]), "=f"(d[25]), "=f"(d[26]), "=f"(d[27])
    : "r"(a[0]), "r"(a[1]), "r"(a[2]), "r"(a[3]), "r"(lo)
    : "memory");
}
__device__ __forceinline__ void bias_in(float (&d)[32], const uint32_t (&a)[4], uint32_t lo) {
  asm volatile("{\n.reg .b64 db;\n"
    "cvt.u64.u32 db, %36;\n"
    "wgmma.mma_async.sync.aligned.m64n64k16.f32.bf16.bf16 {%0, %1, %2, %3, %4, %5, %6, %7, %8, %9, %10, %11, %12, %13, %14, %15, %16, %17, %18, %19, %20, %21, %22, %23, %24, %25, %26, %27, %28, %29, %30, %31}, {%32, %33, %34, %35}, db, 0, 1, 1, 0;\n}\n"
    : "=f"(d[0]), "=f"(d[1]), "=f"(d[2]), "=f"(d[3]), "=f"(d[4]), "=f"(d[5]), "=f"(d[6]), "=f"(d[7]), "=f"(d[8]), "=f"(d[9]), "=f"(d[10]), "=f"(d[11]), "=f"(d[12]), "=f"(d[13]), "=f"(d[14]), "=f"(d[15]), "=f"(d[16]), "=f"(d[17]), "=f"(d[18]), "=f"(d[19]), "=f"(d[20]), "=f"(d[21]), "=f"(d[22]), "=f"(d[23]), "=f"(d[24]), "=f"(d[25]), "=f"(d[26]), "=f"(d[27]), "=f"(d[28]), "=f"(d[29]), "=f"(d[30]), "=f"(d[31])
    : "r"(a[0]), "r"(a[1]), "r"(a[2]), "r"(a[3]), "r"(lo)
    : "memory");
}
__device__ __forceinline__ void bias_in(float (&d)[36], const uint32_t (&a)[4], uint32_t lo) {
  asm volatile("{\n.reg .b64 db;\n"
    "cvt.u64.u32 db, %40;\n"
    "wgmma.mma_async.sync.aligned.m64n72k16.f32.bf16.bf16 {%0, %1, %2, %3, %4, %5, %6, %7, %8, %9, %10, %11, %12, %13, %14, %15, %16, %17, %18, %19, %20, %21, %22, %23, %24, %25, %26, %27, %28, %29, %30, %31, %32, %33, %34, %35}, {%36, %37, %38, %39}, db, 0, 1, 1, 0;\n}\n"
    : "=f"(d[0]), "=f"(d[1]), "=f"(d[2]), "=f"(d[3]), "=f"(d[4]), "=f"(d[5]), "=f"(d[6]), "=f"(d[7]), "=f"(d[8]), "=f"(d[9]), "=f"(d[10]), "=f"(d[11]), "=f"(d[12]), "=f"(d[13]), "=f"(d[14]), "=f"(d[15]), "=f"(d[16]), "=f"(d[17]), "=f"(d[18]), "=f"(d[19]), "=f"(d[20]), "=f"(d[21]), "=f"(d[22]), "=f"(d[23]), "=f"(d[24]), "=f"(d[25]), "=f"(d[26]), "=f"(d[27]), "=f"(d[28]), "=f"(d[29]), "=f"(d[30]), "=f"(d[31]), "=f"(d[32]), "=f"(d[33]), "=f"(d[34]), "=f"(d[35])
    : "r"(a[0]), "r"(a[1]), "r"(a[2]), "r"(a[3]), "r"(lo)
    : "memory");
}
__device__ __forceinline__ void bias_in(float (&d)[40], const uint32_t (&a)[4], uint32_t lo) {
  asm volatile("{\n.reg .b64 db;\n"
    "cvt.u64.u32 db, %44;\n"
    "wgmma.mma_async.sync.aligned.m64n80k16.f32.bf16.bf16 {%0, %1, %2, %3, %4, %5, %6, %7, %8, %9, %10, %11, %12, %13, %14, %15, %16, %17, %18, %19, %20, %21, %22, %23, %24, %25, %26, %27, %28, %29, %30, %31, %32, %33, %34, %35, %36, %37, %38, %39}, {%40, %41, %42, %43}, db, 0, 1, 1, 0;\n}\n"
    : "=f"(d[0]), "=f"(d[1]), "=f"(d[2]), "=f"(d[3]), "=f"(d[4]), "=f"(d[5]), "=f"(d[6]), "=f"(d[7]), "=f"(d[8]), "=f"(d[9]), "=f"(d[10]), "=f"(d[11]), "=f"(d[12]), "=f"(d[13]), "=f"(d[14]), "=f"(d[15]), "=f"(d[16]), "=f"(d[17]), "=f"(d[18]), "=f"(d[19]), "=f"(d[20]), "=f"(d[21]), "=f"(d[22]), "=f"(d[23]), "=f"(d[24]), "=f"(d[25]), "=f"(d[26]), "=f"(d[27]), "=f"(d[28]), "=f"(d[29]), "=f"(d[30]), "=f"(d[31]), "=f"(d[32]), "=f"(d[33]), "=f"(d[34]), "=f"(d[35]), "=f"(d[36]), "=f"(d[37]), "=f"(d[38]), "=f"(d[39])
    : "r"(a[0]), "r"(a[1]), "r"(a[2]), "r"(a[3]), "r"(lo)
    : "memory");
}
__device__ __forceinline__ void bias_in(float (&d)[44], const uint32_t (&a)[4], uint32_t lo) {
  asm volatile("{\n.reg .b64 db;\n"
    "cvt.u64.u32 db, %48;\n"
    "wgmma.mma_async.sync.aligned.m64n88k16.f32.bf16.bf16 {%0, %1, %2, %3, %4, %5, %6, %7, %8, %9, %10, %11, %12, %13, %14, %15, %16, %17, %18, %19, %20, %21, %22, %23, %24, %25, %26, %27, %28, %29, %30, %31, %32, %33, %34, %35, %36, %37, %38, %39, %40, %41, %42, %43}, {%44, %45, %46, %47}, db, 0, 1, 1, 0;\n}\n"
    : "=f"(d[0]), "=f"(d[1]), "=f"(d[2]), "=f"(d[3]), "=f"(d[4]), "=f"(d[5]), "=f"(d[6]), "=f"(d[7]), "=f"(d[8]), "=f"(d[9]), "=f"(d[10]), "=f"(d[11]), "=f"(d[12]), "=f"(d[13]), "=f"(d[14]), "=f"(d[15]), "=f"(d[16]), "=f"(d[17]), "=f"(d[18]), "=f"(d[19]), "=f"(d[20]), "=f"(d[21]), "=f"(d[22]), "=f"(d[23]), "=f"(d[24]), "=f"(d[25]), "=f"(d[26]), "=f"(d[27]), "=f"(d[28]), "=f"(d[29]), "=f"(d[30]), "=f"(d[31]), "=f"(d[32]), "=f"(d[33]), "=f"(d[34]), "=f"(d[35]), "=f"(d[36]), "=f"(d[37]), "=f"(d[38]), "=f"(d[39]), "=f"(d[40]), "=f"(d[41]), "=f"(d[42]), "=f"(d[43])
    : "r"(a[0]), "r"(a[1]), "r"(a[2]), "r"(a[3]), "r"(lo)
    : "memory");
}
template<int D> __device__ __forceinline__ void gemm1(float (&d)[20], const uint32_t (&a)[16], uint64_t db) {
  asm volatile("{\n.reg .b64 db;\n"
    "add.s64 db, %36, %37 + 0;\n"
    "wgmma.mma_async.sync.aligned.m64n40k16.f32.bf16.bf16 {%0, %1, %2, %3, %4, %5, %6, %7, %8, %9, %10, %11, %12, %13, %14, %15, %16, %17, %18, %19}, {%20, %21, %22, %23}, db, 1, 1, 1, 0;\n"
    "add.s64 db, %36, %37 + 2;\n"
    "wgmma.mma_async.sync.aligned.m64n40k16.f32.bf16.bf16 {%0, %1, %2, %3, %4, %5, %6, %7, %8, %9, %10, %11, %12, %13, %14, %15, %16, %17, %18, %19}, {%24, %25, %26, %27}, db, 1, 1, 1, 0;\n"
    "add.s64 db, %36, %37 + 4;\n"
    "wgmma.mma_async.sync.aligned.m64n40k16.f32.bf16.bf16 {%0, %1, %2, %3, %4, %5, %6, %7, %8, %9, %10, %11, %12, %13, %14, %15, %16, %17, %18, %19}, {%28, %29, %30, %31}, db, 1, 1, 1, 0;\n"
    "add.s64 db, %36, %37 + 6;\n"
    "wgmma.mma_async.sync.aligned.m64n40k16.f32.bf16.bf16 {%0, %1, %2, %3, %4, %5, %6, %7, %8, %9, %10, %11, %12, %13, %14, %15, %16, %17, %18, %19}, {%32, %33, %34, %35}, db, 1, 1, 1, 0;\n"
    "wgmma.commit_group.sync.aligned;\n}\n"
    : "+f"(d[0]), "+f"(d[1]), "+f"(d[2]), "+f"(d[3]), "+f"(d[4]), "+f"(d[5]), "+f"(d[6]), "+f"(d[7]), "+f"(d[8]), "+f"(d[9]), "+f"(d[10]), "+f"(d[11]), "+f"(d[12]), "+f"(d[13]), "+f"(d[14]), "+f"(d[15]), "+f"(d[16]), "+f"(d[17]), "+f"(d[18]), "+f"(d[19])
    : "r"(a[0]), "r"(a[1]), "r"(a[2]), "r"(a[3]), "r"(a[4]), "r"(a[5]), "r"(a[6]), "r"(a[7]), "r"(a[8]), "r"(a[9]), "r"(a[10]), "r"(a[11]), "r"(a[12]), "r"(a[13]), "r"(a[14]), "r"(a[15]), "l"(db), "n"(D)
    : "memory");
}
template<int D> __device__ __forceinline__ void gemm1(float (&d)[28], const uint32_t (&a)[16], uint64_t db) {
  asm volatile("{\n.reg .b64 db;\n"
    "add.s64 db, %44, %45 + 0;\n"
    "wgmma.mma_async.sync.aligned.m64n56k16.f32.bf16.bf16 {%0, %1, %2, %3, %4, %5, %6, %7, %8, %9, %10, %11, %12, %13, %14, %15, %16, %17, %18, %19, %20, %21, %22, %23, %24, %25, %26, %27}, {%28, %29, %30, %31}, db, 1, 1, 1, 0;\n"
    "add.s64 db, %44, %45 + 2;\n"
    "wgmma.mma_async.sync.aligned.m64n56k16.f32.bf16.bf16 {%0, %1, %2, %3, %4, %5, %6, %7, %8, %9, %10, %11, %12, %13, %14, %15, %16, %17, %18, %19, %20, %21, %22, %23, %24, %25, %26, %27}, {%32, %33, %34, %35}, db, 1, 1, 1, 0;\n"
    "add.s64 db, %44, %45 + 4;\n"
    "wgmma.mma_async.sync.aligned.m64n56k16.f32.bf16.bf16 {%0, %1, %2, %3, %4, %5, %6, %7, %8, %9, %10, %11, %12, %13, %14, %15, %16, %17, %18, %19, %20, %21, %22, %23, %24, %25, %26, %27}, {%36, %37, %38, %39}, db, 1, 1, 1, 0;\n"
    "add.s64 db, %44, %45 + 6;\n"
    "wgmma.mma_async.sync.aligned.m64n56k16.f32.bf16.bf16 {%0, %1, %2, %3, %4, %5, %6, %7, %8, %9, %10, %11, %12, %13, %14, %15, %16, %17, %18, %19, %20, %21, %22, %23, %24, %25, %26, %27}, {%40, %41, %42, %43}, db, 1, 1, 1, 0;\n"
    "wgmma.commit_group.sync.aligned;\n}\n"
    : "+f"(d[0]), "+f"(d[1]), "+f"(d[2]), "+f"(d[3]), "+f"(d[4]), "+f"(d[5]), "+f"(d[6]), "+f"(d[7]), "+f"(d[8]), "+f"(d[9]), "+f"(d[10]), "+f"(d[11]), "+f"(d[12]), "+f"(d[13]), "+f"(d[14]), "+f"(d[15]), "+f"(d[16]), "+f"(d[17]), "+f"(d[18]), "+f"(d[19]), "+f"(d[20]), "+f"(d[21]), "+f"(d[22]), "+f"(d[23]), "+f"(d[24]), "+f"(d[25]), "+f"(d[26]), "+f"(d[27])
    : "r"(a[0]), "r"(a[1]), "r"(a[2]), "r"(a[3]), "r"(a[4]), "r"(a[5]), "r"(a[6]), "r"(a[7]), "r"(a[8]), "r"(a[9]), "r"(a[10]), "r"(a[11]), "r"(a[12]), "r"(a[13]), "r"(a[14]), "r"(a[15]), "l"(db), "n"(D)
    : "memory");
}
template<int D> __device__ __forceinline__ void gemm1(float (&d)[32], const uint32_t (&a)[16], uint64_t db) {
  asm volatile("{\n.reg .b64 db;\n"
    "add.s64 db, %48, %49 + 0;\n"
    "wgmma.mma_async.sync.aligned.m64n64k16.f32.bf16.bf16 {%0, %1, %2, %3, %4, %5, %6, %7, %8, %9, %10, %11, %12, %13, %14, %15, %16, %17, %18, %19, %20, %21, %22, %23, %24, %25, %26, %27, %28, %29, %30, %31}, {%32, %33, %34, %35}, db, 1, 1, 1, 0;\n"
    "add.s64 db, %48, %49 + 2;\n"
    "wgmma.mma_async.sync.aligned.m64n64k16.f32.bf16.bf16 {%0, %1, %2, %3, %4, %5, %6, %7, %8, %9, %10, %11, %12, %13, %14, %15, %16, %17, %18, %19, %20, %21, %22, %23, %24, %25, %26, %27, %28, %29, %30, %31}, {%36, %37, %38, %39}, db, 1, 1, 1, 0;\n"
    "add.s64 db, %48, %49 + 4;\n"
    "wgmma.mma_async.sync.aligned.m64n64k16.f32.bf16.bf16 {%0, %1, %2, %3, %4, %5, %6, %7, %8, %9, %10, %11, %12, %13, %14, %15, %16, %17, %18, %19, %20, %21, %22, %23, %24, %25, %26, %27, %28, %29, %30, %31}, {%40, %41, %42, %43}, db, 1, 1, 1, 0;\n"
    "add.s64 db, %48, %49 + 6;\n"
    "wgmma.mma_async.sync.aligned.m64n64k16.f32.bf16.bf16 {%0, %1, %2, %3, %4, %5, %6, %7, %8, %9, %10, %11, %12, %13, %14, %15, %16, %17, %18, %19, %20, %21, %22, %23, %24, %25, %26, %27, %28, %29, %30, %31}, {%44, %45, %46, %47}, db, 1, 1, 1, 0;\n"
    "wgmma.commit_group.sync.aligned;\n}\n"
    : "+f"(d[0]), "+f"(d[1]), "+f"(d[2]), "+f"(d[3]), "+f"(d[4]), "+f"(d[5]), "+f"(d[6]), "+f"(d[7]), "+f"(d[8]), "+f"(d[9]), "+f"(d[10]), "+f"(d[11]), "+f"(d[12]), "+f"(d[13]), "+f"(d[14]), "+f"(d[15]), "+f"(d[16]), "+f"(d[17]), "+f"(d[18]), "+f"(d[19]), "+f"(d[20]), "+f"(d[21]), "+f"(d[22]), "+f"(d[23]), "+f"(d[24]), "+f"(d[25]), "+f"(d[26]), "+f"(d[27]), "+f"(d[28]), "+f"(d[29]), "+f"(d[30]), "+f"(d[31])
    : "r"(a[0]), "r"(a[1]), "r"(a[2]), "r"(a[3]), "r"(a[4]), "r"(a[5]), "r"(a[6]), "r"(a[7]), "r"(a[8]), "r"(a[9]), "r"(a[10]), "r"(a[11]), "r"(a[12]), "r"(a[13]), "r"(a[14]), "r"(a[15]), "l"(db), "n"(D)
    : "memory");
}
template<int D> __device__ __forceinline__ void gemm1(float (&d)[36], const uint32_t (&a)[16], uint64_t db) {
  asm volatile("{\n.reg .b64 db;\n"
    "add.s64 db, %52, %53 + 0;\n"
    "wgmma.mma_async.sync.aligned.m64n72k16.f32.bf16.bf16 {%0, %1, %2, %3, %4, %5, %6, %7, %8, %9, %10, %11, %12, %13, %14, %15, %16, %17, %18, %19, %20, %21, %22, %23, %24, %25, %26, %27, %28, %29, %30, %31, %32, %33, %34, %35}, {%36, %37, %38, %39}, db, 1, 1, 1, 0;\n"
    "add.s64 db, %52, %53 + 2;\n"
    "wgmma.mma_async.sync.aligned.m64n72k16.f32.bf16.bf16 {%0, %1, %2, %3, %4, %5, %6, %7, %8, %9, %10, %11, %12, %13, %14, %15, %16, %17, %18, %19, %20, %21, %22, %23, %24, %25, %26, %27, %28, %29, %30, %31, %32, %33, %34, %35}, {%40, %41, %42, %43}, db, 1, 1, 1, 0;\n"
    "add.s64 db, %52, %53 + 4;\n"
    "wgmma.mma_async.sync.aligned.m64n72k16.f32.bf16.bf16 {%0, %1, %2, %3, %4, %5, %6, %7, %8, %9, %10, %11, %12, %13, %14, %15, %16, %17, %18, %19, %20, %21, %22, %23, %24, %25, %26, %27, %28, %29, %30, %31, %32, %33, %34, %35}, {%44, %45, %46, %47}, db, 1, 1, 1, 0;\n"
    "add.s64 db, %52, %53 + 6;\n"
    "wgmma.mma_async.sync.aligned.m64n72k16.f32.bf16.bf16 {%0, %1, %2, %3, %4, %5, %6, %7, %8, %9, %10, %11, %12, %13, %14, %15, %16, %17, %18, %19, %20, %21, %22, %23, %24, %25, %26, %27, %28, %29, %30, %31, %32, %33, %34, %35}, {%48, %49, %50, %51}, db, 1, 1, 1, 0;\n"
    "wgmma.commit_group.sync.aligned;\n}\n"
    : "+f"(d[0]), "+f"(d[1]), "+f"(d[2]), "+f"(d[3]), "+f"(d[4]), "+f"(d[5]), "+f"(d[6]), "+f"(d[7]), "+f"(d[8]), "+f"(d[9]), "+f"(d[10]), "+f"(d[11]), "+f"(d[12]), "+f"(d[13]), "+f"(d[14]), "+f"(d[15]), "+f"(d[16]), "+f"(d[17]), "+f"(d[18]), "+f"(d[19]), "+f"(d[20]), "+f"(d[21]), "+f"(d[22]), "+f"(d[23]), "+f"(d[24]), "+f"(d[25]), "+f"(d[26]), "+f"(d[27]), "+f"(d[28]), "+f"(d[29]), "+f"(d[30]), "+f"(d[31]), "+f"(d[32]), "+f"(d[33]), "+f"(d[34]), "+f"(d[35])
    : "r"(a[0]), "r"(a[1]), "r"(a[2]), "r"(a[3]), "r"(a[4]), "r"(a[5]), "r"(a[6]), "r"(a[7]), "r"(a[8]), "r"(a[9]), "r"(a[10]), "r"(a[11]), "r"(a[12]), "r"(a[13]), "r"(a[14]), "r"(a[15]), "l"(db), "n"(D)
    : "memory");
}
template<int D> __device__ __forceinline__ void gemm1(float (&d)[40], const uint32_t (&a)[16], uint64_t db) {
  asm volatile("{\n.reg .b64 db;\n"
    "add.s64 db, %56, %57 + 0;\n"
    "wgmma.mma_async.sync.aligned.m64n80k16.f32.bf16.bf16 {%0, %1, %2, %3, %4, %5, %6, %7, %8, %9, %10, %11, %12, %13, %14, %15, %16, %17, %18, %19, %20, %21, %22, %23, %24, %25, %26, %27, %28, %29, %30, %31, %32, %33, %34, %35, %36, %37, %38, %39}, {%40, %41, %42, %43}, db, 1, 1, 1, 0;\n"
    "add.s64 db, %56, %57 + 2;\n"
    "wgmma.mma_async.sync.aligned.m64n80k16.f32.bf16.bf16 {%0, %1, %2, %3, %4, %5, %6, %7, %8, %9, %10, %11, %12, %13, %14, %15, %16, %17, %18, %19, %20, %21, %22, %23, %24, %25, %26, %27, %28, %29, %30, %31, %32, %33, %34, %35, %36, %37, %38, %39}, {%44, %45, %46, %47}, db, 1, 1, 1, 0;\n"
    "add.s64 db, %56, %57 + 4;\n"
    "wgmma.mma_async.sync.aligned.m64n80k16.f32.bf16.bf16 {%0, %1, %2, %3, %4, %5, %6, %7, %8, %9, %10, %11, %12, %13, %14, %15, %16, %17, %18, %19, %20, %21, %22, %23, %24, %25, %26, %27, %28, %29, %30, %31, %32, %33, %34, %35, %36, %37, %38, %39}, {%48, %49, %50, %51}, db, 1, 1, 1, 0;\n"
    "add.s64 db, %56, %57 + 6;\n"
    "wgmma.mma_async.sync.aligned.m64n80k16.f32.bf16.bf16 {%0, %1, %2, %3, %4, %5, %6, %7, %8, %9, %10, %11, %12, %13, %14, %15, %16, %17, %18, %19, %20, %21, %22, %23, %24, %25, %26, %27, %28, %29, %30, %31, %32, %33, %34, %35, %36, %37, %38, %39}, {%52, %53, %54, %55}, db, 1, 1, 1, 0;\n"
    "wgmma.commit_group.sync.aligned;\n}\n"
    : "+f"(d[0]), "+f"(d[1]), "+f"(d[2]), "+f"(d[3]), "+f"(d[4]), "+f"(d[5]), "+f"(d[6]), "+f"(d[7]), "+f"(d[8]), "+f"(d[9]), "+f"(d[10]), "+f"(d[11]), "+f"(d[12]), "+f"(d[13]), "+f"(d[14]), "+f"(d[15]), "+f"(d[16]), "+f"(d[17]), "+f"(d[18]), "+f"(d[19]), "+f"(d[20]), "+f"(d[21]), "+f"(d[22]), "+f"(d[23]), "+f"(d[24]), "+f"(d[25]), "+f"(d[26]), "+f"(d[27]), "+f"(d[28]), "+f"(d[29]), "+f"(d[30]), "+f"(d[31]), "+f"(d[32]), "+f"(d[33]), "+f"(d[34]), "+f"(d[35]), "+f"(d[36]), "+f"(d[37]), "+f"(d[38]), "+f"(d[39])
    : "r"(a[0]), "r"(a[1]), "r"(a[2]), "r"(a[3]), "r"(a[4]), "r"(a[5]), "r"(a[6]), "r"(a[7]), "r"(a[8]), "r"(a[9]), "r"(a[10]), "r"(a[11]), "r"(a[12]), "r"(a[13]), "r"(a[14]), "r"(a[15]), "l"(db), "n"(D)
    : "memory");
}
template<int D> __device__ __forceinline__ void gemm1(float (&d)[44], const uint32_t (&a)[16], uint64_t db) {
  asm volatile("{\n.reg .b64 db;\n"
    "add.s64 db, %60, %61 + 0;\n"
    "wgmma.mma_async.sync.aligned.m64n88k16.f32.bf16.bf16 {%0, %1, %2, %3, %4, %5, %6, %7, %8, %9, %10, %11, %12, %13, %14, %15, %16, %17, %18, %19, %20, %21, %22, %23, %24, %25, %26, %27, %28, %29, %30, %31, %32, %33, %34, %35, %36, %37, %38, %39, %40, %41, %42, %43}, {%44, %45, %46, %47}, db, 1, 1, 1, 0;\n"
    "add.s64 db, %60, %61 + 2;\n"
    "wgmma.mma_async.sync.aligned.m64n88k16.f32.bf16.bf16 {%0, %1, %2, %3, %4, %5, %6, %7, %8, %9, %10, %11, %12, %13, %14, %15, %16, %17, %18, %19, %20, %21, %22, %23, %24, %25, %26, %27, %28, %29, %30, %31, %32, %33, %34, %35, %36, %37, %38, %39, %40, %41, %42, %43}, {%48, %49, %50, %51}, db, 1, 1, 1, 0;\n"
    "add.s64 db, %60, %61 + 4;\n"
    "wgmma.mma_async.sync.aligned.m64n88k16.f32.bf16.bf16 {%0, %1, %2, %3, %4, %5, %6, %7, %8, %9, %10, %11, %12, %13, %14, %15, %16, %17, %18, %19, %20, %21, %22, %23, %24, %25, %26, %27, %28, %29, %30, %31, %32, %33, %34, %35, %36, %37, %38, %39, %40, %41, %42, %43}, {%52, %53, %54, %55}, db, 1, 1, 1, 0;\n"
    "add.s64 db, %60, %61 + 6;\n"
    "wgmma.mma_async.sync.aligned.m64n88k16.f32.bf16.bf16 {%0, %1, %2, %3, %4, %5, %6, %7, %8, %9, %10, %11, %12, %13, %14, %15, %16, %17, %18, %19, %20, %21, %22, %23, %24, %25, %26, %27, %28, %29, %30, %31, %32, %33, %34, %35, %36, %37, %38, %39, %40, %41, %42, %43}, {%56, %57, %58, %59}, db, 1, 1, 1, 0;\n"
    "wgmma.commit_group.sync.aligned;\n}\n"
    : "+f"(d[0]), "+f"(d[1]), "+f"(d[2]), "+f"(d[3]), "+f"(d[4]), "+f"(d[5]), "+f"(d[6]), "+f"(d[7]), "+f"(d[8]), "+f"(d[9]), "+f"(d[10]), "+f"(d[11]), "+f"(d[12]), "+f"(d[13]), "+f"(d[14]), "+f"(d[15]), "+f"(d[16]), "+f"(d[17]), "+f"(d[18]), "+f"(d[19]), "+f"(d[20]), "+f"(d[21]), "+f"(d[22]), "+f"(d[23]), "+f"(d[24]), "+f"(d[25]), "+f"(d[26]), "+f"(d[27]), "+f"(d[28]), "+f"(d[29]), "+f"(d[30]), "+f"(d[31]), "+f"(d[32]), "+f"(d[33]), "+f"(d[34]), "+f"(d[35]), "+f"(d[36]), "+f"(d[37]), "+f"(d[38]), "+f"(d[39]), "+f"(d[40]), "+f"(d[41]), "+f"(d[42]), "+f"(d[43])
    : "r"(a[0]), "r"(a[1]), "r"(a[2]), "r"(a[3]), "r"(a[4]), "r"(a[5]), "r"(a[6]), "r"(a[7]), "r"(a[8]), "r"(a[9]), "r"(a[10]), "r"(a[11]), "r"(a[12]), "r"(a[13]), "r"(a[14]), "r"(a[15]), "l"(db), "n"(D)
    : "memory");
}
template<int D> __device__ __forceinline__ void bias_out(float (&d)[4], const uint32_t (&a)[16], uint64_t db) {
  asm volatile("{\n.reg .b64 db;\n"
    "add.s64 db, %20, %21 + 0;\n"
    "wgmma.mma_async.sync.aligned.m64n8k16.f32.bf16.bf16 {%0, %1, %2, %3}, {%4, %5, %6, %7}, db, 0, 1, 1, 0;\n"
    "add.s64 db, %20, %21 + 2;\n"
    "wgmma.mma_async.sync.aligned.m64n8k16.f32.bf16.bf16 {%0, %1, %2, %3}, {%8, %9, %10, %11}, db, 1, 1, 1, 0;\n"
    "add.s64 db, %20, %21 + 4;\n"
    "wgmma.mma_async.sync.aligned.m64n8k16.f32.bf16.bf16 {%0, %1, %2, %3}, {%12, %13, %14, %15}, db, 1, 1, 1, 0;\n"
    "add.s64 db, %20, %21 + 6;\n"
    "wgmma.mma_async.sync.aligned.m64n8k16.f32.bf16.bf16 {%0, %1, %2, %3}, {%16, %17, %18, %19}, db, 1, 1, 1, 0;\n"
    "wgmma.commit_group.sync.aligned;\n}\n"
    : "=f"(d[0]), "=f"(d[1]), "=f"(d[2]), "=f"(d[3])
    : "r"(a[0]), "r"(a[1]), "r"(a[2]), "r"(a[3]), "r"(a[4]), "r"(a[5]), "r"(a[6]), "r"(a[7]), "r"(a[8]), "r"(a[9]), "r"(a[10]), "r"(a[11]), "r"(a[12]), "r"(a[13]), "r"(a[14]), "r"(a[15]), "l"(db), "n"(D)
    : "memory");
}
template<int D> __device__ __forceinline__ void gemm2_first(float (&d)[16], const uint32_t (&a)[12], uint64_t db, uint32_t meta) {
  asm volatile("{\n.reg .b64 db;\n"
    "wgmma.fence.sync.aligned;\n"
    "add.s64 db, %28, %29 + 0;\n"
    "wgmma.mma_async.sp.sync.aligned.m64n32k32.f32.bf16.bf16 {%0, %1, %2, %3, %4, %5, %6, %7, %8, %9, %10, %11, %12, %13, %14, %15}, {%16, %17, %18, %19}, db, %30, 0, 0, 1, 1, 1;\n"
    "add.s64 db, %28, %29 + 128;\n"
    "wgmma.mma_async.sp.sync.aligned.m64n32k32.f32.bf16.bf16 {%0, %1, %2, %3, %4, %5, %6, %7, %8, %9, %10, %11, %12, %13, %14, %15}, {%20, %21, %22, %23}, db, %30, 0, 1, 1, 1, 1;\n"
    "add.s64 db, %28, %29 + 256;\n"
    "wgmma.mma_async.sp.sync.aligned.m64n32k32.f32.bf16.bf16 {%0, %1, %2, %3, %4, %5, %6, %7, %8, %9, %10, %11, %12, %13, %14, %15}, {%24, %25, %26, %27}, db, %30, 0, 1, 1, 1, 1;\n"
    "wgmma.commit_group.sync.aligned;\n}\n"
    : "=f"(d[0]), "=f"(d[1]), "=f"(d[2]), "=f"(d[3]), "=f"(d[4]), "=f"(d[5]), "=f"(d[6]), "=f"(d[7]), "=f"(d[8]), "=f"(d[9]), "=f"(d[10]), "=f"(d[11]), "=f"(d[12]), "=f"(d[13]), "=f"(d[14]), "=f"(d[15])
    : "r"(a[0]), "r"(a[1]), "r"(a[2]), "r"(a[3]), "r"(a[4]), "r"(a[5]), "r"(a[6]), "r"(a[7]), "r"(a[8]), "r"(a[9]), "r"(a[10]), "r"(a[11]), "l"(db), "n"(D), "r"(meta)
    : "memory");
}
template<int D> __device__ __forceinline__ void gemm2_first(float (&d)[16], const uint32_t (&a)[16], uint64_t db, uint32_t meta) {
  asm volatile("{\n.reg .b64 db;\n"
    "wgmma.fence.sync.aligned;\n"
    "add.s64 db, %32, %33 + 0;\n"
    "wgmma.mma_async.sp.sync.aligned.m64n32k32.f32.bf16.bf16 {%0, %1, %2, %3, %4, %5, %6, %7, %8, %9, %10, %11, %12, %13, %14, %15}, {%16, %17, %18, %19}, db, %34, 0, 0, 1, 1, 1;\n"
    "add.s64 db, %32, %33 + 128;\n"
    "wgmma.mma_async.sp.sync.aligned.m64n32k32.f32.bf16.bf16 {%0, %1, %2, %3, %4, %5, %6, %7, %8, %9, %10, %11, %12, %13, %14, %15}, {%20, %21, %22, %23}, db, %34, 0, 1, 1, 1, 1;\n"
    "add.s64 db, %32, %33 + 256;\n"
    "wgmma.mma_async.sp.sync.aligned.m64n32k32.f32.bf16.bf16 {%0, %1, %2, %3, %4, %5, %6, %7, %8, %9, %10, %11, %12, %13, %14, %15}, {%24, %25, %26, %27}, db, %34, 0, 1, 1, 1, 1;\n"
    "add.s64 db, %32, %33 + 384;\n"
    "wgmma.mma_async.sp.sync.aligned.m64n32k32.f32.bf16.bf16 {%0, %1, %2, %3, %4, %5, %6, %7, %8, %9, %10, %11, %12, %13, %14, %15}, {%28, %29, %30, %31}, db, %34, 0, 1, 1, 1, 1;\n"
    "wgmma.commit_group.sync.aligned;\n}\n"
    : "=f"(d[0]), "=f"(d[1]), "=f"(d[2]), "=f"(d[3]), "=f"(d[4]), "=f"(d[5]), "=f"(d[6]), "=f"(d[7]), "=f"(d[8]), "=f"(d[9]), "=f"(d[10]), "=f"(d[11]), "=f"(d[12]), "=f"(d[13]), "=f"(d[14]), "=f"(d[15])
    : "r"(a[0]), "r"(a[1]), "r"(a[2]), "r"(a[3]), "r"(a[4]), "r"(a[5]), "r"(a[6]), "r"(a[7]), "r"(a[8]), "r"(a[9]), "r"(a[10]), "r"(a[11]), "r"(a[12]), "r"(a[13]), "r"(a[14]), "r"(a[15]), "l"(db), "n"(D), "r"(meta)
    : "memory");
}
template<int D> __device__ __forceinline__ void gemm2_first(float (&d)[16], const uint32_t (&a)[20], uint64_t db, uint32_t meta) {
  asm volatile("{\n.reg .b64 db;\n"
    "wgmma.fence.sync.aligned;\n"
    "add.s64 db, %36, %37 + 0;\n"
    "wgmma.mma_async.sp.sync.aligned.m64n32k32.f32.bf16.bf16 {%0, %1, %2, %3, %4, %5, %6, %7, %8, %9, %10, %11, %12, %13, %14, %15}, {%16, %17, %18, %19}, db, %38, 0, 0, 1, 1, 1;\n"
    "add.s64 db, %36, %37 + 128;\n"
    "wgmma.mma_async.sp.sync.aligned.m64n32k32.f32.bf16.bf16 {%0, %1, %2, %3, %4, %5, %6, %7, %8, %9, %10, %11, %12, %13, %14, %15}, {%20, %21, %22, %23}, db, %38, 0, 1, 1, 1, 1;\n"
    "add.s64 db, %36, %37 + 256;\n"
    "wgmma.mma_async.sp.sync.aligned.m64n32k32.f32.bf16.bf16 {%0, %1, %2, %3, %4, %5, %6, %7, %8, %9, %10, %11, %12, %13, %14, %15}, {%24, %25, %26, %27}, db, %38, 0, 1, 1, 1, 1;\n"
    "add.s64 db, %36, %37 + 384;\n"
    "wgmma.mma_async.sp.sync.aligned.m64n32k32.f32.bf16.bf16 {%0, %1, %2, %3, %4, %5, %6, %7, %8, %9, %10, %11, %12, %13, %14, %15}, {%28, %29, %30, %31}, db, %38, 0, 1, 1, 1, 1;\n"
    "add.s64 db, %36, %37 + 512;\n"
    "wgmma.mma_async.sp.sync.aligned.m64n32k32.f32.bf16.bf16 {%0, %1, %2, %3, %4, %5, %6, %7, %8, %9, %10, %11, %12, %13, %14, %15}, {%32, %33, %34, %35}, db, %38, 0, 1, 1, 1, 1;\n"
    "wgmma.commit_group.sync.aligned;\n}\n"
    : "=f"(d[0]), "=f"(d[1]), "=f"(d[2]), "=f"(d[3]), "=f"(d[4]), "=f"(d[5]), "=f"(d[6]), "=f"(d[7]), "=f"(d[8]), "=f"(d[9]), "=f"(d[10]), "=f"(d[11]), "=f"(d[12]), "=f"(d[13]), "=f"(d[14]), "=f"(d[15])
    : "r"(a[0]), "r"(a[1]), "r"(a[2]), "r"(a[3]), "r"(a[4]), "r"(a[5]), "r"(a[6]), "r"(a[7]), "r"(a[8]), "r"(a[9]), "r"(a[10]), "r"(a[11]), "r"(a[12]), "r"(a[13]), "r"(a[14]), "r"(a[15]), "r"(a[16]), "r"(a[17]), "r"(a[18]), "r"(a[19]), "l"(db), "n"(D), "r"(meta)
    : "memory");
}
template<int D> __device__ __forceinline__ void gemm2_more(float (&d)[16], const uint32_t (&a)[4], uint64_t db, uint32_t meta) {
  asm volatile("{\n.reg .b64 db;\n"
    "wgmma.fence.sync.aligned;\n"
    "add.s64 db, %20, %21 + 0;\n"
    "wgmma.mma_async.sp.sync.aligned.m64n32k32.f32.bf16.bf16 {%0, %1, %2, %3, %4, %5, %6, %7, %8, %9, %10, %11, %12, %13, %14, %15}, {%16, %17, %18, %19}, db, %22, 0, 1, 1, 1, 1;\n"
    "wgmma.commit_group.sync.aligned;\n}\n"
    : "+f"(d[0]), "+f"(d[1]), "+f"(d[2]), "+f"(d[3]), "+f"(d[4]), "+f"(d[5]), "+f"(d[6]), "+f"(d[7]), "+f"(d[8]), "+f"(d[9]), "+f"(d[10]), "+f"(d[11]), "+f"(d[12]), "+f"(d[13]), "+f"(d[14]), "+f"(d[15])
    : "r"(a[0]), "r"(a[1]), "r"(a[2]), "r"(a[3]), "l"(db), "n"(D), "r"(meta)
    : "memory");
}
template<int D> __device__ __forceinline__ void gemm2_more(float (&d)[16], const uint32_t (&a)[8], uint64_t db, uint32_t meta) {
  asm volatile("{\n.reg .b64 db;\n"
    "wgmma.fence.sync.aligned;\n"
    "add.s64 db, %24, %25 + 0;\n"
    "wgmma.mma_async.sp.sync.aligned.m64n32k32.f32.bf16.bf16 {%0, %1, %2, %3, %4, %5, %6, %7, %8, %9, %10, %11, %12, %13, %14, %15}, {%16, %17, %18, %19}, db, %26, 0, 1, 1, 1, 1;\n"
    "add.s64 db, %24, %25 + 128;\n"
    "wgmma.mma_async.sp.sync.aligned.m64n32k32.f32.bf16.bf16 {%0, %1, %2, %3, %4, %5, %6, %7, %8, %9, %10, %11, %12, %13, %14, %15}, {%20, %21, %22, %23}, db, %26, 0, 1, 1, 1, 1;\n"
    "wgmma.commit_group.sync.aligned;\n}\n"
    : "+f"(d[0]), "+f"(d[1]), "+f"(d[2]), "+f"(d[3]), "+f"(d[4]), "+f"(d[5]), "+f"(d[6]), "+f"(d[7]), "+f"(d[8]), "+f"(d[9]), "+f"(d[10]), "+f"(d[11]), "+f"(d[12]), "+f"(d[13]), "+f"(d[14]), "+f"(d[15])
    : "r"(a[0]), "r"(a[1]), "r"(a[2]), "r"(a[3]), "r"(a[4]), "r"(a[5]), "r"(a[6]), "r"(a[7]), "l"(db), "n"(D), "r"(meta)
    : "memory");
}
template<int D> __device__ __forceinline__ void gemm2_more(float (&d)[16], const uint32_t (&a)[12], uint64_t db, uint32_t meta) {
  asm volatile("{\n.reg .b64 db;\n"
    "wgmma.fence.sync.aligned;\n"
    "add.s64 db, %28, %29 + 0;\n"
    "wgmma.mma_async.sp.sync.aligned.m64n32k32.f32.bf16.bf16 {%0, %1, %2, %3, %4, %5, %6, %7, %8, %9, %10, %11, %12, %13, %14, %15}, {%16, %17, %18, %19}, db, %30, 0, 1, 1, 1, 1;\n"
    "add.s64 db, %28, %29 + 128;\n"
    "wgmma.mma_async.sp.sync.aligned.m64n32k32.f32.bf16.bf16 {%0, %1, %2, %3, %4, %5, %6, %7, %8, %9, %10, %11, %12, %13, %14, %15}, {%20, %21, %22, %23}, db, %30, 0, 1, 1, 1, 1;\n"
    "add.s64 db, %28, %29 + 256;\n"
    "wgmma.mma_async.sp.sync.aligned.m64n32k32.f32.bf16.bf16 {%0, %1, %2, %3, %4, %5, %6, %7, %8, %9, %10, %11, %12, %13, %14, %15}, {%24, %25, %26, %27}, db, %30, 0, 1, 1, 1, 1;\n"
    "wgmma.commit_group.sync.aligned;\n}\n"
    : "+f"(d[0]), "+f"(d[1]), "+f"(d[2]), "+f"(d[3]), "+f"(d[4]), "+f"(d[5]), "+f"(d[6]), "+f"(d[7]), "+f"(d[8]), "+f"(d[9]), "+f"(d[10]), "+f"(d[11]), "+f"(d[12]), "+f"(d[13]), "+f"(d[14]), "+f"(d[15])
    : "r"(a[0]), "r"(a[1]), "r"(a[2]), "r"(a[3]), "r"(a[4]), "r"(a[5]), "r"(a[6]), "r"(a[7]), "r"(a[8]), "r"(a[9]), "r"(a[10]), "r"(a[11]), "l"(db), "n"(D), "r"(meta)
    : "memory");
}
template<int D> __device__ __forceinline__ void gemm2_more(float (&d)[16], const uint32_t (&a)[16], uint64_t db, uint32_t meta) {
  asm volatile("{\n.reg .b64 db;\n"
    "wgmma.fence.sync.aligned;\n"
    "add.s64 db, %32, %33 + 0;\n"
    "wgmma.mma_async.sp.sync.aligned.m64n32k32.f32.bf16.bf16 {%0, %1, %2, %3, %4, %5, %6, %7, %8, %9, %10, %11, %12, %13, %14, %15}, {%16, %17, %18, %19}, db, %34, 0, 1, 1, 1, 1;\n"
    "add.s64 db, %32, %33 + 128;\n"
    "wgmma.mma_async.sp.sync.aligned.m64n32k32.f32.bf16.bf16 {%0, %1, %2, %3, %4, %5, %6, %7, %8, %9, %10, %11, %12, %13, %14, %15}, {%20, %21, %22, %23}, db, %34, 0, 1, 1, 1, 1;\n"
    "add.s64 db, %32, %33 + 256;\n"
    "wgmma.mma_async.sp.sync.aligned.m64n32k32.f32.bf16.bf16 {%0, %1, %2, %3, %4, %5, %6, %7, %8, %9, %10, %11, %12, %13, %14, %15}, {%24, %25, %26, %27}, db, %34, 0, 1, 1, 1, 1;\n"
    "add.s64 db, %32, %33 + 384;\n"
    "wgmma.mma_async.sp.sync.aligned.m64n32k32.f32.bf16.bf16 {%0, %1, %2, %3, %4, %5, %6, %7, %8, %9, %10, %11, %12, %13, %14, %15}, {%28, %29, %30, %31}, db, %34, 0, 1, 1, 1, 1;\n"
    "wgmma.commit_group.sync.aligned;\n}\n"
    : "+f"(d[0]), "+f"(d[1]), "+f"(d[2]), "+f"(d[3]), "+f"(d[4]), "+f"(d[5]), "+f"(d[6]), "+f"(d[7]), "+f"(d[8]), "+f"(d[9]), "+f"(d[10]), "+f"(d[11]), "+f"(d[12]), "+f"(d[13]), "+f"(d[14]), "+f"(d[15])
    : "r"(a[0]), "r"(a[1]), "r"(a[2]), "r"(a[3]), "r"(a[4]), "r"(a[5]), "r"(a[6]), "r"(a[7]), "r"(a[8]), "r"(a[9]), "r"(a[10]), "r"(a[11]), "r"(a[12]), "r"(a[13]), "r"(a[14]), "r"(a[15]), "l"(db), "n"(D), "r"(meta)
    : "memory");
}
template<int N> __device__ __forceinline__ void mma_wait(float (&d)[4]) {
  asm volatile("wgmma.wait_group.sync.aligned %4;"
    : "+f"(d[0]), "+f"(d[1]), "+f"(d[2]), "+f"(d[3])
    : "n"(N) : "memory");
}
template<int N> __device__ __forceinline__ void mma_wait(float (&d)[16]) {
  asm volatile("wgmma.wait_group.sync.aligned %16;"
    : "+f"(d[0]), "+f"(d[1]), "+f"(d[2]), "+f"(d[3]), "+f"(d[4]), "+f"(d[5]), "+f"(d[6]), "+f"(d[7]), "+f"(d[8]), "+f"(d[9]), "+f"(d[10]), "+f"(d[11]), "+f"(d[12]), "+f"(d[13]), "+f"(d[14]), "+f"(d[15])
    : "n"(N) : "memory");
}
template<int N> __device__ __forceinline__ void mma_wait(float (&d)[20]) {
  asm volatile("wgmma.wait_group.sync.aligned %20;"
    : "+f"(d[0]), "+f"(d[1]), "+f"(d[2]), "+f"(d[3]), "+f"(d[4]), "+f"(d[5]), "+f"(d[6]), "+f"(d[7]), "+f"(d[8]), "+f"(d[9]), "+f"(d[10]), "+f"(d[11]), "+f"(d[12]), "+f"(d[13]), "+f"(d[14]), "+f"(d[15]), "+f"(d[16]), "+f"(d[17]), "+f"(d[18]), "+f"(d[19])
    : "n"(N) : "memory");
}
template<int N> __device__ __forceinline__ void mma_wait(float (&d)[28]) {
  asm volatile("wgmma.wait_group.sync.aligned %28;"
    : "+f"(d[0]), "+f"(d[1]), "+f"(d[2]), "+f"(d[3]), "+f"(d[4]), "+f"(d[5]), "+f"(d[6]), "+f"(d[7]), "+f"(d[8]), "+f"(d[9]), "+f"(d[10]), "+f"(d[11]), "+f"(d[12]), "+f"(d[13]), "+f"(d[14]), "+f"(d[15]), "+f"(d[16]), "+f"(d[17]), "+f"(d[18]), "+f"(d[19]), "+f"(d[20]), "+f"(d[21]), "+f"(d[22]), "+f"(d[23]), "+f"(d[24]), "+f"(d[25]), "+f"(d[26]), "+f"(d[27])
    : "n"(N) : "memory");
}
template<int N> __device__ __forceinline__ void mma_wait(float (&d)[32]) {
  asm volatile("wgmma.wait_group.sync.aligned %32;"
    : "+f"(d[0]), "+f"(d[1]), "+f"(d[2]), "+f"(d[3]), "+f"(d[4]), "+f"(d[5]), "+f"(d[6]), "+f"(d[7]), "+f"(d[8]), "+f"(d[9]), "+f"(d[10]), "+f"(d[11]), "+f"(d[12]), "+f"(d[13]), "+f"(d[14]), "+f"(d[15]), "+f"(d[16]), "+f"(d[17]), "+f"(d[18]), "+f"(d[19]), "+f"(d[20]), "+f"(d[21]), "+f"(d[22]), "+f"(d[23]), "+f"(d[24]), "+f"(d[25]), "+f"(d[26]), "+f"(d[27]), "+f"(d[28]), "+f"(d[29]), "+f"(d[30]), "+f"(d[31])
    : "n"(N) : "memory");
}
template<int N> __device__ __forceinline__ void mma_wait(float (&d)[36]) {
  asm volatile("wgmma.wait_group.sync.aligned %36;"
    : "+f"(d[0]), "+f"(d[1]), "+f"(d[2]), "+f"(d[3]), "+f"(d[4]), "+f"(d[5]), "+f"(d[6]), "+f"(d[7]), "+f"(d[8]), "+f"(d[9]), "+f"(d[10]), "+f"(d[11]), "+f"(d[12]), "+f"(d[13]), "+f"(d[14]), "+f"(d[15]), "+f"(d[16]), "+f"(d[17]), "+f"(d[18]), "+f"(d[19]), "+f"(d[20]), "+f"(d[21]), "+f"(d[22]), "+f"(d[23]), "+f"(d[24]), "+f"(d[25]), "+f"(d[26]), "+f"(d[27]), "+f"(d[28]), "+f"(d[29]), "+f"(d[30]), "+f"(d[31]), "+f"(d[32]), "+f"(d[33]), "+f"(d[34]), "+f"(d[35])
    : "n"(N) : "memory");
}
template<int N> __device__ __forceinline__ void mma_wait(float (&d)[40]) {
  asm volatile("wgmma.wait_group.sync.aligned %40;"
    : "+f"(d[0]), "+f"(d[1]), "+f"(d[2]), "+f"(d[3]), "+f"(d[4]), "+f"(d[5]), "+f"(d[6]), "+f"(d[7]), "+f"(d[8]), "+f"(d[9]), "+f"(d[10]), "+f"(d[11]), "+f"(d[12]), "+f"(d[13]), "+f"(d[14]), "+f"(d[15]), "+f"(d[16]), "+f"(d[17]), "+f"(d[18]), "+f"(d[19]), "+f"(d[20]), "+f"(d[21]), "+f"(d[22]), "+f"(d[23]), "+f"(d[24]), "+f"(d[25]), "+f"(d[26]), "+f"(d[27]), "+f"(d[28]), "+f"(d[29]), "+f"(d[30]), "+f"(d[31]), "+f"(d[32]), "+f"(d[33]), "+f"(d[34]), "+f"(d[35]), "+f"(d[36]), "+f"(d[37]), "+f"(d[38]), "+f"(d[39])
    : "n"(N) : "memory");
}
template<int N> __device__ __forceinline__ void mma_wait(float (&d)[44]) {
  asm volatile("wgmma.wait_group.sync.aligned %44;"
    : "+f"(d[0]), "+f"(d[1]), "+f"(d[2]), "+f"(d[3]), "+f"(d[4]), "+f"(d[5]), "+f"(d[6]), "+f"(d[7]), "+f"(d[8]), "+f"(d[9]), "+f"(d[10]), "+f"(d[11]), "+f"(d[12]), "+f"(d[13]), "+f"(d[14]), "+f"(d[15]), "+f"(d[16]), "+f"(d[17]), "+f"(d[18]), "+f"(d[19]), "+f"(d[20]), "+f"(d[21]), "+f"(d[22]), "+f"(d[23]), "+f"(d[24]), "+f"(d[25]), "+f"(d[26]), "+f"(d[27]), "+f"(d[28]), "+f"(d[29]), "+f"(d[30]), "+f"(d[31]), "+f"(d[32]), "+f"(d[33]), "+f"(d[34]), "+f"(d[35]), "+f"(d[36]), "+f"(d[37]), "+f"(d[38]), "+f"(d[39]), "+f"(d[40]), "+f"(d[41]), "+f"(d[42]), "+f"(d[43])
    : "n"(N) : "memory");
}
__device__ __forceinline__ void mma_fence() { asm volatile("wgmma.fence.sync.aligned;" ::: "memory"); }


__device__ __forceinline__ uint32_t smem_u32(const void* p) { return (uint32_t)__cvta_generic_to_shared(p); }

__device__ __forceinline__ void mbar_init(uint32_t bar, uint32_t cnt) {
  asm volatile("mbarrier.init.shared::cta.b64 [%0], %1;" :: "r"(bar), "r"(cnt) : "memory");
}
__device__ __forceinline__ void mbar_arrive(uint32_t bar) {
  asm volatile("mbarrier.arrive.shared::cta.b64 _, [%0];" :: "r"(bar) : "memory");
}
__device__ __forceinline__ void mbar_wait(uint32_t bar, uint32_t parity) {
  asm volatile("{\n.reg .pred p;\n.reg .u32 n;\n"
               "mov.u32 n, 0;\n"
               "WAIT_LOOP:\n"
               "mbarrier.try_wait.parity.shared::cta.b64 p, [%0], %1;\n"
               "@p bra.uni WAIT_DONE;\n"
               "add.u32 n, n, 1;\n"
               "setp.lt.u32 p, n, 0x1000000;\n"
               "@p bra.uni WAIT_LOOP;\n"
               "trap;\n"
               "WAIT_DONE:\n}\n"
               :: "r"(bar), "r"(parity) : "memory");
}
__device__ __forceinline__ void mbar_wait_unless(uint32_t ok, uint32_t bar, uint32_t parity) {
  asm volatile("{\n.reg .pred p;\n.reg .u32 n;\n"
               "setp.ne.u32 p, %2, 0;\n"
               "@p bra.uni WAIT_DONE;\n"
               "mov.u32 n, 0;\n"
               "WAIT_LOOP:\n"
               "mbarrier.try_wait.parity.shared::cta.b64 p, [%0], %1;\n"
               "@p bra.uni WAIT_DONE;\n"
               "add.u32 n, n, 1;\n"
               "setp.lt.u32 p, n, 0x1000000;\n"
               "@p bra.uni WAIT_LOOP;\n"
               "trap;\n"
               "WAIT_DONE:\n}\n"
               :: "r"(bar), "r"(parity), "r"(ok) : "memory");
}
__device__ __forceinline__ uint32_t mbar_test(uint32_t bar, uint32_t parity) {
  uint32_t ok;
  asm volatile("{\n.reg .pred p;\nmbarrier.test_wait.parity.shared::cta.b64 p, [%1], %2;\nselp.u32 %0, 1, 0, p;\n}\n"
               : "=r"(ok) : "r"(bar), "r"(parity) : "memory");
  return ok;
}
__device__ __forceinline__ void cp_async16(uint32_t dst, const void* src) {
  asm volatile("cp.async.cg.shared.global [%0], [%1], 16;" :: "r"(dst), "l"(src) : "memory");
}
#define DIN_ADDR4                                                                        \
  "mov.b64 {x, y}, %0;\ndp4a.u32.u32 x, %8, 0x80, %11;\nmov.b64 %0, {x, y};\n"           \
  "mov.b64 {x, y}, %1;\ndp4a.u32.u32 x, %8, 0x8000, %11;\nmov.b64 %1, {x, y};\n"         \
  "mov.b64 {x, y}, %2;\ndp4a.u32.u32 x, %8, 0x800000, %11;\nmov.b64 %2, {x, y};\n"       \
  "mov.b64 {x, y}, %3;\ndp4a.u32.u32 x, %8, 0x80000000, %11;\nmov.b64 %3, {x, y};\n"
template<int T>
__device__ __forceinline__ void cp_group(const uint32_t (&dst)[4], uint64_t (&a)[4], uint32_t rows4, uint32_t base, uint64_t pol) {
  asm volatile("{\n.reg .u32 x, y;\n" DIN_ADDR4
               "cp.async.cg.shared.global.L2::cache_hint [%4 + %10], [%0], 16, %9;\n"
               "cp.async.cg.shared.global.L2::cache_hint [%5 + %10], [%1], 16, %9;\n"
               "cp.async.cg.shared.global.L2::cache_hint [%6 + %10], [%2], 16, %9;\n"
               "cp.async.cg.shared.global.L2::cache_hint [%7 + %10], [%3], 16, %9;\n}\n"
               : "+l"(a[0]), "+l"(a[1]), "+l"(a[2]), "+l"(a[3])
               : "r"(dst[0]), "r"(dst[1]), "r"(dst[2]), "r"(dst[3]), "r"(rows4), "l"(pol), "n"(T * 2048), "r"(base) : "memory");
}
template<int T>
__device__ __forceinline__ void cp_group_z(const uint32_t (&dst)[4], uint64_t (&a)[4], uint32_t rows4, uint32_t base, int left, uint64_t pol) {
  asm volatile("{\n.reg .u32 x, y;\n.reg .pred p0, p1, p2, p3;\n" DIN_ADDR4
               "setp.le.s32 p0, %12, %13;\nsetp.le.s32 p1, %12, %13 + 1;\nsetp.le.s32 p2, %12, %13 + 2;\nsetp.le.s32 p3, %12, %13 + 3;\n"
               "cp.async.cg.shared.global.L2::cache_hint [%4 + %10], [%0], 16, p0, %9;\n"
               "cp.async.cg.shared.global.L2::cache_hint [%5 + %10], [%1], 16, p1, %9;\n"
               "cp.async.cg.shared.global.L2::cache_hint [%6 + %10], [%2], 16, p2, %9;\n"
               "cp.async.cg.shared.global.L2::cache_hint [%7 + %10], [%3], 16, p3, %9;\n}\n"
               : "+l"(a[0]), "+l"(a[1]), "+l"(a[2]), "+l"(a[3])
               : "r"(dst[0]), "r"(dst[1]), "r"(dst[2]), "r"(dst[3]), "r"(rows4), "l"(pol), "n"(T * 2048), "r"(base),
                 "r"(left), "n"(T * 16) : "memory");
}
__device__ __forceinline__ void wait_for(uint32_t t, uint32_t most) {
  asm volatile("{\n.reg .u32 c;\n.reg .pred p;\n"
               "SPIN:\n"
               "mov.u32 c, %%globaltimer_lo;\n"
               "sub.u32 c, c, %0;\n"
               "setp.gt.u32 p, c, %1;\n"
               "@p bra.uni SPIN;\n}\n" :: "r"(t), "r"(~most) : "memory");
}
template<int T, int SH>
__device__ __forceinline__ void cp_group_m(const uint32_t (&dst)[4], uint64_t (&a)[4], uint32_t rows4, uint32_t base, uint32_t have, uint32_t go, uint64_t pol) {
  asm volatile("{\n.reg .u32 x, y;\n.reg .pred p0, p1, p2, p3, g;\n" DIN_ADDR4
               "setp.ne.u32 g, %14, 0;\n"
               "and.b32 x, %12, 1 << %13;\nsetp.eq.u32 p0, x, 0;\nand.b32 x, %12, 2 << %13;\nsetp.eq.u32 p1, x, 0;\n"
               "and.b32 x, %12, 4 << %13;\nsetp.eq.u32 p2, x, 0;\nand.b32 x, %12, 8 << %13;\nsetp.eq.u32 p3, x, 0;\n"
               "@g cp.async.cg.shared.global.L2::cache_hint [%4 + %10], [%0], 16, p0, %9;\n"
               "@g cp.async.cg.shared.global.L2::cache_hint [%5 + %10], [%1], 16, p1, %9;\n"
               "@g cp.async.cg.shared.global.L2::cache_hint [%6 + %10], [%2], 16, p2, %9;\n"
               "@g cp.async.cg.shared.global.L2::cache_hint [%7 + %10], [%3], 16, p3, %9;\n}\n"
               : "+l"(a[0]), "+l"(a[1]), "+l"(a[2]), "+l"(a[3])
               : "r"(dst[0]), "r"(dst[1]), "r"(dst[2]), "r"(dst[3]), "r"(rows4), "l"(pol), "n"(T * 2048), "r"(base),
                 "r"(have), "n"(SH), "r"(go) : "memory");
}
__device__ __forceinline__ uint32_t prmt(uint32_t a, uint32_t b, uint32_t sel) {
  uint32_t d;
  asm("prmt.b32 %0, %1, %2, %3;" : "=r"(d) : "r"(a), "r"(b), "r"(sel));
  return d;
}
__device__ __forceinline__ uint32_t ballot_bit(uint32_t x, uint32_t bit) {
  uint32_t d;
  asm volatile("{\n.reg .pred p;\n.reg .u32 t;\nand.b32 t, %1, %2;\nsetp.ne.u32 p, t, 0;\nvote.sync.ballot.b32 %0, p, 0xffffffff;\n}\n"
               : "=r"(d) : "r"(x), "r"(bit));
  return d;
}
__device__ __forceinline__ uint4 load_mask(const void* mask, uint32_t b, uint32_t i) {
  uint4 m;
  asm volatile("ld.global.nc.L1::no_allocate.v4.u32 {%0,%1,%2,%3}, [%4];"
               : "=r"(m.x), "=r"(m.y), "=r"(m.z), "=r"(m.w) : "l"(reinterpret_cast<const uint4*>(mask) + (b * 25u + i)));
  return m;
}
__device__ __forceinline__ uint32_t nonzero_as_one(uint32_t x) {
  uint32_t d;
  asm("set.neu.bf16x2.bf16x2 %0, %1, %2;" : "=r"(d) : "r"(x), "r"(0u));
  return d;
}
__device__ __forceinline__ void cp_async_arrive_noinc(uint32_t bar) {
  asm volatile("cp.async.mbarrier.arrive.noinc.shared::cta.b64 [%0];" :: "r"(bar) : "memory");
}
__device__ __forceinline__ void ldsm_x4(uint32_t addr, uint32_t& r0, uint32_t& r1, uint32_t& r2, uint32_t& r3) {
  asm volatile("ldmatrix.sync.aligned.m8n8.x4.shared.b16 {%0,%1,%2,%3}, [%4];"
               : "=r"(r0), "=r"(r1), "=r"(r2), "=r"(r3) : "r"(addr) : "memory");
}
__device__ __forceinline__ void ldsm_x4_t(uint32_t addr, uint32_t& r0, uint32_t& r1, uint32_t& r2, uint32_t& r3) {
  asm volatile("ldmatrix.sync.aligned.m8n8.x4.trans.shared.b16 {%0,%1,%2,%3}, [%4];"
               : "=r"(r0), "=r"(r1), "=r"(r2), "=r"(r3) : "r"(addr) : "memory");
}
__device__ __forceinline__ void stsm_x4(uint32_t addr, uint32_t r0, uint32_t r1, uint32_t r2, uint32_t r3) {
  asm volatile("stmatrix.sync.aligned.m8n8.x4.shared.b16 [%0], {%1,%2,%3,%4};"
               :: "r"(addr), "r"(r0), "r"(r1), "r"(r2), "r"(r3) : "memory");
}
__device__ __forceinline__ void stsm_x2(uint32_t addr, uint32_t r0, uint32_t r1) {
  asm volatile("stmatrix.sync.aligned.m8n8.x2.shared.b16 [%0], {%1,%2};"
               :: "r"(addr), "r"(r0), "r"(r1) : "memory");
}
__device__ __forceinline__ void mma_bf16(float (&c)[4], const uint32_t (&a)[4], uint32_t b) {
  asm("mma.sync.aligned.m16n8k16.row.col.f32.bf16.bf16.f32 {%0,%1,%2,%3}, {%4,%5,%6,%7}, {%8,%8}, {%0,%1,%2,%3};"
      : "+f"(c[0]), "+f"(c[1]), "+f"(c[2]), "+f"(c[3]) : "r"(a[0]), "r"(a[1]), "r"(a[2]), "r"(a[3]), "r"(b));
}
__device__ __forceinline__ uint32_t hfma2_bf16(uint32_t a, uint32_t b, uint32_t c) {
  uint32_t d;
  asm volatile("fma.rn.bf16x2 %0, %1, %2, %3;" : "=r"(d) : "r"(a), "r"(b), "r"(c));
  return d;
}
__device__ __forceinline__ uint32_t pack_bf16(float lo, float hi) {
  uint32_t d;
  asm("cvt.rn.bf16x2.f32 %0, %1, %2;" : "=r"(d) : "f"(hi), "f"(lo));
  return d;
}
__device__ __forceinline__ uint32_t lds32(uint32_t a) {
  uint32_t v; asm volatile("ld.shared.u32 %0, [%1];" : "=r"(v) : "r"(a) : "memory"); return v;
}
__device__ __forceinline__ uint32_t lds16(uint32_t a) {
  uint32_t v; asm volatile("ld.shared.u16 %0, [%1];" : "=r"(v) : "r"(a) : "memory"); return v;
}
__device__ __forceinline__ void sts32(uint32_t a, uint32_t v) {
  asm volatile("st.shared.u32 [%0], %1;" :: "r"(a), "r"(v) : "memory");
}
__device__ __forceinline__ void sts16(uint32_t a, uint32_t v) {
  asm volatile("st.shared.u16 [%0], %1;" :: "r"(a), "h"((unsigned short)v) : "memory");
}
__device__ __forceinline__ void sts8(uint32_t a, uint32_t v) {
  asm volatile("st.shared.u8 [%0], %1;" :: "r"(a), "r"(v) : "memory");
}
constexpr uint32_t DESC_ROWS = 0x40000040u, DESC_HALVES = 0x80000020u;
__device__ __forceinline__ uint32_t desc_lo(uint32_t addr) { return ((addr & 0x3FFFF) >> 4) | (1u << 16); }

__device__ __forceinline__ uint4 lds128(uint32_t a) {
  uint4 v;
  asm volatile("ld.shared.v4.u32 {%0,%1,%2,%3}, [%4];" : "=r"(v.x), "=r"(v.y), "=r"(v.z), "=r"(v.w) : "r"(a) : "memory");
  return v;
}
__device__ __forceinline__ void sts128(uint32_t a, uint4 v) {
  asm volatile("st.shared.v4.u32 [%0], {%1,%2,%3,%4};" :: "r"(a), "r"(v.x), "r"(v.y), "r"(v.z), "r"(v.w) : "memory");
}
__device__ __forceinline__ void prefetch_l2(const void* p, uint32_t bytes) {
  asm volatile("cp.async.bulk.prefetch.L2.global [%0], %1;" :: "l"(p), "r"(bytes) : "memory");
}

__device__ __forceinline__ void prefetch_piece(const void* p, uint32_t bytes) {
  asm volatile("{\n.reg .u32 t, c;\n.reg .u64 a;\nmov.u32 t, %%tid.x;\nmov.u32 c, %%ctaid.x;\n"
               "mad.lo.u32 c, c, %2, t;\nmad.wide.u32 a, c, %1, %0;\nprefetch.global.L2 [a];\n}\n"
               :: "l"(p), "r"(bytes), "n"(NTHREADS) : "memory");
}

template<int ND>
__device__ __forceinline__ void tanh_range(float (&d)[ND], int i0, int i1) {
#pragma unroll
  for (int i = i0; i < i1; i++) asm volatile("tanh.approx.f32 %0, %0;" : "+f"(d[i ^ 2]));
}
template<int ND>
__device__ __forceinline__ uint32_t mix(const float (&d)[ND], int i, float w2a, float w2b, float c32) {
  uint32_t p;
  asm volatile("{\n.reg .f32 x, y;\nfma.rn.f32 x, %3, %6, %7;\nfma.rn.f32 y, %4, %6, %7;\n"
               "fma.rn.f32 x, %1, %5, x;\nfma.rn.f32 y, %2, %5, y;\ncvt.rn.bf16x2.f32 %0, y, x;\n}\n"
               : "=r"(p) : "f"(d[4 * i]), "f"(d[4 * i + 1]), "f"(d[4 * i + 2]), "f"(d[4 * i + 3]), "f"(w2a), "f"(w2b), "f"(c32));
  return p;
}
__device__ __forceinline__ uint32_t size_bit(int n) { return n > 120 ? H_16 : H_12 << (max(n - 89, 0) >> 3); }
template<int V> struct Int { static constexpr int value = V; };

__global__ void __launch_bounds__(NTHREADS, 1)
din_kernel(const __nv_bfloat16* __restrict__ mask, const __nv_bfloat16* __restrict__ target, int B, int grid,
           uint32_t pf_mask, uint32_t pf_tgt, const __nv_bfloat16* __restrict__ w1, const __nv_bfloat16* __restrict__ hist,
           const __nv_bfloat16* __restrict__ b1, const __nv_bfloat16* __restrict__ w2,
           const __nv_bfloat16* __restrict__ b2, __nv_bfloat16* __restrict__ out, unsigned int* counter, int pace,
           int slow_from, int pace_slow, int spread, int align) {
  prefetch_piece(mask, pf_mask);
  asm volatile("{\n.reg .pred p;\n.reg .u32 c;\nmov.u32 c, %%clock;\nsetp.eq.u32 p, c, %0;\n@p nanosleep.u32 1;\n}\n" :: "n"(0) : "memory");
  prefetch_piece(target, pf_tgt);
  extern __shared__ unsigned char smem_raw[];
  const uint32_t sb = (smem_u32(smem_raw) + 1023u) & ~1023u;
  const int tid = threadIdx.x, lane = tid & 31;
  const int warp = __shfl_sync(0xffffffffu, tid >> 5, 0);
#define ACT NCW
  const int bstep = ACT * grid;

  if (warp < NCW * 4) {
    const int wg = warp >> 2, w = warp & 3;
    const int g = lane >> 2;
    const uint32_t ring = sb + wg * RING_BYTES;
    const bool active = wg * grid + (int)blockIdx.x < B && wg < ACT;
    {
      const int t = tid & 127;
      const uint32_t dst = sb + ((t ^ ((t >> 3) & 7)) << 4);
      const char* src = reinterpret_cast<const char*>(w1) + t * 16;
#pragma unroll
      for (int i = 0; i < 4; i++) cp_async16(dst + w1_at(i) + wg * 2048, src + i * 8192 + wg * 2048);
      cp_async16(dst + w1_at(0) + (wg >> 1) * RING_BYTES + (wg & 1) * SLOT_BYTES + 6144, src + wg * 8192 + 6144);
      if (wg == 0) cp_async16(dst + w1_at(3) + 6144, src + 3 * 8192 + 6144);
      if (lane < 8) {
        if (w == 0 && active) cp_async16(ring + R_TGT0 + lane * 16, target + (size_t)(wg * grid + blockIdx.x) * kD + lane * 8);
        if (w == 1 && wg < 2) cp_async16(ring + R_VEC + lane * 16, (wg ? w2 : b1) + lane * 8);
      }
    }
    if (w == 2) sts32(ring + R_SEL + lane * 4, 0x3f803f80u);
    uint32_t rb2;
    asm volatile("ld.global.nc.u16 %0, [%1];" : "=r"(rb2) : "l"(b2));
    asm volatile("setmaxnreg.inc.sync.aligned.u32 %0;" :: "n"(CONS_REGS));
    asm volatile("cp.async.wait_all;" ::: "memory");
    asm volatile("bar.sync 1, %0;" :: "n"(NCW * 160) : "memory");
    const uint32_t half2 = 0x3f003f00u, nhalf2 = 0xbf00bf00u, nzero2 = 0x80008000u;
    const uint32_t vec = sb + R_VEC + (16 * w + g) * 2;
    const float w2a = 0.5f * __uint_as_float(lds16(vec + RING_BYTES) << 16);
    const float w2b = 0.5f * __uint_as_float(lds16(vec + RING_BYTES + 16) << 16);
    const uint32_t rw2 = lds32(sb + RING_BYTES + R_VEC + lane * 4);
    float c32 = __uint_as_float(rw2 << 16) + __uint_as_float(rw2 & 0xffff0000u);
#pragma unroll
    for (int o = 16; o; o >>= 1) c32 += __shfl_xor_sync(0xffffffffu, c32, o);
    c32 = (0.5f * c32 + __uint_as_float(rb2 << 16)) * (1.0f / 32.0f);
    uint32_t bq[4];
    bq[2] = hfma2_bf16(lds16(vec), half2, nzero2);
    bq[3] = hfma2_bf16(lds16(vec + 16), half2, nzero2);
    if (lane & 3) bq[2] = bq[3] = 0;
    uint32_t wac[16], wd[16], wbc[16];
    {
      const int mi = lane >> 3, rr = lane & 7;
      const uint32_t a0 = sb + (8 * (mi >> 1) + rr) * 128 + (((2 * w + (mi & 1)) ^ rr) << 4);
#pragma unroll
      for (int ks = 0; ks < 4; ks++) {
        uint32_t A[4], Bm[4], C[4], Dm[4];
        ldsm_x4_t(a0 + ks * 2048 + w1_at(0), A[0], A[1], A[2], A[3]);
        ldsm_x4_t(a0 + ks * 2048 + w1_at(1), Bm[0], Bm[1], Bm[2], Bm[3]);
        ldsm_x4_t(a0 + ks * 2048 + w1_at(2), C[0], C[1], C[2], C[3]);
        ldsm_x4_t(a0 + ks * 2048 + w1_at(3), Dm[0], Dm[1], Dm[2], Dm[3]);
#pragma unroll
        for (int e = 0; e < 4; e++) {
          wac[4 * ks + e] = hfma2_bf16(A[e], half2, hfma2_bf16(C[e], half2, nzero2));
          wbc[4 * ks + e] = hfma2_bf16(Bm[e], half2, hfma2_bf16(C[e], nhalf2, nzero2));
          wd[4 * ks + e] = hfma2_bf16(Dm[e], half2, nzero2);
        }
      }
    }
    asm volatile("fence.proxy.async.shared::cta;" ::: "memory");
    asm volatile("bar.sync 5, %0;" :: "n"(NCW * 128) : "memory");

    const uint32_t ln = __shfl_sync(0xffffffffu, lane, lane);
    const uint32_t q0 = __shfl_sync(0xffffffffu, (lane & 3) ? 0u : 0xffffffffu, lane);
    const uint32_t meta = __shfl_sync(0xffffffffu, 0x88dddd88u + (grid >> 20), lane);
    const uint32_t zr = grid >> 20;
    const uint32_t sel = (ring + R_SEL) >> 4;
    const uint32_t ost = __shfl_sync(0xffffffffu, (lane >> 4) * 1024 + w * 256 + (lane & 15) * 16, lane);
    const uint32_t first = ring;
    const uint32_t last = first + (NSLOT - 1) * SLOT_BYTES;
    uint32_t sa = first, phase = 0;
    uint32_t we[16];
    auto make_weff = [&](uint32_t ta) {
      uint32_t t[8];
      ta += (ln & 24) << 1;
      ldsm_x4(ta, t[0], t[1], t[2], t[3]);
      ldsm_x4(ta + 64, t[4], t[5], t[6], t[7]);
#pragma unroll
      for (int i = 0; i < 16; i++) we[i] = hfma2_bf16(t[i >> 1], wd[i], wac[i]);
    };
    auto make_bq = [&](const float (&bz)[4]) {
#pragma unroll
      for (int e = 0; e < 2; e++) {
        const uint32_t v = __float_as_uint(bz[2 * e]) & q0;
        const float hi = __uint_as_float(v & 0xffff0000u);
        bq[e] = pack_bf16(__uint_as_float(v) - hi, hi);
      }
    };
    if (active) {
      {
        float bz[4];
        uint64_t d0 = (uint64_t)DESC_ROWS << 32 | (ring + R_TGT0) >> 4;
        mma_fence();
        bias_out<0>(bz, wbc, d0);
        make_weff(ring + R_TGT0);
        mma_wait<0>(bz);
        make_bq(bz);
      }
      uint32_t raw = 0, cur, hdr;
      uint32_t full = 0;
      auto finish = [&]() {
        asm volatile("bar.sync %0, 128;" :: "r"(2 + wg) : "memory");
        const uint32_t ra = cur + S_OUT + w * 1024 + ln * 16;
        uint32_t f0[4], f1[4];
        ldsm_x4_t(ra, f0[0], f0[1], f0[2], f0[3]);
        ldsm_x4_t(ra + 512, f1[0], f1[1], f1[2], f1[3]);
        uint32_t* dst = reinterpret_cast<uint32_t*>(out) + (lds32(first + R_STOP + 4) + 4 * w + (ln & 4) * 4 + (ln >> 3));
        float c0[4] = {0.f, 0.f, 0.f, 0.f}, c1[4] = {0.f, 0.f, 0.f, 0.f};
        mma_bf16(c0, f0, 0x3f803f80u);
        mma_bf16(c1, f1, 0x3f803f80u);
        *dst = pack_bf16(c0[0] + c1[0], c0[2] + c1[2]);
      };
      auto chunk = [&](auto groups) {
        constexpr int N8 = decltype(groups)::value, NY = N8 - NA;
        constexpr int KT = (N8 + 1) / 2, E1 = KT - (N8 == 16 ? 3 : KL), E0 = N8 < 16 && K0 < E1 ? K0 : E1;
        float x[4 * NA], y[4 * NY], bz[4], o[16];
        uint32_t a[4 * E0], a1[E1 > E0 ? 4 * (E1 - E0) : 4], a2[4 * (KT - E1)];
        auto M = [&](int i0, int i1) {
#pragma unroll
          for (int i = i0; i < i1; i++) {
            uint32_t p = i < NA ? mix(x, i, w2a, w2b, c32) : i < N8 ? mix(y, i - NA, w2a, w2b, c32) : 0;
            if (N8 == 16) {
              uint32_t m = 0x3f803f80u;
              asm volatile("{\n.reg .pred p;\nsetp.ne.u32 p, %1, 0;\n@p ld.shared.u32 %0, [%2];\n}\n"
                           : "+r"(m) : "r"(hdr & H_GENERAL), "r"(cur + S_MASK + i * 16 + (ln & 3) * 4) : "memory");
              p = hfma2_bf16(p, m, 0x80008000u);
            }
            if (i < 2 * E0) a[2 * i] = a[2 * i + 1] = p;
            else if (i < 2 * E1) a1[2 * i - 4 * E0] = a1[2 * i - 4 * E0 + 1] = p;
            else a2[2 * i - 4 * E1] = a2[2 * i - 4 * E1 + 1] = p;
          }
        };
        auto header = [&]() {
          raw = lds32(sa + S_HDR);
          raw = (raw >> 31) == phase ? 0 : raw;
        };
        const uint32_t sta = cur + S_OUT + ost;
        uint64_t db = (uint64_t)(DESC_ROWS + (cur >> 24)) << 32 | cur >> 4;
        const uint32_t par = phase;
        phase ^= sa == last;
        sa = sa == last ? first : sa + SLOT_BYTES;
        mma_fence();
        bias_in(x, bq, sel);
        bias_in(y, bq, sel);
        mbar_wait_unless(full, cur + S_FULL, par);
        mma_fence();
        gemm1<0>(x, we, db);
        bias_out<S_TGT / 16>(bz, wbc, db);
        mma_wait<1>(x);
        const uint32_t there = mbar_test(cur + S_REST, par);
        tanh_range(x, 0, 4 * SA);
        mbar_wait_unless(there, cur + S_REST, par);
        mma_fence();
        gemm1<64 * NA>(y, we, db);
        tanh_range(x, 4 * SA, 4 * (SA + SB));
        if (__builtin_expect(zr != 0, 0)) {
          __nanosleep(zr);
#pragma unroll
          for (int i = 4 * (SA + SB); i < 4 * NA; i++) asm volatile("mov.b32 %0, %1;" : "=f"(x[i]) : "r"(ln));
        }
        tanh_range(x, 4 * (SA + SB), 4 * NA);
        M(0, NA - 1);
        if (__builtin_expect(zr != 0, 0)) {
          __nanosleep(zr);
#pragma unroll
          for (int i = 0; i < NA - 1; i++) sts32(zr + i, a[2 * i]);
#pragma unroll
          for (int i = 4 * NA - 4; i < 4 * NA; i++) sts32(zr + i, __float_as_uint(x[i]));
        }
        mma_wait<0>(y);
        asm volatile("" : "+f"(bz[0]), "+f"(bz[2]) :: "memory");
        header();
        tanh_range(y, 0, 4 * (2 * E0 - NA));
        make_weff(cur + S_TGT);
        M(NA - 1, 2 * E0);
        auto after = [&](uint32_t g, uint32_t u, auto more) {
          asm volatile("{\n.reg .b32 lo, hi, z;\n.reg .pred p;\nand.b32 z, %1, %2;\nsetp.ne.u32 p, z, 0;\nvote.sync.ballot.b32 z, p, 0xffffffff;\n"
                       "and.b32 z, z, %4;\nmov.b64 {lo, hi}, %0;\nadd.u32 hi, hi, %3;\nadd.u32 hi, hi, z;\nmov.b64 %0, {lo, hi};\n}\n"
                       : "+l"(db) : "r"(g), "r"(zr), "n"(decltype(more)::value), "r"(u));
        };
        constexpr bool TWO = E1 == E0;
        make_bq(bz);
        raw = __shfl_sync(0xffffffffu, raw, 0);
        after(a[4 * E0 - 2] | a[4 * E0 - 4] | (TWO ? bq[0] | bq[1] | sta : 0), TWO ? raw : ~0u, Int<(int)(DESC_HALVES - DESC_ROWS)>());
        gemm2_first<0>(o, a, db, meta);
        if constexpr (E1 > E0) {
          tanh_range(y, 4 * (2 * E0 - NA), 4 * (2 * E1 - NA));
          M(2 * E0, 2 * E1);
          after(bq[0] | bq[1] | sta, raw, Int<0>());
          gemm2_more<128 * E0>(o, a1, db, meta);
        }
        tanh_range(y, 4 * (2 * E1 - NA), 4 * NY);
        M(2 * E1, 2 * KT);
        gemm2_more<128 * E1>(o, a2, db, meta);
        full = mbar_test(sa + S_FULL, phase);
        mma_wait<0>(o);
#pragma unroll
        for (int j = 0; j < 2; j++)
          stsm_x4(sta + j * 2048, pack_bf16(o[8 * j], o[8 * j + 2]), pack_bf16(o[8 * j + 1], o[8 * j + 3]),
                  pack_bf16(o[8 * j + 4], o[8 * j + 6]), pack_bf16(o[8 * j + 5], o[8 * j + 7]));
        __syncwarp();
        asm volatile("{\n.reg .pred p;\nsetp.eq.u32 p, %1, 0;\n@p mbarrier.arrive.shared::cta.b64 _, [%0];\n}\n"
                     :: "r"(cur + S_EMPTY), "r"(ln | (hdr & H_FINAL)) : "memory");
      };
      while (true) {
        hdr = __shfl_sync(0xffffffffu, raw, 0);
        cur = sa;
        if (hdr & H_13) { chunk(Int<13>()); if (hdr & H_FINAL) break; }
        else if (hdr & H_12) { chunk(Int<12>()); if (hdr & H_FINAL) break; }
        else if (hdr & H_14) { chunk(Int<14>()); if (hdr & H_FINAL) break; }
        else if (hdr & H_15) { chunk(Int<15>()); if (hdr & H_FINAL) break; }
        else if (hdr & H_STOP) return;
        else if (hdr) { chunk(Int<16>()); if (hdr & H_FINAL) break; }
        else {
          asm volatile("{\n.reg .pred p;\n.reg .u32 n, t;\nmov.u32 n, 0;\n"
                       "AGAIN:\nnanosleep.u32 32;\nld.shared.u32 %0, [%1];\nshfl.sync.idx.b32 %0, %0, 0, 31, 0xffffffff;\n"
                       "shr.u32 t, %0, 31;\nsetp.ne.u32 p, t, %2;\n@p bra.uni THERE;\n"
                       "add.u32 n, n, 1;\nsetp.lt.u32 p, n, 0x1000000;\n@p bra.uni AGAIN;\ntrap;\nTHERE:\n}\n"
                       : "=r"(raw) : "r"(sa + S_HDR), "r"(phase) : "memory");
        }
      }
      finish();
    }
  } else {
    const int pw = warp - NCW * 4;
    const uint32_t ring = sb + pw * RING_BYTES;
    asm volatile("setmaxnreg.dec.sync.aligned.u32 %0;" :: "n"(PROD_REGS));
    if (pw < NCW) {
      int b = pw * grid + blockIdx.x, bn = b + bstep;
      uint4 mw = load_mask(mask, min(b, B - 1), min(lane, 24));
      if (lane == 0) {
#pragma unroll
        for (int i = 0; i < NSLOT; i++) {
          mbar_init(ring + i * SLOT_BYTES + S_FULL, 33);
          mbar_init(ring + i * SLOT_BYTES + S_REST, 33);
          mbar_arrive(ring + i * SLOT_BYTES + S_REST);
          mbar_init(ring + i * SLOT_BYTES + S_EMPTY, 4);
          sts32(ring + i * SLOT_BYTES + S_HDR, 0);
        }
        sts32(ring + R_STOP, b < B && pw < ACT ? 0 : ring);
      }
      sts32(sb + R_PACE + lane * 4, 0);
      sts32(sb + R_ADJ, 0);
      asm volatile("bar.arrive 1, %0;" :: "n"(NCW * 160) : "memory");
      asm volatile("bar.arrive 6, 128;" ::: "memory");
      if (pw >= ACT) return;
      const uint32_t list = ring + R_LIST;
      uint32_t lt;
      asm("mov.u32 %0, %%lanemask_lt;" : "=r"(lt));
      const uint32_t ln = __shfl_sync(0xffffffffu, lane, lane);
      const uint32_t r4 = (ln >> 3) * 4, c16 = (ln & 7) * 16, l25 = min(ln, 24u);
      const uint32_t pick = ln < 25 ? 0xeca8 : 0x9999;
      uint32_t dst[4];
#pragma unroll
      for (int i = 0; i < 4; i++) dst[i] = ring + (r4 + i) * 128 + (c16 ^ (((r4 + i) & 7) << 4));
      uint64_t pol;
      asm("createpolicy.fractional.L2::evict_first.b64 %0, 1.0;" : "=l"(pol));
      uint32_t sa = ring, phase = 1;
      const uint32_t wrap = (uint32_t)(max(B - NSTATIC * bstep, 0) + bstep - 1);
      auto next_slot = [&]() {
        const bool wrapped = sa == ring + (NSLOT - 1) * SLOT_BYTES;
        const int step = wrapped ? -(NSLOT - 1) * SLOT_BYTES : SLOT_BYTES;
        sa += step;
        phase ^= wrapped;
#pragma unroll
        for (int i = 0; i < 4; i++) dst[i] += step;
      };
      uint32_t claimer = ln;
      uint32_t drawn, started = 0;
      int mean16 = 0;
      auto draw = [&]() {
        drawn = B;
        asm volatile("{\n.reg .pred p;\nsetp.eq.u32 p, %3, 0;\n@p atom.global.inc.u32 %0, [%1], %2;\n}\n"
                     : "+r"(drawn) : "l"(counter), "r"(wrap), "r"(claimer) : "memory");
      };
      if (b >= B) draw();
      while (b < B) {
        const uint32_t e0 = nonzero_as_one(mw.x), e1 = nonzero_as_one(mw.y);
        const uint32_t e2 = nonzero_as_one(mw.z), e3 = nonzero_as_one(mw.w);
        const uint32_t nonbin = (e0 ^ mw.x) | (e1 ^ mw.y) | (e2 ^ mw.z) | (e3 ^ mw.w);
        const uint32_t sA = prmt(e0, e1, pick), sB = prmt(e2, e3, pick);
        const uint32_t pA = (sA & 0x01010101u) * 0x01010101u;
        const uint32_t pB = ((sB & 0x01010101u) + (pA >> 24)) * 0x01010101u;
        uint32_t pos = 0;
        int n = 0;
#pragma unroll
        for (int k = 0; k < 4; k++) {
          const uint32_t bal = ballot_bit(pB, 0x01000000u << k);
          pos += __popc(bal & lt) << k;
          n += __popc(bal) << k;
        }
        const uint32_t general = __any_sync(0xffffffffu, nonbin != 0);
        const uint32_t aA = (pA + pos * 0x01010101u) | ~sA, aB = (pB + pos * 0x01010101u) | ~sB;
#pragma unroll
        for (int i = 0; i < 8; i++) sts8(list - 1 + prmt(i < 4 ? aA : aB, 0, 0x4440 + (i & 3)), 8 * ln + i);
        __syncwarp();

        const uint64_t src = reinterpret_cast<uint64_t>(hist) + (uint64_t)b * (kL * kD * 2);
        const bool no_carry = (uint32_t)src <= 0xffffffffu - kL * kD * 2;
        auto begin_fill = [&](uint32_t h, uint32_t part, int nc, int bt, auto extra) {
          mbar_wait(sa + S_EMPTY, phase);
          if (bt >= B && !part) h |= H_FINAL;
          asm volatile("{\n.reg .pred p;\nsetp.ne.u32 p, %3, 0;\n@p st.shared.v2.u32 [%0], {%1, %2};\n}\n"
                       :: "r"(ring + R_STOP), "r"(sa + (phase ^ 1)), "r"(b * 32), "r"(h & H_FINAL) : "memory");
          extra();
          sts32(sa + S_HDR, h | phase << 31);
          sts32(sa + S_ROW + phase * 4, b | part);
          asm volatile("{\n.reg .pred p;\nsetp.eq.u32 p, %1, 0;\n@p mbarrier.arrive.shared::cta.b64 _, [%0];\n}\n"
                       :: "r"(sa + S_FULL), "r"(ln) : "memory");
          mean16 = mean16 == 0 ? 16 * nc : bn >= slow_from ? mean16 : mean16 + nc - (mean16 >> 4);
          asm volatile("{\n.reg .u32 c;\n"
                       "mov.u32 c, %%globaltimer_lo;\n"
                       "red.shared.max.u32 [%1], c;\n"
                       "atom.shared.add.u32 %0, [%1], %2;\n}\n"
                       : "=r"(started) : "r"(sb + R_PACE + ln * 4),
                         "r"(bn >= slow_from ? mean16 * (pace_slow + (int)lds32(sb + R_ADJ)) >> 12 : nc * pace >> 4) : "memory");
          started = __shfl_sync(0xffffffffu, started, 0);
          if (!(part & ROW_REST)) mw = load_mask(mask, min(bn, B - 1), l25);
          wait_for(started, pace * (CHUNK / 4));
          if (!(part & ROW_REST)) draw();
          asm volatile("cp.async.ca.shared.global [%0], [%1], 4;"
                       :: "r"(sa + S_TGT + ln * 4), "l"(reinterpret_cast<const uint32_t*>(target) + ((uint32_t)min(bt, B - 1) * 32u + ln)) : "memory");
        };
        auto end_fill = [&](int nc) {
          cp_async_arrive_noinc(sa + S_REST);
          next_slot();
        };
        const uint32_t base = (uint32_t)src + c16;
        uint64_t a[4];
        a[0] = a[1] = a[2] = a[3] = (uint64_t)((uint32_t)(src >> 32) + (ln >> 5)) << 32;
        if (__builtin_expect(no_carry && !general && n >= 80 && n <= CHUNK, 1)) {
          uint32_t idx[7];
#pragma unroll
          for (int t = 0; t < 7; t++) idx[t] = lds32(list + r4 + t * 16);
          uint32_t have;
          asm("bmsk.clamp.b32 %0, 0, %1;" : "=r"(have) : "r"(max(n - 80 - (int)r4, 0)));
          begin_fill(size_bit(n), 0, n, bn, [](){});
          cp_group<0>(dst, a, idx[0], base, pol);
          cp_group<1>(dst, a, idx[1], base, pol);
          cp_group<2>(dst, a, idx[2], base, pol);
          cp_async_arrive_noinc(sa + S_FULL);
          if (bn >= slow_from) wait_for(started + spread, spread);
          cp_group<3>(dst, a, idx[3], base, pol);
          cp_group<4>(dst, a, idx[4], base, pol);
          cp_group_m<5, 0>(dst, a, idx[5], base, have, 1, pol);
          cp_group_m<6, 16>(dst, a, idx[6], base, have, n > 96, pol);
          if (n > 112) cp_group_z<7>(dst, a, lds32(list + r4 + 112), base, n - r4, pol);
          end_fill(n);
        } else if (no_carry && !general) {
          int nc = n <= CHUNK ? n : n <= 160 ? 64 : 96;
          uint32_t la = list + r4, part = n <= CHUNK ? 0 : ROW_MORE;
#pragma unroll 1
          while (true) {
            begin_fill(size_bit(nc), part, nc, part == ROW_MORE ? b : bn, [](){});
            const int left = nc - r4;
            cp_group_z<0>(dst, a, lds32(la), base, left, pol);
            cp_group_z<1>(dst, a, lds32(la + 16), base, left, pol);
            cp_group_z<2>(dst, a, lds32(la + 32), base, left, pol);
            cp_async_arrive_noinc(sa + S_FULL);
            if (bn >= slow_from) wait_for(started + spread, spread);
            cp_group_z<3>(dst, a, lds32(la + 48), base, left, pol);
            cp_group_z<4>(dst, a, lds32(la + 64), base, left, pol);
            cp_group_z<5>(dst, a, lds32(la + 80), base, left, pol);
            cp_group_z<6>(dst, a, lds32(la + 96), base, left, pol);
            cp_group_z<7>(dst, a, lds32(la + 112), base, left, pol);
            end_fill(nc);
            if (part != ROW_MORE) break;
            la += nc;
            nc = n - nc;
            part = ROW_REST;
          }
        } else {
          int r0 = 0;
#pragma unroll 1
          do {
            const int nc = min(n - r0, CHUNK);
            const bool more = r0 + CHUNK < n;
            begin_fill(general ? H_GENERAL : H_16, (more ? ROW_MORE : 0u) | (r0 ? ROW_REST : 0u), nc, more ? b : bn, [&]() {
#pragma unroll 1
              for (int z = ln; general && z < CHUNK; z += 32) {
                uint32_t v = 0;
                if (z < nc) {
                  uint32_t row;
                  asm volatile("ld.shared.u8 %0, [%1];" : "=r"(row) : "r"(list + r0 + z) : "memory");
                  v = __bfloat16_as_ushort(mask[(size_t)b * kL + row]);
                }
                sts16(sa + S_MASK + z * 2, v);
              }
              __syncwarp();
            });
#pragma unroll 1
            for (int z = r4 >> 2; z < CHUNK; z += 4) {
              uint32_t row;
              asm volatile("ld.shared.u8 %0, [%1];" : "=r"(row) : "r"(list + r0 + z) : "memory");
              asm volatile("cp.async.cg.shared.global [%0], [%1], 16, %2;"
                           :: "r"(sa + z * 128 + (c16 ^ ((z & 7) << 4))), "l"(src + c16 + (z < nc ? row : 0) * 128),
                              "r"(z < nc ? 16 : 0) : "memory");
            }
            cp_async_arrive_noinc(sa + S_FULL);
            end_fill(nc);
            r0 += CHUNK;
          } while (r0 < n);
        }
        b = bn;
        bn = __shfl_sync(0xffffffffu, drawn, 0) + NSTATIC * bstep;
        if (bn >= B) claimer = 1;
        asm volatile("{\n.reg .pred p;\nsetp.lt.u32 p, %2, %3;\n@p st.shared.u32 [%0], %1;\n}\n"
                     :: "r"(sb + R_ADJ), "r"((B - bn - (grid >> 1)) * align >> 8), "r"(B - 1 - bn), "r"(grid) : "memory");
      }
      if (lds32(ring + R_STOP) == 0) {
        mbar_wait(sa + S_EMPTY, phase);
        sts32(sa + S_HDR, H_STOP | phase << 31);
        sts32(ring + R_STOP, sa + (phase ^ 1));
      }
      asm volatile("cp.async.wait_all;" ::: "memory");
    } else {
      uint32_t due = clock();
      int s0 = NSTATIC * bstep + (PF_EARLY * grid + blockIdx.x) * PF_ROWS;
      auto prefetch = [&]() {
        const int cnt = min(PF_ROWS, B - s0);
        if (lane == 0) {
          prefetch_l2(mask + (size_t)s0 * kL, cnt * kL * 2);
          prefetch_l2(target + (size_t)s0 * kD, cnt * kD * 2);
        }
        s0 += grid * PF_ROWS;
      };
#pragma unroll 1
      for (int j = PF_EARLY; j < PF_FAST && s0 < B; j++) {
        while ((int)(due - (uint32_t)clock()) > 0) {}
        prefetch();
        due += PF_CYCLES;
      }
      due += (PF_FAST - 1) * PF_SLOW - (PF_FAST - PF_EARLY) * PF_CYCLES + (blockIdx.x & 255) * (PF_SLOW / 256);
      asm volatile("bar.sync 6, 128;" ::: "memory");
      const uint32_t ln = __shfl_sync(0xffffffffu, lane, lane);
      const uint32_t home = sb + min(ln, NCW - 1u) * RING_BYTES;
      uint32_t mine = ln < NCW ? home : 0;
      const uint32_t word = __shfl_sync(0xffffffffu, (lane & 4) * 4 + (lane & 3) * 4 + (lane >> 3), lane);
      uint32_t idle = 0, r = 0, at;
      auto poll = [&]() {
        uint32_t ready;
        asm volatile("{\n.reg .pred p;\nsetp.ne.u32 p, %3, 0;\n@p mbarrier.test_wait.parity.shared::cta.b64 p, [%1], %2;\n"
                     "vote.sync.ballot.b32 %0, p, 0xffffffff;\n}\n"
                     : "=r"(ready) : "r"((mine & ~1u) + S_EMPTY), "r"(mine & 1), "r"(mine) : "memory");
        static_assert(NCW == 3, "");
        const uint32_t pick = ((r == 0 ? 0x5a53u : r == 1 ? 0xaa13u : 0x1213u) >> (2 * ready)) & 3;
        at = __shfl_sync(0xffffffffu, mine, pick);
        r = ready ? pick : r;
      };
      poll();
#pragma unroll 1
      while (true) {
        if (at) {
          const uint32_t sa = at & ~1u, carry = sb + r * RING_BYTES + R_CARRY + ln * 8;
          uint32_t f[8][4];
#pragma unroll
          for (int i = 0; i < 8; i++) ldsm_x4_t(sa + S_OUT + ln * 16 + (i >> 2) * 512 + (i & 3) * 1024, f[i][0], f[i][1], f[i][2], f[i][3]);
          const uint32_t row = lds32(sa + S_ROW + 4 - (at & 1) * 4);
          if (ln == r) mine = sa == home + (NSLOT - 1) * SLOT_BYTES ? (at - (NSLOT - 1) * SLOT_BYTES) ^ 1 : at + SLOT_BYTES;
          float c[8][4];
#pragma unroll
          for (int i = 0; i < 8; i++) {
            c[i][0] = c[i][1] = c[i][2] = c[i][3] = 0.f;
            mma_bf16(c[i], f[i], 0x3f803f80u);
          }
          poll();
          asm volatile("{\n.reg .pred p;\nsetp.eq.u32 p, %1, 0;\n@p mbarrier.arrive.shared::cta.b64 _, [%0];\n}\n"
                       :: "r"(sa + S_REST), "r"(ln) : "memory");
          float e[2];
#pragma unroll
          for (int k = 0; k < 2; k++) {
            const float u0 = ln & 1 ? c[1][2 * k] : c[0][2 * k], u1 = ln & 1 ? c[3][2 * k] : c[2][2 * k];
            const float u2 = ln & 1 ? c[5][2 * k] : c[4][2 * k], u3 = ln & 1 ? c[7][2 * k] : c[6][2 * k];
            e[k] = ln & 2 ? u1 + u3 : u0 + u2;
          }
          asm volatile("{\n.reg .pred p, q;\n.reg .f32 a, b;\n.reg .u32 t;\nshr.u32 t, %3, 30;\nsetp.eq.u32 p, t, 1;\nsetp.eq.u32 q, t, 2;\n"
                       "@p ld.shared.v2.f32 {a, b}, [%2];\n@p add.f32 %0, %0, a;\n@p add.f32 %1, %1, b;\n@q st.shared.v2.f32 [%2], {%0, %1};\n}\n"
                       : "+f"(e[0]), "+f"(e[1]) : "r"(carry), "r"(row) : "memory");
          asm volatile("{\n.reg .pred p;\nsetp.ge.s32 p, %2, 0;\n@p st.global.u32 [%0], %1;\n}\n"
                       :: "l"(reinterpret_cast<uint32_t*>(out) + (row * 32u + word)), "r"(pack_bf16(e[0], e[1])), "r"(row) : "memory");
        } else {
          const uint32_t stop = lds32(home + R_STOP);
          poll();
          if (stop == mine) mine = 0;
          if (!__any_sync(0xffffffffu, mine)) break;
          if (s0 < B) {
            if ((int)(due - (uint32_t)clock()) <= 0) { prefetch(); due += PF_SLOW; }
          } else if (++idle > 0x10000000) __trap();
        }
      }
    }
  }
}

}

extern "C" void kernel_launch(void* const* d_in, const int* in_sizes, int n_in, void* d_out, int out_size) {
  const __nv_bfloat16* target = (const __nv_bfloat16*)d_in[0];
  const __nv_bfloat16* hist = (const __nv_bfloat16*)d_in[1];
  const __nv_bfloat16* mask = (const __nv_bfloat16*)d_in[2];
  const __nv_bfloat16* w1 = (const __nv_bfloat16*)d_in[3];
  const __nv_bfloat16* b1 = (const __nv_bfloat16*)d_in[4];
  const __nv_bfloat16* w2 = (const __nv_bfloat16*)d_in[5];
  const __nv_bfloat16* b2 = (const __nv_bfloat16*)d_in[6];
  const int B = in_sizes[0] / din::kD;
  if (B <= 0) return;
  static int sms = 0, pace = 0;
  static unsigned int* counter = nullptr;
  if (sms == 0) {
    int dev = 0, khz = 0, bits = 0;
    cudaGetDevice(&dev);
    cudaDeviceGetAttribute(&sms, cudaDevAttrMultiProcessorCount, dev);
    cudaDeviceGetAttribute(&khz, cudaDevAttrMemoryClockRate, dev);
    cudaDeviceGetAttribute(&bits, cudaDevAttrGlobalMemoryBusWidth, dev);
    if (khz > 0 && bits > 0) pace = (int)(16.0 * 128.0 * sms / (khz * 1e-6 * 2.0 * bits / 8.0));
    if (pace > 256) pace = 0;
    cudaGetSymbolAddress((void**)&counter, din::g_next);
    cudaFuncSetAttribute(din::din_kernel, cudaFuncAttributeMaxDynamicSharedMemorySize, din::SMEM_BYTES);
  }
  const long long early = (long long)(din::NSTATIC * NCW + PF_EARLY * PF_ROWS) * sms, threads = (long long)din::NTHREADS * sms;
  long long pf_mask = (early * din::kL * 2 + threads - 1) / threads, pf_tgt = (early * din::kD * 2 + threads - 1) / threads;
  if (pf_mask > (long long)B * din::kL * 2 / threads) pf_mask = (long long)B * din::kL * 2 / threads;
  if (pf_tgt > (long long)B * din::kD * 2 / threads) pf_tgt = (long long)B * din::kD * 2 / threads;
  din::din_kernel<<<sms, din::NTHREADS, din::SMEM_BYTES>>>(mask, target, B, sms, (uint32_t)pf_mask, (uint32_t)pf_tgt,
                                                          w1, hist, b1, w2, b2, (__nv_bfloat16*)d_out, counter, pace,
                                                          B - SLOW_ROUNDS * NCW * sms / 2, pace * (160 + SLOW_BY) / 10,
                                                          pace * SPREAD / 16, pace * 16 * 256 * ALIGN / (100 * sms));
}
```
